```python
import torch

def _softmax(x, axis=-1):
    return torch.softmax(x, dim=axis)
def _gelu(x):
    return torch.nn.functional.gelu(x, approximate="tanh")
def _silu(x):
    return torch.nn.functional.silu(x)
def _sigmoid(x):
    return torch.sigmoid(x)
def _layernorm(x, axis=-1, eps=1e-5):
    m = x.mean(dim=axis, keepdim=True)
    v = x.var(dim=axis, keepdim=True, unbiased=False)
    return (x - m) / torch.sqrt(v + eps)
def _scatter_add(tgt, idx, src, axis=0):
    return tgt.clone().index_add_(axis, idx, src)
def _segment_sum(src, seg, n):
    out = torch.zeros((n,) + src.shape[1:], dtype=src.dtype)
    return out.index_add_(0, seg, src)
def _pad(x, pw):
    flat = tuple(v for pair in reversed(pw) for v in pair)
    return torch.nn.functional.pad(x, flat)

kernel_name = 'interleave_layers__softmax_full_mha__moe_arch_mod__prompt'

def setup_inputs():

    _w = (lambda a: (lambda t: t.to(torch.bfloat16) if t.is_floating_point() else t)(torch.as_tensor(a)))
    def _A_setup():
        B, S, D = 1, 2048, 1024
        return {
            "x": _w((lambda *s: torch.randn(*s, dtype=torch.bfloat16) * 0.05)(B, S, D)),
            "wqkv": _w((lambda *s: torch.randn(*s, dtype=torch.bfloat16) * 0.05)(D, 3 * D)),
            "wo": _w((lambda *s: torch.randn(*s, dtype=torch.bfloat16) * 0.05)(D, D)),
        }
    _A_in = _A_setup()

    def _B_setup():
        B, S, D, F, C = 1, 2048, 1024, 3584, 1
        return {
            "x": _w((lambda *s: torch.randn(*s, dtype=torch.bfloat16) * 0.05)(B, S, D)),
            "w_r": _w((lambda *s: torch.randn(*s, dtype=torch.bfloat16) * 0.05)(D)),
            "w_gate": _w((lambda *s: torch.randn(*s, dtype=torch.bfloat16) * 0.05)(D, F)),
            "w_up": _w((lambda *s: torch.randn(*s, dtype=torch.bfloat16) * 0.05)(D, F)),
            "w_down": _w((lambda *s: torch.randn(*s, dtype=torch.bfloat16) * 0.05)(F, D)),
        }
    _B_in = _B_setup()

    return {
        "A_x": _A_in["x"],
        "A_wqkv": _A_in["wqkv"],
        "A_wo": _A_in["wo"],
        "B_x": _B_in["x"],
        "B_w_r": _B_in["w_r"],
        "B_w_gate": _B_in["w_gate"],
        "B_w_up": _B_in["w_up"],
        "B_w_down": _B_in["w_down"],
    }

def reference(A_x, A_wqkv, A_wo, B_x, B_w_r, B_w_gate, B_w_up, B_w_down):
    def _A_ref(x, wqkv, wo):
        B, S, D = x.shape
        H = 32; Dh = D // H
        qkv = (lambda x, *d: x.permute(*d))((x @ wqkv).reshape(B, S, 3, H, Dh), 2, 0, 3, 1, 4)
        q, k, v = qkv[0], qkv[1], qkv[2]
        scale = Dh ** -0.5
        scores = torch.einsum("bhqd,bhkd->bhqk", q, k) * scale
        p = _softmax(scores, axis=-1)
        o = torch.einsum("bhqk,bhkd->bhqd", p, v)
        return (lambda x, *d: x.permute(*d))(o, 0, 2, 1, 3).reshape(B, S, D) @ wo

    def _B_ref(x, w_r, w_gate, w_up, w_down):
        B, S, D = x.shape
        C = 1
        r = x @ w_r
        idx = torch.argsort(-r, axis=-1)[:, :C]
        idx_e = (lambda x, n, axis: torch.repeat_interleave(x, n, dim=axis))(idx.reshape(B, C, 1), D, axis=2)
        x_sel = (lambda x, i, axis: torch.take_along_dim(x, i, dim=axis))(x, idx_e, axis=1)
        g = _silu(x_sel @ w_gate)
        u = x_sel @ w_up
        y = (g * u) @ w_down
        r_sel = _sigmoid((lambda x, i, axis: torch.take_along_dim(x, i, dim=axis))(r, idx, axis=1))
        y = y * r_sel.reshape(B, C, 1)
        b_off = (torch.arange(B) * S).reshape(B, 1)
        flat_idx = (idx + b_off).reshape(B * C)
        zero = (x * 0.0).reshape(B * S, D)
        upd = _scatter_add(zero, flat_idx, y.reshape(B * C, D), axis=0)
        return x + upd.reshape(B, S, D)

    x = A_x
    x = x + _A_ref(_layernorm(x, axis=-1), A_wqkv, A_wo)
    x = x + _B_ref(_layernorm(x, axis=-1), B_w_r, B_w_gate, B_w_up, B_w_down)
    x = x + _A_ref(_layernorm(x, axis=-1), A_wqkv, A_wo)
    x = x + _B_ref(_layernorm(x, axis=-1), B_w_r, B_w_gate, B_w_up, B_w_down)
    return x
```

```cpp
#include <cuda_runtime.h>
#include <cuda_bf16.h>
#include <cuda_fp16.h>
#include <cuda.h>
#include <cudaTypedefs.h>
#include <stdint.h>

namespace {

typedef __nv_bfloat16 bf16;

constexpr int S_ = 2048, D_ = 1024, NH = 32, FF = 3584, NFC = FF / 32;
constexpr float LN_EPS = 1e-5f;
constexpr float QSCALE = 0.17677669529663687f * 1.4426950408889634f;
constexpr uint32_t EMPTY = 0xFFFFFFFFu;

constexpr int KV_TILE = 16384;
__device__ __align__(1024) char g_kv[NH * 16 * KV_TILE];
__device__ __align__(1024) bf16 g_o[S_ * D_];
__device__ __align__(1024) bf16 g_x1[S_ * D_];
__device__ __align__(16) float g_csum[8][3 * D_];
__device__ __align__(16) float g_cssq[8][3 * D_];
__device__ __align__(16) float2 g_rs[2][S_];
__device__ __align__(16) uint4 g_part[2][16][8][128];
__device__ __align__(16) uint4 g_hdr[2][16];
__device__ __align__(16) uint32_t g_cand[2][16][D_ / 2];
__device__ __align__(16) float g_ypart[2][NFC][D_];
__device__ __align__(16) uint32_t g_x2row[D_ / 2];
__device__ __align__(16) float g_fix[3 * D_];
struct Flags {
    uint8_t kv[2][NH][8];
    uint32_t o[2][16][2];
    uint32_t x[8];
};
__device__ __align__(16) Flags g_fl;
__device__ uint32_t g_pctr;

constexpr uint32_t SMEM_BASE = 1024;

__device__ __forceinline__ int tid_now() { int v; asm volatile("mov.u32 %0, %%tid.x;" : "=r"(v)); return v; }
__device__ __forceinline__ int cta_now() { int v; asm volatile("mov.u32 %0, %%ctaid.x;" : "=r"(v)); return v; }
__device__ __forceinline__ uint64_t opaque(uint64_t v) { uint64_t r; asm volatile("mov.b64 %0, %1;" : "=l"(r) : "l"(v)); return r; }
__device__ __forceinline__ uint32_t smem_u32(const void* p) { return (uint32_t)__cvta_generic_to_shared(p); }
__device__ __forceinline__ void mbar_init(uint32_t bar, int cnt) { asm volatile("mbarrier.init.shared::cta.b64 [%0], %1;" :: "r"(bar), "r"(cnt) : "memory"); }
__device__ __forceinline__ void mbar_expect_tx(uint32_t bar, uint32_t bytes) { asm volatile("mbarrier.arrive.expect_tx.shared::cta.b64 _, [%0], %1;" :: "r"(bar), "r"(bytes) : "memory"); }
__device__ __forceinline__ void mbar_arrive(uint32_t bar) { asm volatile("mbarrier.arrive.shared::cta.b64 _, [%0];" :: "r"(bar) : "memory"); }
__device__ __forceinline__ void mbar_wait(uint32_t bar, uint32_t parity) {
    asm volatile("{\n.reg .pred p;\n.reg .u32 n;\n"
                 "mbarrier.try_wait.parity.shared::cta.b64 p, [%0], %1;\n@p bra LAB_DONE;\nmov.u32 n, 0;\n"
                 "LAB_WAIT:\nmbarrier.try_wait.parity.shared::cta.b64 p, [%0], %1, 0x989680;\n@p bra LAB_DONE;\n"
                 "add.u32 n, n, 1;\nsetp.lt.u32 p, n, 400;\n@p bra LAB_WAIT;\ntrap;\nLAB_DONE:\n}" :: "r"(bar), "r"(parity) : "memory");
}
__device__ __forceinline__ void mbar_arrive_elect(uint32_t bar) {
    asm volatile("{\n.reg .pred p;\nelect.sync _|p, 0xffffffff;\n@p mbarrier.arrive.shared::cta.b64 _, [%0];\n}" :: "r"(bar) : "memory");
}
__device__ __forceinline__ void mbar_arrive_elect_p(uint32_t bar, uint32_t on) {
    asm volatile("{\n.reg .pred p, q;\nelect.sync _|p, 0xffffffff;\nsetp.ne.and.u32 q, %1, 0, p;\n@q mbarrier.arrive.shared::cta.b64 _, [%0];\n}" :: "r"(bar), "r"(on) : "memory");
}
__device__ __forceinline__ int warp_uniform(int v) { return __shfl_sync(0xffffffffu, v, 0); }
__device__ __forceinline__ void fence_mbar_init() { asm volatile("fence.mbarrier_init.release.cluster;" ::: "memory"); }
__device__ __forceinline__ void fence_async_smem() { asm volatile("fence.proxy.async.shared::cta;" ::: "memory"); }
__device__ __forceinline__ void fence_async_global() { asm volatile("fence.proxy.async.global;" ::: "memory"); }
__device__ __forceinline__ void named_sync(int id, int n) { asm volatile("bar.sync %0, %1;" :: "r"(id), "r"(n) : "memory"); }
__device__ __forceinline__ void named_arrive(int id, int n) { asm volatile("bar.arrive %0, %1;" :: "r"(id), "r"(n) : "memory"); }
__device__ __forceinline__ void bulk_load(uint32_t dst, const void* src, uint32_t bytes, uint32_t bar) {
    asm volatile("cp.async.bulk.shared::cluster.global.mbarrier::complete_tx::bytes [%0], [%1], %2, [%3];" :: "r"(dst), "l"(src), "r"(bytes), "r"(bar) : "memory");
}
__device__ __forceinline__ void bulk_store(void* dst, uint32_t src, uint32_t bytes) {
    asm volatile("cp.async.bulk.global.shared::cta.bulk_group [%0], [%1], %2;" :: "l"(dst), "r"(src), "r"(bytes) : "memory");
}
__device__ __forceinline__ void bulk_commit() { asm volatile("cp.async.bulk.commit_group;" ::: "memory"); }
__device__ __forceinline__ void bulk_wait() { asm volatile("cp.async.bulk.wait_group 0;" ::: "memory"); }
__device__ __forceinline__ void l2_prefetch(const void* src, uint32_t bytes) {
    asm volatile("cp.async.bulk.prefetch.L2.global [%0], %1;" :: "l"(src), "r"(bytes) : "memory");
}
__device__ __forceinline__ void tma_load(uint32_t dst, const CUtensorMap* tm, int c0, int c1, uint32_t bar) {
    asm volatile("cp.async.bulk.tensor.2d.shared::cluster.global.mbarrier::complete_tx::bytes [%0], [%1, {%3, %4}], [%2];"
                 :: "r"(dst), "l"(tm), "r"(bar), "r"(c0), "r"(c1) : "memory");
}
__device__ __forceinline__ void tma_load3(uint32_t dst, const CUtensorMap* tm, int c0, int c1, int c2, uint32_t bar) {
    asm volatile("cp.async.bulk.tensor.3d.shared::cluster.global.mbarrier::complete_tx::bytes [%0], [%1, {%3, %4, %5}], [%2];"
                 :: "r"(dst), "l"(tm), "r"(bar), "r"(c0), "r"(c1), "r"(c2) : "memory");
}
__device__ __forceinline__ void tma_load5(uint32_t dst, const CUtensorMap* tm, int c0, int c4, uint32_t bar) {
    asm volatile("cp.async.bulk.tensor.5d.shared::cluster.global.mbarrier::complete_tx::bytes [%0], [%1, {%3, %5, %5, %5, %4}], [%2];"
                 :: "r"(dst), "l"(tm), "r"(bar), "r"(c0), "r"(c4), "r"(0) : "memory");
}
__device__ __forceinline__ void tma_prefetch(const CUtensorMap* tm, int c0, int c1) {
    asm volatile("cp.async.bulk.prefetch.tensor.2d.L2.global [%0, {%1, %2}];" :: "l"(tm), "r"(c0), "r"(c1) : "memory");
}
__device__ __forceinline__ void tm_prefetch(const CUtensorMap* tm) { asm volatile("prefetch.tensormap [%0];" :: "l"(tm) : "memory"); }
__device__ __forceinline__ void wg_fence() { asm volatile("wgmma.fence.sync.aligned;" ::: "memory"); }
__device__ __forceinline__ void wg_commit() { asm volatile("wgmma.commit_group.sync.aligned;" ::: "memory"); }
template <int N> __device__ __forceinline__ void wg_wait() { asm volatile("wgmma.wait_group.sync.aligned %0;" :: "n"(N) : "memory"); }
template <int N> __device__ __forceinline__ void pin(uint32_t (&r)[N]) {
    #pragma unroll
    for (int i = 0; i < N; i++) asm volatile("" : "+r"(r[i]) :: "memory");
}
template <int N> __device__ __forceinline__ void pin(float (&r)[N]) {
    #pragma unroll
    for (int i = 0; i < N; i++) asm volatile("" : "+f"(r[i]) :: "memory");
}
template <int N> __device__ __forceinline__ void reg_inc() { asm volatile("setmaxnreg.inc.sync.aligned.u32 %0;" :: "n"(N)); }
template <int N> __device__ __forceinline__ void reg_dec() { asm volatile("setmaxnreg.dec.sync.aligned.u32 %0;" :: "n"(N)); }
__host__ __device__ constexpr uint64_t desc_plain(uint32_t addr, uint32_t lbo, uint32_t sbo) {
    return (uint64_t)((addr & 0x3FFFF) >> 4) | ((uint64_t)(lbo >> 4) << 16) | ((uint64_t)(sbo >> 4) << 32);
}
__host__ __device__ constexpr uint64_t desc_sw128(uint32_t addr, uint32_t lbo, uint32_t sbo) { return desc_plain(addr, lbo, sbo) | (1ull << 62); }
__host__ __device__ constexpr uint64_t desc_sw64(uint32_t addr, uint32_t lbo, uint32_t sbo) { return desc_plain(addr, lbo, sbo) | (2ull << 62); }

__device__ __forceinline__ uint32_t lds32(uint32_t a) { uint32_t v; asm volatile("ld.shared.b32 %0, [%1];" : "=r"(v) : "r"(a) : "memory"); return v; }
__device__ __forceinline__ float ldsf(uint32_t a) { return __uint_as_float(lds32(a)); }
__device__ __forceinline__ float2 lds64f(uint32_t a) { float2 v; asm volatile("ld.shared.v2.f32 {%0, %1}, [%2];" : "=f"(v.x), "=f"(v.y) : "r"(a) : "memory"); return v; }
__device__ __forceinline__ uint4 lds128(uint32_t a) { uint4 v; asm volatile("ld.shared.v4.b32 {%0, %1, %2, %3}, [%4];" : "=r"(v.x), "=r"(v.y), "=r"(v.z), "=r"(v.w) : "r"(a) : "memory"); return v; }
__device__ __forceinline__ void sts16(uint32_t a, uint32_t v) { asm volatile("st.shared.b16 [%0], %1;" :: "r"(a), "h"((uint16_t)v) : "memory"); }
__device__ __forceinline__ void sts32(uint32_t a, uint32_t v) { asm volatile("st.shared.b32 [%0], %1;" :: "r"(a), "r"(v) : "memory"); }
__device__ __forceinline__ void stsf(uint32_t a, float v) { sts32(a, __float_as_uint(v)); }
__device__ __forceinline__ void sts64(uint32_t a, uint32_t x, uint32_t y) { asm volatile("st.shared.v2.b32 [%0], {%1, %2};" :: "r"(a), "r"(x), "r"(y) : "memory"); }
__device__ __forceinline__ void sts128(uint32_t a, uint32_t x, uint32_t y, uint32_t z, uint32_t w) { asm volatile("st.shared.v4.b32 [%0], {%1, %2, %3, %4};" :: "r"(a), "r"(x), "r"(y), "r"(z), "r"(w) : "memory"); }
__device__ __forceinline__ void stsm4(uint32_t a, uint32_t x, uint32_t y, uint32_t z, uint32_t w) {
    asm volatile("stmatrix.sync.aligned.m8n8.x4.shared.b16 [%0], {%1, %2, %3, %4};" :: "r"(a), "r"(x), "r"(y), "r"(z), "r"(w) : "memory");
}
__device__ __forceinline__ void ldsm4(uint32_t& a0, uint32_t& a1, uint32_t& a2, uint32_t& a3, uint32_t addr) {
    asm volatile("ldmatrix.sync.aligned.m8n8.x4.shared.b16 {%0,%1,%2,%3}, [%4];" : "=r"(a0), "=r"(a1), "=r"(a2), "=r"(a3) : "r"(addr) : "memory");
}
__device__ __forceinline__ void ldsm4t(uint32_t& a0, uint32_t& a1, uint32_t& a2, uint32_t& a3, uint32_t addr) {
    asm volatile("ldmatrix.sync.aligned.m8n8.x4.trans.shared.b16 {%0,%1,%2,%3}, [%4];" : "=r"(a0), "=r"(a1), "=r"(a2), "=r"(a3) : "r"(addr) : "memory");
}
__device__ __forceinline__ void mma_bf16(float (&d)[4], uint32_t a0, uint32_t a1, uint32_t a2, uint32_t a3, uint32_t b0, uint32_t b1) {
    asm("mma.sync.aligned.m16n8k16.row.col.f32.bf16.bf16.f32 {%0,%1,%2,%3}, {%4,%5,%6,%7}, {%8,%9}, {%0,%1,%2,%3};"
        : "+f"(d[0]), "+f"(d[1]), "+f"(d[2]), "+f"(d[3]) : "r"(a0), "r"(a1), "r"(a2), "r"(a3), "r"(b0), "r"(b1));
}
__device__ __forceinline__ void mma_f16(float (&d)[4], uint32_t a0, uint32_t a1, uint32_t a2, uint32_t a3, uint32_t b0, uint32_t b1) {
    asm("mma.sync.aligned.m16n8k16.row.col.f32.f16.f16.f32 {%0,%1,%2,%3}, {%4,%5,%6,%7}, {%8,%9}, {%0,%1,%2,%3};"
        : "+f"(d[0]), "+f"(d[1]), "+f"(d[2]), "+f"(d[3]) : "r"(a0), "r"(a1), "r"(a2), "r"(a3), "r"(b0), "r"(b1));
}
__device__ __forceinline__ void stg128_pred(void* p, const uint4& v, bool on) {
    asm volatile("{\n.reg .pred q;\nsetp.ne.u32 q, %5, 0;\n@q st.global.v4.b32 [%0], {%1, %2, %3, %4};\n}"
                 :: "l"(p), "r"(v.x), "r"(v.y), "r"(v.z), "r"(v.w), "r"((uint32_t)on) : "memory");
}
__device__ __forceinline__ void st_x32(void* p, uint32_t v) { asm volatile("st.relaxed.gpu.global.u32 [%0], %1;" :: "l"(p), "r"(v) : "memory"); }
__device__ __forceinline__ void st_x64(void* p, uint32_t x, uint32_t y) {
    asm volatile("{\n.reg .b64 v;\nmov.b64 v, {%1, %2};\nst.relaxed.gpu.global.b64 [%0], v;\n}" :: "l"(p), "r"(x), "r"(y) : "memory");
}
__device__ __forceinline__ void st_x128(void* p, uint32_t x, uint32_t y, uint32_t z, uint32_t w) {
    asm volatile("{\n.reg .b64 a, b;\n.reg .b128 v;\nmov.b64 a, {%1, %2};\nmov.b64 b, {%3, %4};\nmov.b128 v, {a, b};\nst.relaxed.gpu.global.b128 [%0], v;\n}"
                 :: "l"(p), "r"(x), "r"(y), "r"(z), "r"(w) : "memory");
}
__device__ __forceinline__ uint32_t ld_x32(const void* p) { uint32_t v; asm volatile("ld.relaxed.gpu.global.u32 %0, [%1];" : "=r"(v) : "l"(p) : "memory"); return v; }
__device__ __forceinline__ uint2 ld_x64(const void* p) {
    uint2 v; asm volatile("{\n.reg .b64 a;\nld.relaxed.gpu.global.b64 a, [%2];\nmov.b64 {%0, %1}, a;\n}" : "=r"(v.x), "=r"(v.y) : "l"(p) : "memory"); return v;
}
__device__ __forceinline__ uint4 ld_x128(const void* p) {
    uint4 v;
    asm volatile("{\n.reg .b64 a, b;\n.reg .b128 v;\nld.relaxed.gpu.global.b128 v, [%4];\nmov.b128 {a, b}, v;\nmov.b64 {%0, %1}, a;\nmov.b64 {%2, %3}, b;\n}"
                 : "=r"(v.x), "=r"(v.y), "=r"(v.z), "=r"(v.w) : "l"(p) : "memory");
    return v;
}
__device__ __forceinline__ void poll_tick(uint32_t& n) { asm volatile("{\n.reg .pred p;\nadd.u32 %0, %0, 1;\nsetp.ge.u32 p, %0, 0x800000;\n@p st.global.u32 [%1], %0;\n}" : "+r"(n) : "l"(0ull)); }
__device__ __forceinline__ void ctr_arrive(uint32_t* c) { asm volatile("red.release.gpu.global.add.u32 [%0], 1;" :: "l"(c) : "memory"); }
__device__ __forceinline__ void ctr_wait(const uint32_t* c, uint32_t target) {
    uint32_t v, n = 0;
    while (true) {
        asm volatile("ld.acquire.gpu.global.u32 %0, [%1];" : "=r"(v) : "l"(c) : "memory");
        if (v >= target) break;
        poll_tick(n);
    }
}

__device__ __forceinline__ float ex2(float x) { float y; asm("ex2.approx.ftz.f32 %0, %1;" : "=f"(y) : "f"(x)); return y; }
__device__ __forceinline__ float rcp(float x) { float y; asm("rcp.approx.ftz.f32 %0, %1;" : "=f"(y) : "f"(x)); return y; }
__device__ __forceinline__ uint32_t pack_bf16(float lo, float hi) { uint32_t r; asm("cvt.rn.bf16x2.f32 %0, %1, %2;" : "=r"(r) : "f"(hi), "f"(lo)); return r; }
__device__ __forceinline__ uint32_t pack_f16(float lo, float hi) { uint32_t r; asm("cvt.rn.f16x2.f32 %0, %1, %2;" : "=r"(r) : "f"(hi), "f"(lo)); return r; }
__device__ __forceinline__ float bf_lo(uint32_t v) { return __uint_as_float(v << 16); }
__device__ __forceinline__ float bf_hi(uint32_t v) { return __uint_as_float(v & 0xFFFF0000u); }
__device__ __forceinline__ float bf_round(float x) { return __uint_as_float(pack_bf16(0.f, x)); }
__device__ __forceinline__ void h2_unpack(uint32_t v, float& lo, float& hi) {
    asm("{.reg .f16 l, h; mov.b32 {l, h}, %2; cvt.f32.f16 %0, l; cvt.f32.f16 %1, h;}" : "=f"(lo), "=f"(hi) : "r"(v));
}
__device__ __forceinline__ uint32_t hadd2(uint32_t a, uint32_t b) { uint32_t r; asm("add.rn.f16x2 %0, %1, %2;" : "=r"(r) : "r"(a), "r"(b)); return r; }
__device__ __forceinline__ uint32_t hmax2(uint32_t a, uint32_t b) { uint32_t r; asm("max.f16x2 %0, %1, %2;" : "=r"(r) : "r"(a), "r"(b)); return r; }
__device__ __forceinline__ uint32_t badd2(uint32_t a, uint32_t b) { uint32_t r; asm("add.rn.bf16x2 %0, %1, %2;" : "=r"(r) : "r"(a), "r"(b)); return r; }
__device__ __forceinline__ float warp_sum(float v) {
    #pragma unroll
    for (int o = 16; o > 0; o >>= 1) v += __shfl_xor_sync(0xffffffffu, v, o);
    return v;
}
__device__ __forceinline__ float quad_sum(float v) { v += __shfl_xor_sync(0xffffffffu, v, 1); return v + __shfl_xor_sync(0xffffffffu, v, 2); }
__device__ __forceinline__ float quad_max(float v) { v = fmaxf(v, __shfl_xor_sync(0xffffffffu, v, 1)); return fmaxf(v, __shfl_xor_sync(0xffffffffu, v, 2)); }
__device__ __forceinline__ uint32_t redux_max(uint32_t v) { uint32_t r; asm volatile("redux.sync.max.u32 %0, %1, 0xffffffff;" : "=r"(r) : "r"(v)); return r; }
__device__ __forceinline__ uint32_t redux_min(uint32_t v) { uint32_t r; asm volatile("redux.sync.min.u32 %0, %1, 0xffffffff;" : "=r"(r) : "r"(v)); return r; }
__device__ __forceinline__ uint32_t order_bits(float r) { const uint32_t u = __float_as_uint(r); return (u & 0x80000000u) ? ~u : (u | 0x80000000u); }
__device__ __forceinline__ uint32_t add_ln2(uint32_t v, float mean, float rstd) {
    return badd2(v, pack_bf16((bf_lo(v) - mean) * rstd, (bf_hi(v) - mean) * rstd));
}

#define TL(i)

__device__ __forceinline__ void wg_gemm_n128(float (&d)[64], uint64_t desca, uint64_t desc) {
    asm volatile("{\n.reg .pred p;\nsetp.ne.b32 p, 1, 0;\n"
        "wgmma.mma_async.sync.aligned.m64n128k16.f32.bf16.bf16 "
        "{%0,%1,%2,%3,%4,%5,%6,%7,%8,%9,%10,%11,%12,%13,%14,%15,%16,%17,%18,%19,%20,%21,%22,%23,%24,%25,%26,%27,%28,%29,%30,%31,%32,%33,%34,%35,%36,%37,%38,%39,%40,%41,%42,%43,%44,%45,%46,%47,%48,%49,%50,%51,%52,%53,%54,%55,%56,%57,%58,%59,%60,%61,%62,%63}, "
        "%64, %65, p, 1, 1, 0, 1;\n}\n"
        : "+f"(d[0]), "+f"(d[1]), "+f"(d[2]), "+f"(d[3]), "+f"(d[4]), "+f"(d[5]), "+f"(d[6]), "+f"(d[7]), "+f"(d[8]), "+f"(d[9]), "+f"(d[10]), "+f"(d[11]),
          "+f"(d[12]), "+f"(d[13]), "+f"(d[14]), "+f"(d[15]), "+f"(d[16]), "+f"(d[17]), "+f"(d[18]), "+f"(d[19]), "+f"(d[20]), "+f"(d[21]), "+f"(d[22]), "+f"(d[23]),
          "+f"(d[24]), "+f"(d[25]), "+f"(d[26]), "+f"(d[27]), "+f"(d[28]), "+f"(d[29]), "+f"(d[30]), "+f"(d[31]), "+f"(d[32]), "+f"(d[33]), "+f"(d[34]), "+f"(d[35]),
          "+f"(d[36]), "+f"(d[37]), "+f"(d[38]), "+f"(d[39]), "+f"(d[40]), "+f"(d[41]), "+f"(d[42]), "+f"(d[43]), "+f"(d[44]), "+f"(d[45]), "+f"(d[46]), "+f"(d[47]),
          "+f"(d[48]), "+f"(d[49]), "+f"(d[50]), "+f"(d[51]), "+f"(d[52]), "+f"(d[53]), "+f"(d[54]), "+f"(d[55]), "+f"(d[56]), "+f"(d[57]), "+f"(d[58]), "+f"(d[59]),
          "+f"(d[60]), "+f"(d[61]), "+f"(d[62]), "+f"(d[63])
        : "l"(desca), "l"(desc));
}
__device__ __forceinline__ void wg_gemm_n128_init(float (&d)[64], uint64_t desca, uint64_t desc) {
    asm volatile("{\n.reg .pred p;\nsetp.ne.b32 p, 0, 0;\n"
        "wgmma.mma_async.sync.aligned.m64n128k16.f32.bf16.bf16 "
        "{%0,%1,%2,%3,%4,%5,%6,%7,%8,%9,%10,%11,%12,%13,%14,%15,%16,%17,%18,%19,%20,%21,%22,%23,%24,%25,%26,%27,%28,%29,%30,%31,%32,%33,%34,%35,%36,%37,%38,%39,%40,%41,%42,%43,%44,%45,%46,%47,%48,%49,%50,%51,%52,%53,%54,%55,%56,%57,%58,%59,%60,%61,%62,%63}, "
        "%64, %65, p, 1, 1, 0, 1;\n}\n"
        : "=f"(d[0]), "=f"(d[1]), "=f"(d[2]), "=f"(d[3]), "=f"(d[4]), "=f"(d[5]), "=f"(d[6]), "=f"(d[7]), "=f"(d[8]), "=f"(d[9]), "=f"(d[10]), "=f"(d[11]),
          "=f"(d[12]), "=f"(d[13]), "=f"(d[14]), "=f"(d[15]), "=f"(d[16]), "=f"(d[17]), "=f"(d[18]), "=f"(d[19]), "=f"(d[20]), "=f"(d[21]), "=f"(d[22]), "=f"(d[23]),
          "=f"(d[24]), "=f"(d[25]), "=f"(d[26]), "=f"(d[27]), "=f"(d[28]), "=f"(d[29]), "=f"(d[30]), "=f"(d[31]), "=f"(d[32]), "=f"(d[33]), "=f"(d[34]), "=f"(d[35]),
          "=f"(d[36]), "=f"(d[37]), "=f"(d[38]), "=f"(d[39]), "=f"(d[40]), "=f"(d[41]), "=f"(d[42]), "=f"(d[43]), "=f"(d[44]), "=f"(d[45]), "=f"(d[46]), "=f"(d[47]),
          "=f"(d[48]), "=f"(d[49]), "=f"(d[50]), "=f"(d[51]), "=f"(d[52]), "=f"(d[53]), "=f"(d[54]), "=f"(d[55]), "=f"(d[56]), "=f"(d[57]), "=f"(d[58]), "=f"(d[59]),
          "=f"(d[60]), "=f"(d[61]), "=f"(d[62]), "=f"(d[63])
        : "l"(desca), "l"(desc));
}
__device__ __forceinline__ void wg_gemm_n192(float (&d)[96], uint64_t desca, uint64_t desc) {
    asm volatile("{\n.reg .pred p;\nsetp.ne.b32 p, 1, 0;\n"
        "wgmma.mma_async.sync.aligned.m64n192k16.f32.bf16.bf16 "
        "{%0,%1,%2,%3,%4,%5,%6,%7,%8,%9,%10,%11,%12,%13,%14,%15,%16,%17,%18,%19,%20,%21,%22,%23,%24,%25,%26,%27,%28,%29,%30,%31,%32,%33,%34,%35,%36,%37,%38,%39,%40,%41,%42,%43,%44,%45,%46,%47,%48,%49,%50,%51,%52,%53,%54,%55,%56,%57,%58,%59,%60,%61,%62,%63,%64,%65,%66,%67,%68,%69,%70,%71,%72,%73,%74,%75,%76,%77,%78,%79,%80,%81,%82,%83,%84,%85,%86,%87,%88,%89,%90,%91,%92,%93,%94,%95}, "
        "%96, %97, p, 1, 1, 0, 1;\n}\n"
        : "+f"(d[0]), "+f"(d[1]), "+f"(d[2]), "+f"(d[3]), "+f"(d[4]), "+f"(d[5]), "+f"(d[6]), "+f"(d[7]), "+f"(d[8]), "+f"(d[9]), "+f"(d[10]), "+f"(d[11]),
          "+f"(d[12]), "+f"(d[13]), "+f"(d[14]), "+f"(d[15]), "+f"(d[16]), "+f"(d[17]), "+f"(d[18]), "+f"(d[19]), "+f"(d[20]), "+f"(d[21]), "+f"(d[22]), "+f"(d[23]),
          "+f"(d[24]), "+f"(d[25]), "+f"(d[26]), "+f"(d[27]), "+f"(d[28]), "+f"(d[29]), "+f"(d[30]), "+f"(d[31]), "+f"(d[32]), "+f"(d[33]), "+f"(d[34]), "+f"(d[35]),
          "+f"(d[36]), "+f"(d[37]), "+f"(d[38]), "+f"(d[39]), "+f"(d[40]), "+f"(d[41]), "+f"(d[42]), "+f"(d[43]), "+f"(d[44]), "+f"(d[45]), "+f"(d[46]), "+f"(d[47]),
          "+f"(d[48]), "+f"(d[49]), "+f"(d[50]), "+f"(d[51]), "+f"(d[52]), "+f"(d[53]), "+f"(d[54]), "+f"(d[55]), "+f"(d[56]), "+f"(d[57]), "+f"(d[58]), "+f"(d[59]),
          "+f"(d[60]), "+f"(d[61]), "+f"(d[62]), "+f"(d[63]), "+f"(d[64]), "+f"(d[65]), "+f"(d[66]), "+f"(d[67]), "+f"(d[68]), "+f"(d[69]), "+f"(d[70]), "+f"(d[71]),
          "+f"(d[72]), "+f"(d[73]), "+f"(d[74]), "+f"(d[75]), "+f"(d[76]), "+f"(d[77]), "+f"(d[78]), "+f"(d[79]), "+f"(d[80]), "+f"(d[81]), "+f"(d[82]), "+f"(d[83]),
          "+f"(d[84]), "+f"(d[85]), "+f"(d[86]), "+f"(d[87]), "+f"(d[88]), "+f"(d[89]), "+f"(d[90]), "+f"(d[91]), "+f"(d[92]), "+f"(d[93]), "+f"(d[94]), "+f"(d[95])
        : "l"(desca), "l"(desc));
}
__device__ __forceinline__ void wg_gemm_n192_init(float (&d)[96], uint64_t desca, uint64_t desc) {
    asm volatile("{\n.reg .pred p;\nsetp.ne.b32 p, 0, 0;\n"
        "wgmma.mma_async.sync.aligned.m64n192k16.f32.bf16.bf16 "
        "{%0,%1,%2,%3,%4,%5,%6,%7,%8,%9,%10,%11,%12,%13,%14,%15,%16,%17,%18,%19,%20,%21,%22,%23,%24,%25,%26,%27,%28,%29,%30,%31,%32,%33,%34,%35,%36,%37,%38,%39,%40,%41,%42,%43,%44,%45,%46,%47,%48,%49,%50,%51,%52,%53,%54,%55,%56,%57,%58,%59,%60,%61,%62,%63,%64,%65,%66,%67,%68,%69,%70,%71,%72,%73,%74,%75,%76,%77,%78,%79,%80,%81,%82,%83,%84,%85,%86,%87,%88,%89,%90,%91,%92,%93,%94,%95}, "
        "%96, %97, p, 1, 1, 0, 1;\n}\n"
        : "=f"(d[0]), "=f"(d[1]), "=f"(d[2]), "=f"(d[3]), "=f"(d[4]), "=f"(d[5]), "=f"(d[6]), "=f"(d[7]), "=f"(d[8]), "=f"(d[9]), "=f"(d[10]), "=f"(d[11]),
          "=f"(d[12]), "=f"(d[13]), "=f"(d[14]), "=f"(d[15]), "=f"(d[16]), "=f"(d[17]), "=f"(d[18]), "=f"(d[19]), "=f"(d[20]), "=f"(d[21]), "=f"(d[22]), "=f"(d[23]),
          "=f"(d[24]), "=f"(d[25]), "=f"(d[26]), "=f"(d[27]), "=f"(d[28]), "=f"(d[29]), "=f"(d[30]), "=f"(d[31]), "=f"(d[32]), "=f"(d[33]), "=f"(d[34]), "=f"(d[35]),
          "=f"(d[36]), "=f"(d[37]), "=f"(d[38]), "=f"(d[39]), "=f"(d[40]), "=f"(d[41]), "=f"(d[42]), "=f"(d[43]), "=f"(d[44]), "=f"(d[45]), "=f"(d[46]), "=f"(d[47]),
          "=f"(d[48]), "=f"(d[49]), "=f"(d[50]), "=f"(d[51]), "=f"(d[52]), "=f"(d[53]), "=f"(d[54]), "=f"(d[55]), "=f"(d[56]), "=f"(d[57]), "=f"(d[58]), "=f"(d[59]),
          "=f"(d[60]), "=f"(d[61]), "=f"(d[62]), "=f"(d[63]), "=f"(d[64]), "=f"(d[65]), "=f"(d[66]), "=f"(d[67]), "=f"(d[68]), "=f"(d[69]), "=f"(d[70]), "=f"(d[71]),
          "=f"(d[72]), "=f"(d[73]), "=f"(d[74]), "=f"(d[75]), "=f"(d[76]), "=f"(d[77]), "=f"(d[78]), "=f"(d[79]), "=f"(d[80]), "=f"(d[81]), "=f"(d[82]), "=f"(d[83]),
          "=f"(d[84]), "=f"(d[85]), "=f"(d[86]), "=f"(d[87]), "=f"(d[88]), "=f"(d[89]), "=f"(d[90]), "=f"(d[91]), "=f"(d[92]), "=f"(d[93]), "=f"(d[94]), "=f"(d[95])
        : "l"(desca), "l"(desc));
}
__device__ __forceinline__ void wg_qk_init(uint32_t (&d)[32], uint32_t a0, uint32_t a1, uint32_t a2, uint32_t a3, uint64_t desc) {
    asm volatile("{\n.reg .pred p;\nsetp.ne.b32 p, 0, 0;\n"
        "wgmma.mma_async.sync.aligned.m64n128k16.f16.f16.f16 "
        "{%0,%1,%2,%3,%4,%5,%6,%7,%8,%9,%10,%11,%12,%13,%14,%15,%16,%17,%18,%19,%20,%21,%22,%23,%24,%25,%26,%27,%28,%29,%30,%31}, "
        "{%32,%33,%34,%35}, %36, p, 1, 1, 0;\n}\n"
        : "=r"(d[0]), "=r"(d[1]), "=r"(d[2]), "=r"(d[3]), "=r"(d[4]), "=r"(d[5]), "=r"(d[6]), "=r"(d[7]), "=r"(d[8]), "=r"(d[9]), "=r"(d[10]), "=r"(d[11]),
          "=r"(d[12]), "=r"(d[13]), "=r"(d[14]), "=r"(d[15]), "=r"(d[16]), "=r"(d[17]), "=r"(d[18]), "=r"(d[19]), "=r"(d[20]), "=r"(d[21]), "=r"(d[22]), "=r"(d[23]),
          "=r"(d[24]), "=r"(d[25]), "=r"(d[26]), "=r"(d[27]), "=r"(d[28]), "=r"(d[29]), "=r"(d[30]), "=r"(d[31])
        : "r"(a0), "r"(a1), "r"(a2), "r"(a3), "l"(desc));
}
__device__ __forceinline__ void wg_qk_acc(uint32_t (&d)[32], uint32_t a0, uint32_t a1, uint32_t a2, uint32_t a3, uint64_t desc) {
    asm volatile("{\n.reg .pred p;\nsetp.ne.b32 p, 1, 0;\n"
        "wgmma.mma_async.sync.aligned.m64n128k16.f16.f16.f16 "
        "{%0,%1,%2,%3,%4,%5,%6,%7,%8,%9,%10,%11,%12,%13,%14,%15,%16,%17,%18,%19,%20,%21,%22,%23,%24,%25,%26,%27,%28,%29,%30,%31}, "
        "{%32,%33,%34,%35}, %36, p, 1, 1, 0;\n}\n"
        : "+r"(d[0]), "+r"(d[1]), "+r"(d[2]), "+r"(d[3]), "+r"(d[4]), "+r"(d[5]), "+r"(d[6]), "+r"(d[7]), "+r"(d[8]), "+r"(d[9]), "+r"(d[10]), "+r"(d[11]),
          "+r"(d[12]), "+r"(d[13]), "+r"(d[14]), "+r"(d[15]), "+r"(d[16]), "+r"(d[17]), "+r"(d[18]), "+r"(d[19]), "+r"(d[20]), "+r"(d[21]), "+r"(d[22]), "+r"(d[23]),
          "+r"(d[24]), "+r"(d[25]), "+r"(d[26]), "+r"(d[27]), "+r"(d[28]), "+r"(d[29]), "+r"(d[30]), "+r"(d[31])
        : "r"(a0), "r"(a1), "r"(a2), "r"(a3), "l"(desc));
}
__device__ __forceinline__ void wg_pv_init(uint32_t (&d)[10], uint32_t a0, uint32_t a1, uint32_t a2, uint32_t a3, uint64_t desc) {
    asm volatile("{\n.reg .pred p;\nsetp.ne.b32 p, 0, 0;\n"
        "wgmma.mma_async.sync.aligned.m64n40k16.f16.f16.f16 "
        "{%0,%1,%2,%3,%4,%5,%6,%7,%8,%9}, "
        "{%10,%11,%12,%13}, %14, p, 1, 1, 1;\n}\n"
        : "=r"(d[0]), "=r"(d[1]), "=r"(d[2]), "=r"(d[3]), "=r"(d[4]), "=r"(d[5]), "=r"(d[6]), "=r"(d[7]), "=r"(d[8]), "=r"(d[9])
        : "r"(a0), "r"(a1), "r"(a2), "r"(a3), "l"(desc));
}
__device__ __forceinline__ void wg_pv_acc(uint32_t (&d)[10], uint32_t a0, uint32_t a1, uint32_t a2, uint32_t a3, uint64_t desc) {
    asm volatile("{\n.reg .pred p;\nsetp.ne.b32 p, 1, 0;\n"
        "wgmma.mma_async.sync.aligned.m64n40k16.f16.f16.f16 "
        "{%0,%1,%2,%3,%4,%5,%6,%7,%8,%9}, "
        "{%10,%11,%12,%13}, %14, p, 1, 1, 1;\n}\n"
        : "+r"(d[0]), "+r"(d[1]), "+r"(d[2]), "+r"(d[3]), "+r"(d[4]), "+r"(d[5]), "+r"(d[6]), "+r"(d[7]), "+r"(d[8]), "+r"(d[9])
        : "r"(a0), "r"(a1), "r"(a2), "r"(a3), "l"(desc));
}
__device__ __forceinline__ void wg_gemv_init(float (&d)[4], uint64_t desca, uint64_t desc) {
    asm volatile("{\n.reg .pred p;\nsetp.ne.b32 p, 0, 0;\n"
        "wgmma.mma_async.sync.aligned.m64n8k16.f32.bf16.bf16 "
        "{%0,%1,%2,%3}, "
        "%4, %5, p, 1, 1, 1, 0;\n}\n"
        : "=f"(d[0]), "=f"(d[1]), "=f"(d[2]), "=f"(d[3])
        : "l"(desca), "l"(desc));
}
__device__ __forceinline__ void wg_gemv_acc(float (&d)[4], uint64_t desca, uint64_t desc) {
    asm volatile("{\n.reg .pred p;\nsetp.ne.b32 p, 1, 0;\n"
        "wgmma.mma_async.sync.aligned.m64n8k16.f32.bf16.bf16 "
        "{%0,%1,%2,%3}, "
        "%4, %5, p, 1, 1, 1, 0;\n}\n"
        : "+f"(d[0]), "+f"(d[1]), "+f"(d[2]), "+f"(d[3])
        : "l"(desca), "l"(desc));
}

constexpr uint32_t SB = SMEM_BASE;
constexpr uint32_t R_SLOT = 18432, A_RING = SB, A_KP = SB + 73728, A_STB = SB + 81920, A_QX = SB + 212992;
__host__ __device__ constexpr uint32_t o_stage(uint32_t s) { return SB + (s < 2 ? 81920 + s * 32768 : (s - 2) * 32768); }
constexpr uint32_t XT0 = SB + 65536, XT1 = A_QX;
constexpr uint32_t F_GU0 = SB + 147456, F_GU1 = SB + 81920, F_WD = SB;
constexpr uint32_t Q_ABYTES = 256 * 64 * 2, Q_STB = Q_ABYTES + 192 * 64 * 2;
constexpr uint32_t Q_CS = SB + 3 * Q_STB, Q_VS = Q_CS + 768, Q_RC = Q_VS + 256, Q_FIX = Q_RC + 2048;
constexpr uint32_t SD_VEC = SB + 176128, SD_W = SB + 180224;
static_assert(Q_FIX + 768 <= SD_VEC, "smem");
constexpr uint32_t M_XS = SB + 229376, M_BAR = M_XS + 2048, BAR_SET = 320, M_IVS = M_BAR + 2 * BAR_SET, M_SM = M_IVS + 128;
constexpr uint32_t M_F2 = M_SM;
constexpr uint32_t M_WS = M_SM + 16;
constexpr uint32_t M_RT = M_SM + 32;
constexpr uint32_t M_KR = M_SM + 64;
constexpr uint32_t M_SR = M_SM + 128;
constexpr int K_SMEM = M_SR + 128 - SB;
static_assert(K_SMEM == 232448, "smem");
constexpr uint32_t B_QF = 0, B_QE = 24, B_EPI = 48, B_KVA = 56, B_KVB = 64, B_ARD = 72, B_BRD = 80, B_AF = 88, B_AE = 120, B_OD = 152,
                   B_OF = 184, B_OE = 216, B_RES = 248, B_GU0 = 256, B_GU1 = 264, B_WD = 272, B_FG = 280, B_FD = 288, B_XS = 296, B_SW = 304;
constexpr int NB_ML = 1, NB_STG = 2, NB_CONS = 3, NB_SIDE = 4, NB_WG = 5;

struct Maps { CUtensorMap x[2], wqkv, o, wo[2], r, g, u, d; };
struct Route { float r, mean, rstd; int idx; };

__device__ __forceinline__ void reset_exchange(int tid) {
    const int c = blockIdx.x, blk = c >> 3, cb = c & 7, l = tid >> 7, i = tid & 127;
    const uint4 e4 = make_uint4(EMPTY, EMPTY, EMPTY, EMPTY), z4 = make_uint4(0u, 0u, 0u, 0u);
    g_part[l][blk][cb][i] = z4;
    if (c < NFC) { reinterpret_cast<uint4*>(g_ypart[l][c])[i] = e4; reinterpret_cast<uint4*>(g_ypart[l][c])[i + 128] = e4; }
    if (i < 16) reinterpret_cast<uint4*>(&g_cand[l][blk][cb * 64])[i] = e4;
    if (i == 16 && cb == 0) g_hdr[l][blk] = z4;
    if (tid >= 32 && tid < 38) reinterpret_cast<uint4*>(g_fix + c * 24)[tid - 32] = e4;
    if (tid == 38) reinterpret_cast<uint4*>(g_x2row)[c] = e4;
    if (c == 0 && tid >= 64 && tid < 64 + (int)sizeof(Flags) / 16) reinterpret_cast<uint4*>(&g_fl)[tid - 64] = z4;
}
template <int N>
__device__ __forceinline__ void halve(float (&v)[8], int lane, int bit) {
    const bool up = lane & bit;
    #pragma unroll
    for (int i = 0; i < N; i++) v[i] = (up ? v[N + i] : v[i]) + __shfl_xor_sync(0xffffffffu, up ? v[i] : v[N + i], bit);
}

__device__ __forceinline__ void prep_work(const bf16* __restrict__ x0, const bf16* __restrict__ w_r, uint32_t lb) {
    const int t = tid_now() - 288, c = cta_now(), lane = t & 31, warp = t >> 5;
    mbar_wait(lb + B_QF, 0);
    #pragma unroll 1
    for (int r = warp; r < 17; r += 3) {
        const uint4* xp = reinterpret_cast<const uint4*>(r < 16 ? x0 + (size_t)(c * 16 + r) * D_ : w_r) + lane;
        uint4 u[4];
        #pragma unroll
        for (int j = 0; j < 4; j++) u[j] = __ldg(xp + j * 32);
        float s0 = 0.f, s1 = 0.f, q0 = 0.f, q1 = 0.f;
        #pragma unroll
        for (int j = 0; j < 4; j++) {
            const uint32_t w[4] = {u[j].x, u[j].y, u[j].z, u[j].w};
            #pragma unroll
            for (int e = 0; e < 4; e++) { const float a = bf_lo(w[e]), b = bf_hi(w[e]); s0 += a; s1 += b; q0 = fmaf(a, a, q0); q1 = fmaf(b, b, q1); }
        }
        s0 += s1; q0 += q1;
        float v = (lane & 16 ? q0 : s0) + __shfl_xor_sync(0xffffffffu, lane & 16 ? s0 : q0, 16);
        #pragma unroll
        for (int o = 8; o > 0; o >>= 1) v += __shfl_xor_sync(0xffffffffu, v, o);
        const float mean = v * (1.f / D_), sq = __shfl_xor_sync(0xffffffffu, mean, 16);
        if (lane == 0) {
            if (r < 16) g_rs[0][c * 16 + r] = make_float2(fmaxf(sq - mean * mean, 0.f), mean);
            else stsf(M_WS, v);
        }
    }
    if (t == 0) TL(22);
    mbar_wait(lb + B_SW, 0);
    {
        float cs[8], cq[8];
        #pragma unroll
        for (int i = 0; i < 8; i++) { cs[i] = 0.f; cq[i] = 0.f; }
        const uint32_t wb = SD_W + warp * 16384 + (lane >> 3) * 128;
        #pragma unroll 2
        for (int r = 0; r < 32; r++) {
            const uint4 u = lds128(wb + r * 512 + (((lane & 7) ^ ((r * 4 + (lane >> 3)) & 7)) << 4));
            const uint32_t w[4] = {u.x, u.y, u.z, u.w};
            #pragma unroll
            for (int e = 0; e < 4; e++) {
                const float a = bf_lo(w[e]), b = bf_hi(w[e]);
                cs[2*e] += a; cs[2*e+1] += b; cq[2*e] = fmaf(a, a, cq[2*e]); cq[2*e+1] = fmaf(b, b, cq[2*e+1]);
            }
        }
        halve<4>(cs, lane, 16); halve<2>(cs, lane, 8);
        halve<4>(cq, lane, 16); halve<2>(cq, lane, 8);
        const int col = warp * D_ + (c & 15) * 64 + (lane & 7) * 8 + (lane >> 3) * 2;
        *reinterpret_cast<float2*>(&g_csum[c >> 4][col]) = make_float2(cs[0], cs[1]);
        *reinterpret_cast<float2*>(&g_cssq[c >> 4][col]) = make_float2(cq[0], cq[1]);
    }
    named_sync(NB_SIDE, 96);
    if (t == 0) { TL(23); ctr_arrive(&g_pctr); ctr_wait(&g_pctr, 128); TL(24); }
    named_sync(NB_SIDE, 96);
}

__device__ __forceinline__ void epi_inputs(int L) {
    const int t = tid_now() - 288, c = cta_now(), mt = c >> 4, nt = c & 15, lane = t & 31;
    #pragma unroll 1
    for (int k = 0; k < 2; k++) {
        const int i = t + 96 * k, col = (i >> 6) * D_ + nt * 64 + (i & 63);
        float p[8], z[8];
        #pragma unroll
        for (int j = 0; j < 8; j++) { p[j] = __ldcg(&g_csum[j][col]); z[j] = __ldcg(&g_cssq[j][col]); }
        stsf(Q_CS + i * 4, ((p[0] + p[1]) + (p[2] + p[3])) + ((p[4] + p[5]) + (p[6] + p[7])));
        const float zz = ((z[0] + z[1]) + (z[2] + z[3])) + ((z[4] + z[5]) + (z[6] + z[7]));
        const float zs = warp_sum(zz);
        if (i < 128) { if (lane == 0) stsf(M_F2 + (i >> 5) * 4, zs); }
        else {
            const int e = (int)(__float_as_uint(zz) >> 23) - 127;
            const int sh = min(max(((e + 2) >> 1) + 3, -60), 60);
            sts32(Q_VS + (i - 128) * 4, (uint32_t)(127 - sh) << 23);
            sts16(M_IVS + (i - 128) * 2, (uint32_t)(127 + sh - 4) << 7);
        }
    }
    #pragma unroll 1
    for (int i = t; i < 256; i += 96) {
        const float2 s = __ldcg(&g_rs[L][mt * 256 + i]);
        const float a = L ? 1.f + rsqrtf(s.x + LN_EPS) : 1.f;
        sts64(Q_RC + i * 8, __float_as_uint(a * rsqrtf(a * a * s.x + LN_EPS)), __float_as_uint(s.y));
    }
}

__device__ __forceinline__ void ffn_finish(int L, bf16* __restrict__ out) {
    const int t = tid_now() - 288, c = cta_now(), lane = t & 31, warp = t >> 5;
    const uint4 rv = lds128(M_RT + 16 * L);
    const int idx = (int)rv.w;
    uint32_t xw = 0;
    if (t < 4) xw = ld_x32(&g_cand[L][idx >> 7][c * 4 + t]);
    float a[4] = {0.f, 0.f, 0.f, 0.f};
    {
        const float* src = &g_ypart[L][t >> 1][c * 8 + (t & 1) * 4];
        uint4 v[3];
        uint32_t n = 0;
        bool again;
        do {
            v[0] = ld_x128(src); v[1] = ld_x128(src + 48 * D_);
            v[2] = t < 32 ? ld_x128(src + 96 * D_) : make_uint4(0u, 0u, 0u, 0u);
            again = false;
            #pragma unroll
            for (int i = 0; i < 3; i++) again = again || v[i].x == EMPTY || v[i].y == EMPTY || v[i].z == EMPTY || v[i].w == EMPTY;
            poll_tick(n);
        } while (again);
        #pragma unroll
        for (int i = 0; i < 3; i++) { a[0] += __uint_as_float(v[i].x); a[1] += __uint_as_float(v[i].y); a[2] += __uint_as_float(v[i].z); a[3] += __uint_as_float(v[i].w); }
    }
    __syncwarp();
    #pragma unroll
    for (int o = 2; o < 32; o <<= 1) {
        #pragma unroll
        for (int i = 0; i < 4; i++) a[i] += __shfl_xor_sync(0xffffffffu, a[i], o);
    }
    if (lane < 2) sts128(M_SR + warp * 32 + lane * 16, __float_as_uint(a[0]), __float_as_uint(a[1]), __float_as_uint(a[2]), __float_as_uint(a[3]));
    named_sync(NB_SIDE, 96);
    if (t < 4) {
        const float2 y0 = lds64f(M_SR + t * 8), y1 = lds64f(M_SR + 32 + t * 8), y2 = lds64f(M_SR + 64 + t * 8);
        const uint32_t y = pack_bf16(y0.x + y1.x + y2.x, y0.y + y1.y + y2.y);
        const float rsel = bf_round(rcp(1.f + __expf(-bf_round(__uint_as_float(rv.x)))));
        const float mean = __uint_as_float(rv.y), rstd = __uint_as_float(rv.z);
        const uint32_t xn = pack_bf16((bf_lo(xw) - mean) * rstd, (bf_hi(xw) - mean) * rstd);
        const uint32_t res = badd2(xw, badd2(xn, pack_bf16(bf_lo(y) * rsel, bf_hi(y) * rsel)));
        if (L == 0) st_x32(&g_x2row[c * 4 + t], res);
        else reinterpret_cast<uint32_t*>(out + (size_t)idx * D_)[c * 4 + t] = res;
    }
}

__device__ __forceinline__ void fix_row(uint32_t lb) {
    const int t = tid_now() - 288, c = cta_now(), lane = t & 31, warp = t >> 5;
    uint4 v[2];
    {
        uint32_t n = 0;
        bool again;
        do {
            v[0] = ld_x128(g_x2row + t * 4);
            v[1] = t < 32 ? ld_x128(g_x2row + (96 + t) * 4) : make_uint4(0u, 0u, 0u, 0u);
            again = false;
            #pragma unroll
            for (int i = 0; i < 2; i++) again = again || v[i].x == EMPTY || v[i].y == EMPTY || v[i].z == EMPTY || v[i].w == EMPTY;
            poll_tick(n);
        } while (again);
    }
    __syncwarp();
    const uint32_t w[8] = {v[0].x, v[0].y, v[0].z, v[0].w, v[1].x, v[1].y, v[1].z, v[1].w};
    float su = 0.f, sq = 0.f;
    #pragma unroll
    for (int i = 0; i < 8; i++) { const float a = bf_lo(w[i]), b = bf_hi(w[i]); su += a + b; sq = fmaf(a, a, fmaf(b, b, sq)); }
    su = warp_sum(su); sq = warp_sum(sq);
    if (lane == 0) sts64(M_SR + 96 + warp * 8, __float_as_uint(su), __float_as_uint(sq));
    named_sync(NB_SIDE, 96);
    const float2 s0 = lds64f(M_SR + 96), s1 = lds64f(M_SR + 104), s2 = lds64f(M_SR + 112);
    const float mean = (s0.x + s1.x + s2.x) * (1.f / D_);
    const float rstd = rsqrtf(fmaxf((s0.y + s1.y + s2.y) * (1.f / D_) - mean * mean, 0.f) + LN_EPS);
    #pragma unroll
    for (int i = 0; i < 8; i++)
        if (i < 4 || t < 32) sts64(SD_VEC + (t + 96 * (i >> 2)) * 32 + (i & 3) * 8, __float_as_uint(bf_round((bf_lo(w[i]) - mean) * rstd)), __float_as_uint(bf_round((bf_hi(w[i]) - mean) * rstd)));
    named_sync(NB_SIDE, 96);
    if (t == 0) TL(32 + 22);
    mbar_wait(lb + B_SW, 0);
    float a[8];
    #pragma unroll
    for (int i = 0; i < 8; i++) a[i] = 0.f;
    #pragma unroll 4
    for (int b = 0; b < 32; b++) {
        const float x = ldsf(SD_VEC + (b * 32 + lane) * 4);
        const uint4 u = lds128(SD_W + (b * 32 + lane) * 48 + warp * 16);
        a[0] = fmaf(x, bf_lo(u.x), a[0]); a[1] = fmaf(x, bf_hi(u.x), a[1]); a[2] = fmaf(x, bf_lo(u.y), a[2]); a[3] = fmaf(x, bf_hi(u.y), a[3]);
        a[4] = fmaf(x, bf_lo(u.z), a[4]); a[5] = fmaf(x, bf_hi(u.z), a[5]); a[6] = fmaf(x, bf_lo(u.w), a[6]); a[7] = fmaf(x, bf_hi(u.w), a[7]);
    }
    halve<4>(a, lane, 16); halve<2>(a, lane, 8); halve<1>(a, lane, 4);
    a[0] = quad_sum(a[0]);
    if ((lane & 3) == 0) st_x32(&g_fix[c * 24 + warp * 8 + (lane >> 2)], __float_as_uint(a[0]));
    if (t == 0) TL(32 + 23);
    if (((int)lds32(M_RT + 12) >> 8) == (c >> 4)) {
        const float* src = &g_fix[(t >> 5) * D_ + (c & 15) * 64 + (t & 31) * 2];
        uint2 f;
        uint32_t n = 0;
        do { f = ld_x64(src); poll_tick(n); } while (f.x == EMPTY || f.y == EMPTY);
        sts64(Q_FIX + t * 8, f.x, f.y);
    }
}

__device__ __forceinline__ void side_role(const bf16* __restrict__ x0, const bf16* __restrict__ w_r, bf16* __restrict__ out) {
    #pragma unroll 1
    for (int L = 0; L < 2; L++) {
        const uint32_t lb = M_BAR + L * BAR_SET;
        if (L == 0) prep_work(x0, w_r, lb);
        else {
            fix_row(lb);
            if (tid_now() == 288) ctr_wait(&g_fl.x[cta_now() >> 4], 16);
            named_sync(NB_SIDE, 96);
        }
        epi_inputs(L);
        const int t = tid_now() - 288, c = cta_now(), mt = c >> 4, nt = c & 15, lane = t & 31, warp = t >> 5;
        if (t == 0) TL(L * 32 + 4);
        named_sync(NB_ML, 352);
        #pragma unroll 1
        for (int i = t; i < 512; i += 96) sts128(A_RING + (i >> 7) * R_SLOT + 16384 + (i & 127) * 16, 0x2C002C00u, 0x2C002C00u, 0x2C002C00u, 0x2C002C00u);
        fence_async_smem();
        named_arrive(NB_STG, 352);
        if (lane == 0) {
            if (warp == 2) {
                char* dst = g_kv + (size_t)(nt * 2 * 16 + mt * 2) * KV_TILE;
                mbar_wait(lb + B_KVA, 0);
                bulk_store(dst, A_KP, 8192);
                bulk_store(dst + 16384, A_RING, 8192);
                bulk_store(dst + 8192, A_RING + 8192, 8192);
                bulk_store(dst + 24576, A_RING + R_SLOT + 8192, 8192);
                bulk_commit();
                bulk_wait();
                fence_async_global();
                asm volatile("st.release.gpu.global.u8 [%0], 1;" :: "l"(&g_fl.kv[L][nt * 2][mt]) : "memory");
                mbar_arrive(lb + B_ARD);
                TL(L * 32 + 6);
                mbar_wait(lb + B_KVB, 0);
                bulk_store(dst + 16 * KV_TILE, A_STB, 32768);
                bulk_commit();
                bulk_wait();
                fence_async_global();
                asm volatile("st.release.gpu.global.u8 [%0], 1;" :: "l"(&g_fl.kv[L][nt * 2 + 1][mt]) : "memory");
                mbar_arrive(lb + B_BRD);
                if (L == 0) { mbar_wait(lb + B_XS, 0); ctr_arrive(&g_fl.x[mt]); }
            } else {
                #pragma unroll 1
                for (int p = 0; p < 2; p++) { mbar_wait(lb + B_OD + (p * 2 + warp) * 8, 0); ctr_arrive(&g_fl.o[L][mt * 2 + warp][p]); }
            }
        }
        __syncwarp();
        mbar_wait(lb + B_FD, 0);
        if (c == 0 && t == 0 && L == 0) g_pctr = 0u;
        ffn_finish(L, out);
        if (t == 0) TL(L * 32 + 20);
    }
}

template <int HH, bool F16>
__device__ __forceinline__ void qkv_epi_head(const float (&acc0)[96], const float (&acc1)[96], const float (&cf)[4], const float (&nm)[4], int t, uint32_t (&pk)[4][4]) {
    constexpr int TYPE = HH >> 1;
    #pragma unroll
    for (int jj = 0; jj < 4; jj++) {
        const float2 c2 = lds64f(Q_CS + (HH * 32 + jj * 8 + t * 2) * 4);
        float2 v2 = make_float2(1.f, 1.f);
        if (TYPE == 2) v2 = lds64f(Q_VS + ((HH & 1) * 32 + jj * 8 + t * 2) * 4);
        #pragma unroll
        for (int i = 0; i < 4; i++) {
            const float* a = (i >> 1) ? acc1 : acc0;
            const float sc = TYPE == 0 ? cf[i] * QSCALE : cf[i];
            float x = fmaf(nm[i], c2.x, a[4 * (4 * HH + jj) + 2 * (i & 1)]) * sc;
            float y = fmaf(nm[i], c2.y, a[4 * (4 * HH + jj) + 2 * (i & 1) + 1]) * sc;
            if (TYPE == 2) { x *= v2.x; y *= v2.y; }
            pk[i][jj] = F16 ? pack_f16(x, y) : pack_bf16(x, y);
        }
    }
}
template <int HH>
__device__ __forceinline__ void qkv_epi_sel(const float (&acc0)[96], const float (&acc1)[96], const float (&cf)[4], const float (&nm)[4], int t, bool f16, uint32_t (&pk)[4][4]) {
    if (HH >= 4 || __builtin_expect(f16, 1)) qkv_epi_head<HH, true>(acc0, acc1, cf, nm, t, pk);
    else qkv_epi_head<HH, false>(acc0, acc1, cf, nm, t, pk);
}
__device__ __forceinline__ void stage_kv(uint32_t dst, const uint32_t (&pk)[4][4]) {
    #pragma unroll
    for (int i = 0; i < 4; i++) stsm4(dst + (i >> 1) * 1024 + (i & 1) * 128, pk[i][0], pk[i][1], pk[i][2], pk[i][3]);
}
template <int OFF>
__device__ __forceinline__ void patch_row(float (&acc)[96], int t) {
    #pragma unroll
    for (int j = 0; j < 24; j++) { const float2 f = lds64f(Q_FIX + (j * 8 + t * 2) * 4); acc[4 * j + OFF] = f.x; acc[4 * j + OFF + 1] = f.y; }
}
__device__ __forceinline__ uint32_t heads_ok() {
    const uint4 f = lds128(M_F2);
    const float qa = __uint_as_float(f.x), qb = __uint_as_float(f.y), ka = __uint_as_float(f.z), kb = __uint_as_float(f.w);
    return (qa <= 16384.f && ka <= 16384.f && qa * ka <= 50000.f ? 1u : 0u) | (qb <= 16384.f && kb <= 16384.f && qb * kb <= 50000.f ? 2u : 0u);
}

__device__ __forceinline__ void qkv_phase(int L, uint32_t lb, int wg, uint32_t (&qa)[8], uint32_t (&qb)[8]) {
    float acc0[96], acc1[96];
    #pragma unroll
    for (int i = 0; i < 96; i++) { acc0[i] = 0.f; acc1[i] = 0.f; }
    pin(acc0); pin(acc1);
    const bool leader = (tid_now() & 127) == 0;
    {
        uint32_t st = 0, ph = 0;
        #pragma unroll 1
        for (int k = 0; k < 16; k++) {
            mbar_wait(lb + B_QF + 8 * st, ph);
            if (threadIdx.x == 0 && k == 0) TL(L * 32 + 1);
            const uint32_t sa = SB + (st == 0 ? 2 : st - 1) * Q_STB;
            const uint64_t da = desc_sw128(sa + wg * 16384, 16, 1024);
            const uint64_t db = desc_sw128(sa + Q_ABYTES, 8192, 1024);
            wg_fence();
            #pragma unroll
            for (int kk = 0; kk < 4; kk++) {
                wg_gemm_n192(acc0, da + kk * 2, db + kk * 128);
                wg_gemm_n192(acc1, da + (8192 >> 4) + kk * 2, db + kk * 128);
            }
            wg_commit();
            wg_wait<1>();
            if (leader && k > 0) mbar_arrive(lb + B_QE + 8 * (st == 0 ? 2 : st - 1));
            if (++st == 3) { st = 0; ph ^= 1; }
        }
    }
    wg_wait<0>();
    pin(acc0); pin(acc1);
    if (threadIdx.x == 0) TL(L * 32 + 2);
    named_sync(NB_ML, 352);
    if (threadIdx.x == 0) TL(L * 32 + 3);
    const int tid = tid_now(), lane = tid & 31, w = (tid >> 5) & 3, g = lane >> 2, t = lane & 3;
    const int lr0 = wg * 128 + w * 16 + g;
    float cf[4], nm[4];
    #pragma unroll
    for (int i = 0; i < 4; i++) { const float2 r = lds64f(Q_RC + (lr0 + (i >> 1) * 64 + (i & 1) * 8) * 8); cf[i] = r.x; nm[i] = -r.y; }
    if (L) {
        const int d = (int)lds32(M_RT + 12) - ((cta_now() >> 4) * 256 + lr0);
        if (__builtin_expect((d & ~72) == 0, 0)) {
            if (d == 0) { patch_row<0>(acc0, t); cf[0] = 1.f; nm[0] = 0.f; }
            else if (d == 8) { patch_row<2>(acc0, t); cf[1] = 1.f; nm[1] = 0.f; }
            else if (d == 64) { patch_row<0>(acc1, t); cf[2] = 1.f; nm[2] = 0.f; }
            else { patch_row<2>(acc1, t); cf[3] = 1.f; nm[3] = 0.f; }
        }
        __syncwarp();
    }
    const uint32_t ok = heads_ok();
    const uint32_t ko = (lane >> 3) * 2048 + (w * 16 + (lane & 7)) * 16;
    uint32_t pk[4][4];
    qkv_epi_sel<2>(acc0, acc1, cf, nm, t, ok & 1, pk);
    stage_kv((wg ? A_RING : A_KP) + ko, pk);
    qkv_epi_sel<4>(acc0, acc1, cf, nm, t, true, pk);
    stage_kv(A_RING + wg * R_SLOT + 8192 + ko, pk);
    fence_async_smem();
    __syncwarp();
    mbar_arrive_elect(lb + B_KVA);
    qkv_epi_sel<3>(acc0, acc1, cf, nm, t, ok & 2, pk);
    stage_kv(A_STB + wg * KV_TILE + ko, pk);
    qkv_epi_sel<5>(acc0, acc1, cf, nm, t, true, pk);
    stage_kv(A_STB + wg * KV_TILE + 8192 + ko, pk);
    qkv_epi_sel<1>(acc0, acc1, cf, nm, t, ok & 2, pk);
    #pragma unroll
    for (int u = 0; u < 2; u++)
        #pragma unroll
        for (int s = 0; s < 2; s++) sts128(A_QX + (u * 2 + s) * 4096 + tid * 16, pk[2*u][2*s], pk[2*u+1][2*s], pk[2*u][2*s+1], pk[2*u+1][2*s+1]);
    qkv_epi_sel<0>(acc0, acc1, cf, nm, t, ok & 1, pk);
    #pragma unroll
    for (int s = 0; s < 2; s++) {
        qa[4*s] = pk[0][2*s]; qa[4*s+1] = pk[1][2*s]; qa[4*s+2] = pk[0][2*s+1]; qa[4*s+3] = pk[1][2*s+1];
        qb[4*s] = pk[2][2*s]; qb[4*s+1] = pk[3][2*s]; qb[4*s+2] = pk[2][2*s+1]; qb[4*s+3] = pk[3][2*s+1];
    }
    fence_async_smem();
    __syncwarp();
    mbar_arrive_elect(lb + B_KVB);
    named_sync(NB_STG, 352);
    if (threadIdx.x == 0) TL(L * 32 + 5);
}

#define NPOLY 24
__host__ __device__ constexpr bool is_poly(int j) { return ((j + 1) * NPOLY / 32) != (j * NPOLY / 32); }
struct Shift { uint32_t f0, f1, n0, n1, bad; };

__device__ __forceinline__ uint32_t exp2_mufu(uint32_t s, uint32_t nm) {
    uint32_t r;
    asm("ex2.approx.f16x2 %0, %1;" : "=r"(r) : "r"(hadd2(s, nm)));
    return r;
}
__device__ __forceinline__ uint32_t exp2_fix(uint32_t s, uint32_t fm, uint32_t ca, uint32_t& U) {
    uint32_t G, D;
    asm("fma.rn.relu.f16x2 %0, %1, %2, %3;" : "=r"(U) : "r"(s), "r"(0x00400040u), "r"(fm));
    asm("fma.rn.f16x2 %0, %1, %2, %3;" : "=r"(G) : "r"(U & 0x003F003Fu), "r"(ca), "r"(0x98B898B8u));
    asm("{.reg .b32 n; neg.f16x2 n, %1; fma.rn.relu.f16x2 %0, %1, n, %2;}" : "=r"(D) : "r"(G), "r"(0x00570057u));
    return (U << 4) - D;
}
__device__ __forceinline__ void exp_tile(const uint32_t (&S)[32], uint32_t (&P)[32], Shift& h, uint32_t ca) {
    uint32_t pend = 0; bool have = false;
    #pragma unroll
    for (int i = 0; i < 32; i++) {
        if (is_poly(i)) {
            uint32_t U;
            P[i] = exp2_fix(S[i], (i & 1) ? h.f1 : h.f0, ca, U);
            if (have) { asm("lop3.b32 %0, %0, %1, %2, 0xFE;" : "+r"(h.bad) : "r"(pend), "r"(U)); have = false; } else { pend = U; have = true; }
        } else P[i] = exp2_mufu(S[i], (i & 1) ? h.n1 : h.n0);
    }
    if (have) h.bad |= pend;
    pin(P);
}
__device__ __forceinline__ void unit_start(const uint32_t (&S)[32], Shift& h, uint32_t (&o2)[10]) {
    uint32_t m[4] = {S[0], S[1], S[2], S[3]};
    #pragma unroll
    for (int i = 1; i < 8; i++)
        #pragma unroll
        for (int e = 0; e < 4; e++) m[e] = hmax2(m[e], S[4 * i + e]);
    float a0, a1, c0, c1;
    h2_unpack(hadd2(m[0], m[2]), a0, a1); h2_unpack(hadd2(m[1], m[3]), c0, c1);
    const float big = 3145728.f;
    const float m0 = (fmaf(quad_sum(a0 + a1), 0.0625f, 5.25f) + big) - big, m1 = (fmaf(quad_sum(c0 + c1), 0.0625f, 5.25f) + big) - big;
    h.n0 = pack_f16(-m0, -m0); h.n1 = pack_f16(-m1, -m1);
    const float u0 = (15.f - m0) * 0x1p-18f, u1 = (15.f - m1) * 0x1p-18f;
    h.f0 = pack_f16(u0, u0); h.f1 = pack_f16(u1, u1);
    h.bad = fabsf(m0) <= 480.f && fabsf(m1) <= 480.f ? 0u : 0x8000u;
    #pragma unroll
    for (int i = 0; i < 10; i++) o2[i] = 0u;
}
__device__ __forceinline__ bf16* o_ptr(int pass, int unit) {
    const int c = cta_now(), tid = tid_now();
    const int row = (c >> 4) * 256 + (tid >> 7) * 128 + unit * 64 + ((tid >> 5) & 3) * 16 + ((tid & 31) >> 2);
    return g_o + (row * D_ + pass * 512 + (c & 15) * 32);
}
__device__ __forceinline__ uint32_t unit_end(const uint32_t (&o)[10], const uint32_t (&o2)[10], const Shift& h, uint32_t lb, int pass, int unit) {
    const int tid = tid_now(), t = tid & 3;
    float v[20];
    #pragma unroll
    for (int i = 0; i < 10; i++) { float a, b, c, d; h2_unpack(o[i], a, b); h2_unpack(o2[i], c, d); v[2 * i] = a + c; v[2 * i + 1] = b + d; }
    const float i0 = rcp(v[16]), i1 = rcp(v[18]);
    float z = v[16] + v[18];
    uint32_t r[8];
    #pragma unroll
    for (int j = 0; j < 4; j++) {
        const uint32_t iv = lds32(M_IVS + (pass * 32 + j * 8 + t * 2) * 2);
        z += (fabsf(v[4*j]) + fabsf(v[4*j+1])) + (fabsf(v[4*j+2]) + fabsf(v[4*j+3]));
        r[j] = pack_bf16(v[4*j] * i0 * bf_lo(iv), v[4*j+1] * i0 * bf_hi(iv));
        r[4 + j] = pack_bf16(v[4*j+2] * i1 * bf_lo(iv), v[4*j+3] * i1 * bf_hi(iv));
    }
    const bool good = z < 1e30f && v[16] >= 0.25f && v[18] >= 0.25f && (h.bad & 0xF800F800u) == 0 && ((heads_ok() >> pass) & 1);
    const bool all = __all_sync(0xffffffffu, good);
    bf16* dst = o_ptr(pass, unit) + t * 8;
    stg128_pred(dst, make_uint4(r[0], r[1], r[2], r[3]), all);
    stg128_pred(dst + 8 * D_, make_uint4(r[4], r[5], r[6], r[7]), all);
    __syncwarp();
    mbar_arrive_elect_p(lb + B_OD + (pass * 2 + (tid >> 7)) * 8, all);
    return all ? 0u : 1u;
}
__device__ __forceinline__ void swap_q(uint32_t (&q)[8], int unit) {
    const uint32_t a = A_QX + unit * 8192 + tid_now() * 16;
    const uint4 x = lds128(a), y = lds128(a + 4096);
    sts128(a, q[0], q[1], q[2], q[3]); sts128(a + 4096, q[4], q[5], q[6], q[7]);
    q[0] = x.x; q[1] = x.y; q[2] = x.z; q[3] = x.w; q[4] = y.x; q[5] = y.y; q[6] = y.z; q[7] = y.w;
}
template <bool INIT>
__device__ __forceinline__ void issue_pv(uint32_t (&o)[10], const uint32_t (&P)[32], uint64_t dv) {
    if (INIT) wg_pv_init(o, P[0], P[1], P[2], P[3], dv); else wg_pv_acc(o, P[0], P[1], P[2], P[3], dv);
    #pragma unroll
    for (int k = 1; k < 8; k++) wg_pv_acc(o, P[4*k], P[4*k+1], P[4*k+2], P[4*k+3], dv + k * 16);
}

__device__ __forceinline__ uint4 quad_transpose(uint32_t x0, uint32_t x1, uint32_t x2, uint32_t x3, int t) {
    const bool b0 = t & 1, b1 = t & 2;
    uint32_t s0 = b0 ? x0 : x1, s1 = b0 ? x2 : x3;
    s0 = __shfl_xor_sync(0xffffffffu, s0, 1); s1 = __shfl_xor_sync(0xffffffffu, s1, 1);
    const uint32_t y0 = b0 ? s0 : x0, y1 = b0 ? x1 : s0, y2 = b0 ? s1 : x2, y3 = b0 ? x3 : s1;
    uint32_t u0 = b1 ? y0 : y2, u1 = b1 ? y1 : y3;
    u0 = __shfl_xor_sync(0xffffffffu, u0, 2); u1 = __shfl_xor_sync(0xffffffffu, u1, 2);
    return b1 ? make_uint4(u0, u1, y2, y3) : make_uint4(y0, y1, u0, u1);
}
__device__ __forceinline__ uint32_t movm(uint32_t v) { uint32_t r; asm volatile("movmatrix.sync.aligned.m8n8.trans.b16 %0, %1;" : "=r"(r) : "r"(v)); return r; }
__device__ __forceinline__ void attn_repair(const uint32_t (&q)[8], uint32_t lb, int pass, int unit) {
    const int tid = tid_now(), g = (tid & 31) >> 2, t = tid & 3;
    const bool f16 = (heads_ok() >> pass) & 1;
    const uint4 q0 = quad_transpose(q[0], q[2], q[4], q[6], t), q1 = quad_transpose(q[1], q[3], q[5], q[7], t);
    const char* kv = g_kv + (size_t)((cta_now() & 15) * 2 + pass) * 16 * KV_TILE + t * 2048 + g * 16;
    float o[4][4], m0 = -INFINITY, m1 = -INFINITY, l0 = 0.f, l1 = 0.f;
    #pragma unroll
    for (int j = 0; j < 4; j++) { o[j][0] = 0.f; o[j][1] = 0.f; o[j][2] = 0.f; o[j][3] = 0.f; }
    #pragma unroll 1
    for (int b = 0; b < 32; b++) {
        const char* p = kv + (b >> 1) * KV_TILE + (b & 1) * 1024;
        uint4 kf[8], vf[8];
        #pragma unroll
        for (int i = 0; i < 8; i++) { kf[i] = __ldcg(reinterpret_cast<const uint4*>(p + i * 128)); vf[i] = __ldcg(reinterpret_cast<const uint4*>(p + 8192 + i * 128)); }
        float s[8][4];
        #pragma unroll
        for (int i = 0; i < 8; i++) {
            s[i][0] = 0.f; s[i][1] = 0.f; s[i][2] = 0.f; s[i][3] = 0.f;
            if (f16) { mma_f16(s[i], q0.x, q1.x, q0.y, q1.y, kf[i].x, kf[i].y); mma_f16(s[i], q0.z, q1.z, q0.w, q1.w, kf[i].z, kf[i].w); }
            else { mma_bf16(s[i], q0.x, q1.x, q0.y, q1.y, kf[i].x, kf[i].y); mma_bf16(s[i], q0.z, q1.z, q0.w, q1.w, kf[i].z, kf[i].w); }
        }
        float t0 = m0, t1 = m1;
        #pragma unroll
        for (int i = 0; i < 8; i++) { t0 = fmaxf(t0, fmaxf(s[i][0], s[i][1])); t1 = fmaxf(t1, fmaxf(s[i][2], s[i][3])); }
        t0 = quad_max(t0); t1 = quad_max(t1);
        const float a0 = ex2(m0 - t0), a1 = ex2(m1 - t1);
        m0 = t0; m1 = t1;
        l0 *= a0; l1 *= a1;
        #pragma unroll
        for (int j = 0; j < 4; j++) { o[j][0] *= a0; o[j][1] *= a0; o[j][2] *= a1; o[j][3] *= a1; }
        #pragma unroll
        for (int k = 0; k < 4; k++) {
            uint32_t pf[4];
            #pragma unroll
            for (int e = 0; e < 2; e++) {
                const float p0 = ex2(s[2*k+e][0] - m0), p1 = ex2(s[2*k+e][1] - m0), p2 = ex2(s[2*k+e][2] - m1), p3 = ex2(s[2*k+e][3] - m1);
                l0 += p0 + p1; l1 += p2 + p3;
                pf[2*e] = pack_f16(p0, p1); pf[2*e+1] = pack_f16(p2, p3);
            }
            mma_f16(o[0], pf[0], pf[1], pf[2], pf[3], movm(vf[2*k].x), movm(vf[2*k+1].x));
            mma_f16(o[1], pf[0], pf[1], pf[2], pf[3], movm(vf[2*k].y), movm(vf[2*k+1].y));
            mma_f16(o[2], pf[0], pf[1], pf[2], pf[3], movm(vf[2*k].z), movm(vf[2*k+1].z));
            mma_f16(o[3], pf[0], pf[1], pf[2], pf[3], movm(vf[2*k].w), movm(vf[2*k+1].w));
        }
    }
    const float i0 = 16.f * rcp(quad_sum(l0)), i1 = 16.f * rcp(quad_sum(l1));
    uint32_t* dst = reinterpret_cast<uint32_t*>(o_ptr(pass, unit)) + t;
    #pragma unroll
    for (int j = 0; j < 4; j++) {
        const uint32_t iv = lds32(M_IVS + (pass * 32 + t * 8 + j * 2) * 2);
        dst[j * 4] = pack_bf16(o[j][0] * i0 * bf_lo(iv), o[j][1] * i0 * bf_hi(iv));
        dst[j * 4 + 4 * D_] = pack_bf16(o[j][2] * i1 * bf_lo(iv), o[j][3] * i1 * bf_hi(iv));
    }
    __syncwarp();
    mbar_arrive_elect(lb + B_OD + (pass * 2 + (tid >> 7)) * 8);
}

__device__ __forceinline__ void attention_phase(int L, uint32_t lb, uint32_t (&qa)[8], uint32_t (&qb)[8], uint64_t dk0, uint64_t dv0, uint32_t ca) {
    uint32_t SA[32], SB_[32], PA[32], PB[32], oa[10], ob[10], oa2[10], ob2[10];
    Shift ha, hb;
    uint32_t fail = 0;
    constexpr uint64_t SL = R_SLOT >> 4, KH = 4096 >> 4;
    uint64_t dkd = dk0 + ((A_KP - A_RING) >> 4);
    wg_fence();
    wg_qk_init(SA, qa[0], qa[1], qa[2], qa[3], dkd);
    wg_qk_acc(SA, qa[4], qa[5], qa[6], qa[7], dkd + KH);
    wg_qk_init(SB_, qb[0], qb[1], qb[2], qb[3], dkd);
    wg_commit();
    wg_wait<0>();
    pin(SA); pin(SB_);
    unit_start(SA, ha, oa2);
    exp_tile(SA, PA, ha, ca);
    #pragma unroll
    for (int i = 0; i < 10; i++) { ob[i] = 0u; ob2[i] = 0u; }
    hb = ha;
    #pragma unroll 1
    for (int it = 0; ; it++) {
        const uint32_t ph = it & 1;
        #pragma unroll
        for (int u = 0; u < 4; u++) {
            const uint64_t dk = opaque(dk0) + u * SL, dv = opaque(dv0) + u * SL;
            if (u == 3 && it == 3) swap_q(qa, 0);
            wg_fence();
            if (u == 0) { wg_qk_acc(SB_, qb[4], qb[5], qb[6], qb[7], dkd + KH); wg_commit(); }
            if (u == 0) issue_pv<true>(oa, PA, dv); else issue_pv<false>(oa, PA, dv);
            wg_qk_init(SA, qa[0], qa[1], qa[2], qa[3], dk);
            wg_qk_acc(SA, qa[4], qa[5], qa[6], qa[7], dk + KH);
            wg_commit();
            wg_wait<1>();
            pin(SB_); pin(ob);
            if (u == 0) mbar_arrive_elect_p(lb + B_AE + 24, it); else mbar_arrive_elect(lb + B_AE + 8 * (u - 1));
            if (u == 0) {
                if ((it & 3) == 0) {
                    if (it) fail |= unit_end(ob, ob2, hb, lb, 0, 1) << 1;
                    unit_start(SB_, hb, ob2);
                } else {
                    #pragma unroll
                    for (int i = 0; i < 10; i++) ob2[i] = hadd2(ob2[i], ob[i]);
                }
            }
            exp_tile(SB_, PB, hb, ca);
            if (u == 3 && it == 3) swap_q(qb, 1);
            wg_fence();
            if (u == 0) issue_pv<true>(ob, PB, dv); else issue_pv<false>(ob, PB, dv);
            wg_qk_init(SB_, qb[0], qb[1], qb[2], qb[3], dk);
            if (u < 3) wg_qk_acc(SB_, qb[4], qb[5], qb[6], qb[7], dk + KH);
            wg_commit();
            wg_wait<1>();
            pin(SA); pin(oa);
            if (u == 3) {
                if ((it & 3) == 3) {
                    fail |= unit_end(oa, oa2, ha, lb, it >> 2, 0) << (2 * (it >> 2));
                    if (threadIdx.x == 0) TL(L * 32 + 7 + (it >> 2));
                    if (it == 7) goto done;
                    unit_start(SA, ha, oa2);
                } else {
                    #pragma unroll
                    for (int i = 0; i < 10; i++) oa2[i] = hadd2(oa2[i], oa[i]);
                }
            }
            exp_tile(SA, PA, ha, ca);
            mbar_wait(lb + B_AF + 8 * ((u + 1) & 3), u == 3 ? ph ^ 1 : ph);
        }
        wg_wait<0>();
        dkd = dk0 + 3 * SL;
    }
done:
    wg_wait<0>();
    pin(ob);
    mbar_arrive_elect(lb + B_AE + 24);
    fail |= unit_end(ob, ob2, hb, lb, 1, 1) << 3;
    if (__builtin_expect(fail != 0, 0)) {
        #pragma unroll 1
        for (int r = 3; r >= 0; r--) {
            if ((fail >> r) & 1) {
                uint32_t q[8];
                #pragma unroll
                for (int i = 0; i < 8; i++) q[i] = r < 2 ? lds32(A_QX + (r * 2 + (i >> 2)) * 4096 + tid_now() * 16 + (i & 3) * 4) : (r & 1) ? qb[i] : qa[i];
                attn_repair(q, lb, r >> 1, r & 1);
            }
        }
    }
    if (threadIdx.x == 0) TL(L * 32 + 9);
}

__device__ __forceinline__ void oproj_steps(float (&acc)[64], uint32_t lb, int wg, int k0, int k1) {
    const bool leader = (tid_now() & 127) == 0;
    #pragma unroll 1
    for (int k = k0; k < k1; k++) {
        const uint32_t st = k & 3;
        mbar_wait(lb + B_OF + 8 * st, (k >> 2) & 1);
        const uint32_t sa = o_stage(st);
        const uint64_t da = desc_sw128(sa + wg * 8192, 16, 1024);
        const uint64_t db = desc_sw128(sa + 16384, 8192, 1024);
        wg_fence();
        #pragma unroll
        for (int kk = 0; kk < 4; kk++) wg_gemm_n128(acc, da + kk * 2, db + kk * 128);
        wg_commit();
        wg_wait<1>();
        if (leader && k > 0) mbar_arrive(lb + B_OE + 8 * ((k - 1) & 3));
    }
}

__device__ __forceinline__ void tail_phase(int L, uint32_t lb, int wg, const bf16* __restrict__ w_r, bf16* __restrict__ out) {
    const int c = cta_now(), blk = c >> 3, cb = c & 7, tid = tid_now();
    const int lane = tid & 31, w = (tid >> 5) & 3, g = lane >> 2, t = lane & 3;
    const int lr0 = wg * 64 + w * 16 + g;
    const uint32_t xrow = (wg * 64 + w * 16 + (lane & 15)) * 128, xsw = (lane >> 4) ^ (lane & 7);
    uint32_t xv[32];
    {
        float acc[64];
        #pragma unroll
        for (int i = 0; i < 64; i++) acc[i] = 0.f;
        pin(acc);
        uint32_t wv[16];
        #pragma unroll
        for (int j = 0; j < 16; j++) wv[j] = __ldg(reinterpret_cast<const uint32_t*>(w_r + cb * 128) + j * 4 + t);
        float2 rs0 = make_float2(0.f, 0.f), rs1 = rs0;
        if (L) { rs0 = __ldcg(&g_rs[1][blk * 128 + lr0]); rs1 = __ldcg(&g_rs[1][blk * 128 + lr0 + 8]); }
        oproj_steps(acc, lb, wg, 0, 12);
        mbar_wait(lb + B_RES, 0);
        #pragma unroll
        for (int m = 0; m < 8; m++) ldsm4(xv[4*m], xv[4*m+1], xv[4*m+2], xv[4*m+3], (m < 4 ? XT0 : XT1) + xrow + ((xsw ^ (2 * (m & 3))) << 4));
        if (L) {
            const float r0 = rsqrtf(rs0.x + LN_EPS), r1 = rsqrtf(rs1.x + LN_EPS);
            #pragma unroll
            for (int j = 0; j < 16; j++) { xv[2*j] = add_ln2(xv[2*j], rs0.y, r0); xv[2*j+1] = add_ln2(xv[2*j+1], rs1.y, r1); }
            const int d = (int)lds32(M_RT + 12) - (blk * 128 + lr0);
            if (__builtin_expect((d & ~8) == 0, 0)) {
                #pragma unroll
                for (int j = 0; j < 16; j++) {
                    const uint32_t sv = __ldcg(&g_x2row[cb * 64 + j * 4 + t]);
                    if (d == 0) xv[2*j] = sv; else xv[2*j+1] = sv;
                }
            }
            __syncwarp();
        }
        pin(xv);
        oproj_steps(acc, lb, wg, 12, 16);
        wg_wait<0>();
        pin(acc);
        if ((tid & 127) == 0) mbar_arrive(lb + B_OE + 24);
        if (tid == 0) TL(L * 32 + 11);
        float su[2] = {0.f, 0.f}, sq[2] = {0.f, 0.f}, sd[2] = {0.f, 0.f};
        #pragma unroll
        for (int j = 0; j < 16; j++) {
            const float w0 = bf_lo(wv[j]), w1 = bf_hi(wv[j]);
            #pragma unroll
            for (int h = 0; h < 2; h++) {
                const uint32_t ov = badd2(xv[2*j+h], pack_bf16(acc[4*j + 2*h], acc[4*j + 2*h + 1]));
                xv[2*j+h] = ov;
                const float x0 = bf_lo(ov), x1 = bf_hi(ov);
                su[h] += x0 + x1;
                sq[h] = fmaf(x0, x0, fmaf(x1, x1, sq[h]));
                sd[h] = fmaf(x0, w0, fmaf(x1, w1, sd[h]));
            }
        }
        #pragma unroll
        for (int h = 0; h < 2; h++) { su[h] = quad_sum(su[h]); sq[h] = quad_sum(sq[h]); sd[h] = quad_sum(sd[h]); }
        if (t < 2) st_x128(&g_part[L][blk][cb][lr0 + 8 * t], __float_as_uint(t ? su[1] : su[0]), __float_as_uint(t ? sq[1] : sq[0]), __float_as_uint(t ? sd[1] : sd[0]), 1u);
    }
    if (tid == 0) TL(L * 32 + 12);
    float mean[2], rstd[2], score[2];
    {
        const uint4* src = &g_part[L][blk][2 * t][lr0];
        uint4 p[4];
        uint32_t n = 0;
        do {
            p[0] = ld_x128(src); p[1] = ld_x128(src + 128); p[2] = ld_x128(src + 8); p[3] = ld_x128(src + 136);
            poll_tick(n);
        } while ((p[0].w & p[1].w & p[2].w & p[3].w) == 0);
        __syncwarp();
        const float ws = ldsf(M_WS);
        #pragma unroll
        for (int h = 0; h < 2; h++) {
            const float su = quad_sum(__uint_as_float(p[2*h].x) + __uint_as_float(p[2*h+1].x));
            const float sq = quad_sum(__uint_as_float(p[2*h].y) + __uint_as_float(p[2*h+1].y));
            const float sd = quad_sum(__uint_as_float(p[2*h].z) + __uint_as_float(p[2*h+1].z));
            mean[h] = su * (1.f / D_);
            const float var = fmaxf(sq * (1.f / D_) - mean[h] * mean[h], 0.f);
            rstd[h] = rsqrtf(var + LN_EPS);
            score[h] = rstd[h] * (sd - mean[h] * ws);
            if (L == 0 && cb == 0 && t == h) g_rs[1][blk * 128 + lr0 + 8 * h] = make_float2(var, mean[h]);
        }
    }
    if (tid == 0) TL(L * 32 + 13);
    {
        const uint32_t k0 = order_bits(score[0]), k1 = order_bits(score[1]);
        const uint32_t kb = max(k0, k1), m = redux_max(kb);
        const uint32_t mrow = redux_min(kb == m ? (k1 > k0 ? lr0 + 8 : lr0) : 0x7FFFFFFFu);
        if (lane == 0) sts64(M_KR + (tid >> 5) * 8, m, mrow);
        named_sync(NB_CONS, 256);
        const float2 e = lds64f(M_KR + (lane & 7) * 8);
        const uint32_t m2 = redux_max(__float_as_uint(e.x));
        const int d = (int)redux_min(__float_as_uint(e.x) == m2 ? __float_as_uint(e.y) : 0x7FFFFFFFu) - lr0;
        if ((d & ~8) == 0) {
            if (cb == 0 && t == 0)
                st_x128(&g_hdr[L][blk], __float_as_uint(d ? score[1] : score[0]), __float_as_uint(d ? mean[1] : mean[0]), __float_as_uint(d ? rstd[1] : rstd[0]), blk * 128 + lr0 + d + 1);
            #pragma unroll
            for (int j = 0; j < 16; j++) st_x32(&g_cand[L][blk][cb * 64 + j * 4 + t], d ? xv[2*j+1] : xv[2*j]);
        }
        __syncwarp();
    }
    uint4 tv[8];
    if (L) {
        #pragma unroll
        for (int j = 0; j < 16; j++) { xv[2*j] = add_ln2(xv[2*j], mean[0], rstd[0]); xv[2*j+1] = add_ln2(xv[2*j+1], mean[1], rstd[1]); }
    }
    #pragma unroll
    for (int m = 0; m < 8; m++) stsm4((m < 4 ? XT0 : XT1) + xrow + ((xsw ^ (2 * (m & 3))) << 4), xv[4*m], xv[4*m+1], xv[4*m+2], xv[4*m+3]);
    __syncwarp();
    #pragma unroll
    for (int i = 0; i < 8; i++) {
        const int r = 2 * i + (lane >> 4);
        tv[i] = lds128(((lane & 8) ? XT1 : XT0) + (wg * 64 + w * 16 + r) * 128 + (((lane & 7) ^ (r & 7)) << 4));
    }
    Route rt;
    {
        uint4 e;
        uint32_t n = 0;
        do { e = ld_x128(&g_hdr[L][lane & 15]); poll_tick(n); } while (e.w == 0);
        __syncwarp();
        const uint32_t k = order_bits(__uint_as_float(e.x)), m = redux_max(k);
        rt.idx = (int)redux_min(k == m ? e.w : 0x7FFFFFFFu) - 1;
        rt.r = __shfl_sync(0xffffffffu, __uint_as_float(e.x), rt.idx >> 7);
        rt.mean = __shfl_sync(0xffffffffu, __uint_as_float(e.y), rt.idx >> 7);
        rt.rstd = __shfl_sync(0xffffffffu, __uint_as_float(e.z), rt.idx >> 7);
    }
    if (tid == 0) TL(L * 32 + 14);
    {
        uint2 x;
        uint32_t n = 0;
        do { x = ld_x64(&g_cand[L][rt.idx >> 7][tid * 2]); poll_tick(n); } while (x.x == EMPTY || x.y == EMPTY);
        __syncwarp();
        sts64(M_XS + tid * 8, pack_bf16((bf_lo(x.x) - rt.mean) * rt.rstd, (bf_hi(x.x) - rt.mean) * rt.rstd), pack_bf16((bf_lo(x.y) - rt.mean) * rt.rstd, (bf_hi(x.y) - rt.mean) * rt.rstd));
        if (tid == 0) sts128(M_RT + 16 * L, __float_as_uint(rt.r), __float_as_uint(rt.mean), __float_as_uint(rt.rstd), rt.idx);
        fence_async_smem();
    }
    {
        const int row0 = blk * 128 + wg * 64 + w * 16 + (lane >> 4);
        bf16* dst = (L ? out : g_x1) + (size_t)row0 * D_ + cb * 128 + (lane & 15) * 8;
        const int skip = L ? rt.idx - row0 : -1;
        #pragma unroll
        for (int i = 0; i < 8; i++) stg128_pred(dst + 2 * i * D_, tv[i], skip != 2 * i);
        __syncwarp();
        mbar_arrive_elect(lb + B_XS);
    }
    named_sync(NB_CONS, 256);
    if (tid == 0) TL(L * 32 + 15);
    if (c < NFC) {
        float d[4] = {0.f, 0.f, 0.f, 0.f};
        pin(d);
        mbar_wait(lb + (wg ? B_GU1 : B_GU0), 0);
        {
            const uint64_t da = opaque(desc_sw64(wg ? F_GU1 : F_GU0, 16384, 512)), db = opaque(desc_plain(M_XS + wg * 1024, 16, 128));
            wg_fence();
            #pragma unroll
            for (int k = 0; k < 32; k++) wg_gemv_acc(d, da + (((k >> 4) * 32768 + (k & 15) * 1024) >> 4), db + k * 2);
            wg_commit();
            wg_wait<0>();
            pin(d);
        }
        if (t == 0) { stsf(XT0 + (wg * 64 + w * 16 + g) * 4, d[0]); stsf(XT0 + (wg * 64 + w * 16 + g + 8) * 4, d[2]); }
        mbar_arrive_elect(lb + B_FG);
        named_sync(NB_CONS, 256);
        if (tid == 0) TL(L * 32 + 16);
        {
            const float gv = bf_round(ldsf(XT0 + lane * 4) + ldsf(XT0 + 256 + lane * 4)), uv = bf_round(ldsf(XT0 + 128 + lane * 4) + ldsf(XT0 + 384 + lane * 4));
            const uint32_t hv = pack_bf16(bf_round(gv * rcp(1.f + __expf(-gv))) * uv, 0.f);
            const uint32_t ha = XT0 + 1024 + wg * 512 + (lane >> 3) * 128 + w * 32 + (lane & 7) * 2;
            sts16(ha, hv); sts16(ha + 16, hv);
            fence_async_smem();
        }
        named_sync(NB_WG + wg, 128);
        mbar_wait(lb + B_WD, 0);
        float y[8][4];
        #pragma unroll
        for (int i = 0; i < 8; i++) { y[i][0] = 0.f; y[i][1] = 0.f; y[i][2] = 0.f; y[i][3] = 0.f; pin(y[i]); }
        {
            const uint64_t da = opaque(desc_sw128(F_WD + wg * 32768, 8192, 1024)), db = opaque(desc_plain(XT0 + 1024 + wg * 512, 128, 128));
            wg_fence();
            #pragma unroll
            for (int i = 0; i < 8; i++) { wg_gemv_acc(y[i], da + i * 256, db); wg_gemv_acc(y[i], da + i * 256 + 128, db + 16); }
            wg_commit();
            wg_wait<0>();
            #pragma unroll
            for (int i = 0; i < 8; i++) pin(y[i]);
        }
        float* dst = &g_ypart[L][c][wg * 512 + t * 128 + w * 16 + g];
        #pragma unroll
        for (int i = 0; i < 2; i++)
            #pragma unroll
            for (int h = 0; h < 2; h++) {
                const float a = (t & 1) ? y[2 + i][2*h] : y[i][2*h], b = (t & 1) ? y[6 + i][2*h] : y[4 + i][2*h];
                st_x32(dst + i * 64 + h * 8, __float_as_uint((t & 2) ? b : a));
            }
    } else {
        mbar_arrive_elect(lb + B_FG);
    }
    mbar_arrive_elect(lb + B_FD);
    if (tid == 0) TL(L * 32 + 17);
}

__device__ __forceinline__ void qkv_load_w(const Maps& mp, uint32_t sa, int k, uint32_t fb) {
    #pragma unroll
    for (int b = 0; b < 3; b++) tma_load(sa + Q_ABYTES + b * 8192, &mp.wqkv, b * D_ + (blockIdx.x & 15) * 64, k * 64, fb);
}
__device__ __forceinline__ void qkv_load_x(const CUtensorMap* tx, uint32_t sa, int k, uint32_t fb) {
    #pragma unroll
    for (int a = 0; a < 4; a++) tma_load(sa + a * 8192, tx, k * 64, (blockIdx.x >> 4) * 256 + a * 64, fb);
}
__device__ __forceinline__ void producer_role(const Maps& mp, const bf16* __restrict__ x0, const bf16* __restrict__ wo, const bf16* __restrict__ w_down) {
    const int c = blockIdx.x, mt = c >> 4, nt = c & 15, blk = c >> 3, cb = c & 7;
    const bool ffn = c < NFC;
    #pragma unroll 1
    for (int L = 0; L < 2; L++) {
        const uint32_t lb = M_BAR + L * BAR_SET;
        const CUtensorMap* tx = &mp.x[L];
        if (L == 0) {
            mbar_wait(lb + B_QF, 0);
            l2_prefetch(x0 + (size_t)c * 16 * D_, 32768);
            mbar_expect_tx(lb + B_SW, 6 * 8192);
            #pragma unroll 1
            for (int b = 0; b < 6; b++) tma_load(SD_W + b * 8192, &mp.wqkv, (b >> 1) * D_ + nt * 64, mt * 128 + (b & 1) * 64, lb + B_SW);
        } else {
            #pragma unroll 1
            for (int s = 0; s < 3; s++) {
                mbar_wait(M_BAR + (s == 0 ? B_FG : B_FD), 0);
                mbar_expect_tx(lb + B_QF + 8 * s, Q_STB);
                qkv_load_w(mp, SB + (s == 0 ? 2 : s - 1) * Q_STB, s, lb + B_QF + 8 * s);
            }
            ctr_wait(&g_fl.x[mt], 16);
            fence_async_global();
            TL(32);
            #pragma unroll 1
            for (int s = 0; s < 3; s++) qkv_load_x(tx, SB + (s == 0 ? 2 : s - 1) * Q_STB, s, lb + B_QF + 8 * s);
            mbar_expect_tx(lb + B_SW, 4 * 12288);
            #pragma unroll 1
            for (int b = 0; b < 4; b++) tma_load(SD_W + b * 12288, &mp.r, c * 24, b * 256, lb + B_SW);
        }
        {
            uint32_t st = 0, ph = 0;
            #pragma unroll 1
            for (int k = 3; k < 16; k++) {
                mbar_wait(lb + B_QE + 8 * st, ph);
                const uint32_t fb = lb + B_QF + 8 * st, sa = SB + (st == 0 ? 2 : st - 1) * Q_STB;
                mbar_expect_tx(fb, Q_STB);
                qkv_load_x(tx, sa, k, fb);
                qkv_load_w(mp, sa, k, fb);
                if (++st == 3) { st = 0; ph ^= 1; }
            }
        }
        mbar_wait(lb + B_KVA, 0);
        mbar_arrive(lb + B_AF);
        {
            uint64_t ready = 0;
            #pragma unroll 1
            for (int j = 1; j < 32; j++) {
                const uint32_t s = j & 3, fb = lb + B_AF + 8 * s;
                const int n = j + 1, kb = (mt + ((n & 15) >> 1)) & 7;
                if (n == 16) ready = 0;
                if (n < 32 && !((ready >> (8 * kb)) & 1)) {
                    uint32_t cnt = 0;
                    do {
                        asm volatile("ld.acquire.gpu.global.u64 %0, [%1];" : "=l"(ready) : "l"(&g_fl.kv[L][nt * 2 + (n >> 4)][0]) : "memory");
                        poll_tick(cnt);
                    } while (!((ready >> (8 * kb)) & 1));
                    fence_async_global();
                }
                if (j >= 4) mbar_wait(lb + B_AE + 8 * s, ((j >> 2) - 1) & 1);
                if (j == 4) mbar_wait(lb + B_ARD, 0);
                mbar_expect_tx(fb, j == 1 || j == 31 ? 8192 : 16384);
                if (n < 32) bulk_load(A_RING + s * R_SLOT, g_kv + (size_t)((nt * 2 + (n >> 4)) * 16 + kb * 2 + (n & 1)) * KV_TILE, 8192, fb);
                if (j > 1) bulk_load(A_RING + s * R_SLOT + 8192, g_kv + (size_t)((nt * 2 + (j >> 4)) * 16 + ((mt + ((j & 15) >> 1)) & 7) * 2 + (j & 1)) * KV_TILE + 8192, 8192, fb);
                if (j == 1) TL(L * 32 + 21);
                if (ffn && j >= 8 && j < 12) {
                    const int b = j - 8;
                    if (b == 0) mbar_expect_tx(lb + B_GU0, 4 * 16384);
                    tma_load(F_GU0 + b * 16384, (b & 1) ? &mp.u : &mp.g, c * 32, (b >> 1) * 256, lb + B_GU0);
                }
                if (j == 14) l2_prefetch(reinterpret_cast<const char*>(wo) + (size_t)c * 16384, 16384);
                if (ffn && j >= 16 && j < 20) tma_prefetch((j & 1) ? &mp.u : &mp.g, c * 32, 512 + ((j >> 1) & 1) * 256);
                if (ffn && j >= 20 && j < 24) l2_prefetch(reinterpret_cast<const char*>(w_down) + (size_t)c * 65536 + (j - 20) * 16384, 16384);
            }
        }
        mbar_wait(lb + B_BRD, 0);
        #pragma unroll 1
        for (int k = 0; k < 16; k++) {
            const uint32_t s = k & 3, fb = lb + B_OF + 8 * s, sa = o_stage(s);
            if (k == 2) { mbar_wait(lb + B_AE, 1); mbar_wait(lb + B_AE + 8, 1); }
            if (k == 3) { mbar_wait(lb + B_AE + 16, 1); mbar_wait(lb + B_AE + 24, 1); }
            if (k >= 4) mbar_wait(lb + B_OE + 8 * s, ((k >> 2) - 1) & 1);
            mbar_expect_tx(fb, 32768);
            #pragma unroll
            for (int b = 0; b < 2; b++) tma_load5(sa + 16384 + b * 8192, &mp.wo[k >> 3], cb * 128 + b * 64, (k & 7) * 2, fb);
            if ((k & 7) == 0) {
                ctr_wait(&g_fl.o[L][blk][k >> 3], 16);
                fence_async_global();
                if (k) TL(L * 32 + 10);
            }
            #pragma unroll
            for (int a = 0; a < 2; a++) tma_load(sa + a * 8192, &mp.o, k * 64, blk * 128 + a * 64, fb);
            if (k == 4) {
                mbar_expect_tx(lb + B_RES, 32768);
                #pragma unroll
                for (int i = 0; i < 4; i++) tma_load(((i >> 1) ? XT1 : XT0) + (i & 1) * 8192, tx, cb * 128 + (i >> 1) * 64, blk * 128 + (i & 1) * 64, lb + B_RES);
            }
        }
        if (ffn) {
            mbar_expect_tx(lb + B_GU1, 4 * 16384);
            mbar_expect_tx(lb + B_WD, 4 * 16384);
            #pragma unroll 1
            for (int i = 0; i < 8; i++) {
                if (!(i & 1)) mbar_wait(lb + B_OE + 4 * i, 1);
                if (i < 4) tma_load(F_GU1 + i * 16384, (i & 1) ? &mp.u : &mp.g, c * 32, 512 + (i >> 1) * 256, lb + B_GU1);
                else tma_load3(F_WD + (i - 4) * 16384, &mp.d, 0, c * 32, (i - 4) * 4, lb + B_WD);
            }
        }
    }
}

__global__ void __launch_bounds__(384, 1) k_all(const __grid_constant__ Maps mp, const bf16* __restrict__ x0, const bf16* __restrict__ wo, const bf16* __restrict__ w_down,
                                                const bf16* __restrict__ w_r, bf16* __restrict__ out, const uint64_t dk0, const uint64_t dv0, const uint32_t ca) {
    extern __shared__ __align__(1024) char smem[];
    if (smem_u32(smem) != SB) __trap();
    const int wg = warp_uniform(threadIdx.x >> 7);
    if (threadIdx.x == 0) TL(0);
    if (threadIdx.x == 256) {
        tm_prefetch(&mp.x[0]); tm_prefetch(&mp.wqkv);
        #pragma unroll
        for (int s = 0; s < 3; s++) mbar_init(M_BAR + B_QF + 8 * s, 1);
        fence_mbar_init();
        #pragma unroll 1
        for (int s = 0; s < 3; s++) {
            const uint32_t sa = SB + (s == 0 ? 2 : s - 1) * Q_STB, fb = M_BAR + B_QF + 8 * s;
            mbar_expect_tx(fb, Q_STB);
            qkv_load_x(&mp.x[0], sa, s, fb);
            qkv_load_w(mp, sa, s, fb);
        }
    } else if (threadIdx.x >= 288 && threadIdx.x < 288 + 2 * (BAR_SET / 8)) {
        const uint32_t i = threadIdx.x - 288, o = (i % (BAR_SET / 8)) * 8;
        const bool two = (o >= B_QE && o < B_QE + 24) || (o >= B_OE && o < B_OE + 32);
        const bool eight = o == B_KVA || o == B_KVB || (o >= B_AE && o < B_OD + 32) || o == B_FG || o == B_FD || o == B_XS;
        if (i >= BAR_SET / 8 || o >= B_QE) mbar_init(M_BAR + i * 8, two ? 2 : eight ? 8 : 1);
        fence_mbar_init();
    }
    if (wg < 2) reset_exchange(threadIdx.x);
    __syncthreads();
    if (wg == 2) {
        reg_dec<40>();
        if (threadIdx.x >= 288) side_role(x0, w_r, out);
        else if (threadIdx.x == 256) producer_role(mp, x0, wo, w_down);
    } else {
        reg_inc<232>();
        #pragma unroll 1
        for (int L = 0; L < 2; L++)
        {
            const uint32_t lb = M_BAR + L * BAR_SET;
            uint32_t qa[8], qb[8];
            qkv_phase(L, lb, wg, qa, qb);
            attention_phase(L, lb, qa, qb, dk0, dv0, ca);
            tail_phase(L, lb, wg, w_r, out);
        }
    }
}

typedef CUresult (*EncodeFn)(CUtensorMap*, CUtensorMapDataType, cuuint32_t, void*, const cuuint64_t*, const cuuint64_t*, const cuuint32_t*,
                             const cuuint32_t*, CUtensorMapInterleave, CUtensorMapSwizzle, CUtensorMapL2promotion, CUtensorMapFloatOOBfill);

void make_map(EncodeFn enc, CUtensorMap* tm, const void* ptr, int rank, const cuuint64_t* dims, const cuuint64_t* strides, const cuuint32_t* box, CUtensorMapSwizzle sw) {
    const cuuint32_t es[5] = {1, 1, 1, 1, 1};
    enc(tm, CU_TENSOR_MAP_DATA_TYPE_BFLOAT16, rank, const_cast<void*>(ptr), dims, strides, box, es, CU_TENSOR_MAP_INTERLEAVE_NONE, sw,
        box[0] == 64 ? CU_TENSOR_MAP_L2_PROMOTION_L2_128B : CU_TENSOR_MAP_L2_PROMOTION_NONE, CU_TENSOR_MAP_FLOAT_OOB_FILL_NONE);
}
void make_map2(EncodeFn enc, CUtensorMap* tm, const void* ptr, uint64_t cols, uint64_t rows, uint32_t bc, uint32_t br, CUtensorMapSwizzle sw) {
    const cuuint64_t dims[2] = {cols, rows}, strides[1] = {cols * 2};
    const cuuint32_t box[2] = {bc, br};
    make_map(enc, tm, ptr, 2, dims, strides, box, sw);
}

}

extern "C" void kernel_launch(void* const* d_in, const int* in_sizes, int n_in, void* d_out, int out_size) {
    const bf16* x0 = (const bf16*)d_in[0];
    const bf16* wqkv = (const bf16*)d_in[1];
    const bf16* wo = (const bf16*)d_in[2];
    const bf16* w_r = (const bf16*)d_in[4];
    const bf16* w_gate = (const bf16*)d_in[5];
    const bf16* w_up = (const bf16*)d_in[6];
    const bf16* w_down = (const bf16*)d_in[7];

    EncodeFn enc = nullptr;
    cudaDriverEntryPointQueryResult qr;
    cudaGetDriverEntryPoint("cuTensorMapEncodeTiled", (void**)&enc, cudaEnableDefault, &qr);
    void *p_o, *p_x1;
    cudaGetSymbolAddress(&p_o, g_o); cudaGetSymbolAddress(&p_x1, g_x1);
    const CUtensorMapSwizzle S128 = CU_TENSOR_MAP_SWIZZLE_128B, S64 = CU_TENSOR_MAP_SWIZZLE_64B, S0 = CU_TENSOR_MAP_SWIZZLE_NONE;
    Maps mp;
    make_map2(enc, &mp.x[0], x0, D_, S_, 64, 64, S128); make_map2(enc, &mp.x[1], p_x1, D_, S_, 64, 64, S128);
    make_map2(enc, &mp.o, p_o, D_, S_, 64, 64, S128); make_map2(enc, &mp.wqkv, wqkv, 3 * D_, D_, 64, 64, S128);
    make_map2(enc, &mp.r, wqkv, 3 * D_, D_, 24, 256, S0);
    make_map2(enc, &mp.g, w_gate, FF, D_, 32, 256, S64); make_map2(enc, &mp.u, w_up, FF, D_, 32, 256, S64);
    for (int p = 0; p < 2; p++) {
        const cuuint64_t dims[5] = {D_, 2, 4, 4, 16}, strides[4] = {D_ * 2, 8 * D_ * 2, 2 * D_ * 2, 64 * D_ * 2};
        const cuuint32_t box[5] = {64, 2, 4, 4, 2};
        make_map(enc, &mp.wo[p], wo + (size_t)p * 32 * D_, 5, dims, strides, box, S128);
    }
    {
        const cuuint64_t dims[3] = {64, FF, 16}, strides[2] = {D_ * 2, 128};
        const cuuint32_t box[3] = {64, 32, 4};
        make_map(enc, &mp.d, w_down, 3, dims, strides, box, S128);
    }
    cudaFuncSetAttribute(k_all, cudaFuncAttributeMaxDynamicSharedMemorySize, K_SMEM);
    k_all<<<128, 384, K_SMEM, cudaStreamPerThread>>>(mp, x0, wo, w_down, w_r, (bf16*)d_out, desc_plain(A_RING, 2048, 128), desc_plain(A_RING + 8192, 128, 2048), 0x64A264A2u);
}
```

```cpp
#include <cuda_runtime.h>
#include <cuda_bf16.h>
#include <cuda_fp16.h>
#include <cuda.h>
#include <cudaTypedefs.h>
#include <stdint.h>

namespace {

typedef __nv_bfloat16 bf16;

constexpr int S_ = 2048, D_ = 1024, NH = 32, FF = 3584, NFC = FF / 32;
constexpr float LN_EPS = 1e-5f;
constexpr float QSCALE = 0.17677669529663687f * 1.4426950408889634f;
constexpr uint32_t EMPTY = 0xFFFFFFFFu;

constexpr int KV_TILE = 16384;
__device__ __align__(1024) char g_kv[NH * 16 * KV_TILE];
__device__ __align__(1024) bf16 g_o[S_ * D_];
__device__ __align__(1024) bf16 g_x1[S_ * D_];
__device__ __align__(16) float g_csum[8][3 * D_];
__device__ __align__(16) float g_cssq[8][3 * D_];
__device__ __align__(16) float2 g_rs0[S_];
__device__ uint4 g_qsave[128][4][256];
struct Xchg {
    uint4 part[2][16][8][128];
    float ypart[2][128][NFC][8];
    uint32_t cand[2][16][D_ / 2];
    uint4 hdr[2][8][16];
    float2 rs1[S_];
    float fix[3 * D_];
    uint32_t x2row[D_ / 2];
    uint8_t kv[2][NH][128];
    int o[2][16][2][32];
    uint8_t x[2][8][128];
};
union XchgFill { Xchg x; uint4 fill[128][3][256]; };
static_assert(sizeof(Xchg) <= sizeof(uint4) * 128 * 768, "exchange area");
__device__ __align__(128) XchgFill g_u;
#define g_x g_u.x
__device__ int g_pctr;

constexpr uint32_t SMEM_BASE = 1024;

__device__ __forceinline__ int tid_now() { int v; asm volatile("mov.u32 %0, %%tid.x;" : "=r"(v)); return v; }
__device__ __forceinline__ int cta_now() { int v; asm volatile("mov.u32 %0, %%ctaid.x;" : "=r"(v)); return v; }
__device__ __forceinline__ uint64_t opaque(uint64_t v) { uint64_t r; asm volatile("mov.b64 %0, %1;" : "=l"(r) : "l"(v)); return r; }
__device__ __forceinline__ uint32_t base32(uint32_t v) { uint32_t r; asm("mov.b32 %0, %1;" : "=r"(r) : "r"(v)); return r; }
__device__ __forceinline__ uint32_t smem_u32(const void* p) { return (uint32_t)__cvta_generic_to_shared(p); }
__device__ __forceinline__ void mbar_init(uint32_t bar, int cnt) { asm volatile("mbarrier.init.shared::cta.b64 [%0], %1;" :: "r"(bar), "r"(cnt) : "memory"); }
__device__ __forceinline__ void mbar_expect_tx(uint32_t bar, uint32_t bytes) { asm volatile("mbarrier.arrive.expect_tx.shared::cta.b64 _, [%0], %1;" :: "r"(bar), "r"(bytes) : "memory"); }
__device__ __forceinline__ void mbar_arrive(uint32_t bar) { asm volatile("mbarrier.arrive.shared::cta.b64 _, [%0];" :: "r"(bar) : "memory"); }
__device__ __forceinline__ void mbar_wait(uint32_t bar, uint32_t parity) {
    asm volatile("{\n.reg .pred p;\n.reg .u32 n;\nmov.u32 n, 0;\n"
                 "LAB_WAIT:\nmbarrier.try_wait.parity.shared::cta.b64 p, [%0], %1;\n@p bra LAB_DONE;\n"
                 "add.u32 n, n, 1;\nsetp.lt.u32 p, n, 0x4000000;\n@p bra LAB_WAIT;\ntrap;\nLAB_DONE:\n}" :: "r"(bar), "r"(parity) : "memory");
}
__device__ __forceinline__ void mbar_sleep(uint32_t bar, uint32_t parity) {
    asm volatile("{\n.reg .pred p;\n.reg .u32 n;\nmov.u32 n, 0;\n"
                 "LAB_WAIT:\nmbarrier.try_wait.parity.shared::cta.b64 p, [%0], %1, 0x10000;\n@p bra LAB_DONE;\n"
                 "add.u32 n, n, 1;\nsetp.lt.u32 p, n, 0x10000;\n@p bra LAB_WAIT;\ntrap;\nLAB_DONE:\n}" :: "r"(bar), "r"(parity) : "memory");
}
__device__ __forceinline__ void mbar_spin(uint32_t bar, uint32_t parity) {
    asm volatile("{\n.reg .pred p;\nLAB_WAIT:\nmbarrier.try_wait.parity.shared::cta.b64 p, [%0], %1;\n@!p bra LAB_WAIT;\n}" :: "r"(bar), "r"(parity) : "memory");
}
__device__ __forceinline__ uint32_t mbar_test(uint32_t bar, uint32_t parity) {
    uint32_t ok;
    asm volatile("{\n.reg .pred p;\nmbarrier.test_wait.parity.shared::cta.b64 p, [%1], %2;\nselp.u32 %0, 1, 0, p;\n}" : "=r"(ok) : "r"(bar), "r"(parity) : "memory");
    return ok;
}
__device__ __forceinline__ void mbar_spin_unless(uint32_t ok, uint32_t bar, uint32_t parity) {
    asm volatile("{\n.reg .pred p;\nsetp.ne.u32 p, %2, 0;\n@p bra LAB_DONE;\nLAB_WAIT:\nmbarrier.try_wait.parity.shared::cta.b64 p, [%0], %1;\n@!p bra LAB_WAIT;\nLAB_DONE:\n}"
                 :: "r"(bar), "r"(parity), "r"(ok) : "memory");
}
__device__ __forceinline__ bool elect_one() {
    uint32_t r;
    asm volatile("{\n.reg .pred p;\nelect.sync _|p, 0xffffffff;\nselp.u32 %0, 1, 0, p;\n}" : "=r"(r));
    return r != 0;
}
__device__ __forceinline__ void mbar_arrive_elect(uint32_t bar) {
    asm volatile("{\n.reg .pred p;\nelect.sync _|p, 0xffffffff;\n@p mbarrier.arrive.shared::cta.b64 _, [%0];\n}" :: "r"(bar) : "memory");
}
__device__ __forceinline__ void mbar_arrive_elect_p(uint32_t bar, uint32_t on) {
    asm volatile("{\n.reg .pred p, q;\nelect.sync _|p, 0xffffffff;\nsetp.ne.and.u32 q, %1, 0, p;\n@q mbarrier.arrive.shared::cta.b64 _, [%0];\n}" :: "r"(bar), "r"(on) : "memory");
}
__device__ __forceinline__ int warp_uniform(int v) { return __shfl_sync(0xffffffffu, v, 0); }
__device__ __forceinline__ void fence_mbar_init() { asm volatile("fence.mbarrier_init.release.cluster;" ::: "memory"); }
__device__ __forceinline__ void fence_async_smem() { asm volatile("fence.proxy.async.shared::cta;" ::: "memory"); }
__device__ __forceinline__ void fence_async_global() { asm volatile("fence.proxy.async.global;" ::: "memory"); }
__device__ __forceinline__ void named_sync(int id, int n) { asm volatile("bar.sync %0, %1;" :: "r"(id), "r"(n) : "memory"); }
__device__ __forceinline__ void named_arrive(int id, int n) { asm volatile("bar.arrive %0, %1;" :: "r"(id), "r"(n) : "memory"); }
__device__ __forceinline__ void bulk_load(uint32_t dst, const void* src, uint32_t bytes, uint32_t bar) {
    asm volatile("cp.async.bulk.shared::cluster.global.mbarrier::complete_tx::bytes [%0], [%1], %2, [%3];" :: "r"(dst), "l"(src), "r"(bytes), "r"(bar) : "memory");
}
__device__ __forceinline__ void bulk_store(void* dst, uint32_t src, uint32_t bytes) {
    asm volatile("cp.async.bulk.global.shared::cta.bulk_group [%0], [%1], %2;" :: "l"(dst), "r"(src), "r"(bytes) : "memory");
}
__device__ __forceinline__ void bulk_commit() { asm volatile("cp.async.bulk.commit_group;" ::: "memory"); }
__device__ __forceinline__ void bulk_wait() { asm volatile("cp.async.bulk.wait_group 0;" ::: "memory"); }
__device__ __forceinline__ void l2_prefetch(const void* src, uint32_t bytes) {
    asm volatile("cp.async.bulk.prefetch.L2.global [%0], %1;" :: "l"(src), "r"(bytes) : "memory");
}
__device__ __forceinline__ void tma_load(uint32_t dst, const CUtensorMap* tm, int c0, int c1, uint32_t bar) {
    asm volatile("cp.async.bulk.tensor.2d.shared::cluster.global.mbarrier::complete_tx::bytes [%0], [%1, {%3, %4}], [%2];"
                 :: "r"(dst), "l"(tm), "r"(bar), "r"(c0), "r"(c1) : "memory");
}
__device__ __forceinline__ void tma_load3(uint32_t dst, const CUtensorMap* tm, int c0, int c1, int c2, uint32_t bar) {
    asm volatile("cp.async.bulk.tensor.3d.shared::cluster.global.mbarrier::complete_tx::bytes [%0], [%1, {%3, %4, %5}], [%2];"
                 :: "r"(dst), "l"(tm), "r"(bar), "r"(c0), "r"(c1), "r"(c2) : "memory");
}
__device__ __forceinline__ void tma_load5(uint32_t dst, const CUtensorMap* tm, int c0, int c4, uint32_t bar) {
    asm volatile("cp.async.bulk.tensor.5d.shared::cluster.global.mbarrier::complete_tx::bytes [%0], [%1, {%3, %5, %5, %5, %4}], [%2];"
                 :: "r"(dst), "l"(tm), "r"(bar), "r"(c0), "r"(c4), "r"(0) : "memory");
}
__device__ __forceinline__ uint64_t policy_evict_first() { uint64_t p; asm volatile("createpolicy.fractional.L2::evict_first.b64 %0, 1.0;" : "=l"(p)); return p; }
__device__ __forceinline__ void tma_load_s(uint32_t dst, const CUtensorMap* tm, int c0, int c1, uint32_t bar, uint64_t pol) {
    asm volatile("cp.async.bulk.tensor.2d.shared::cluster.global.mbarrier::complete_tx::bytes.L2::cache_hint [%0], [%1, {%3, %4}], [%2], %5;"
                 :: "r"(dst), "l"(tm), "r"(bar), "r"(c0), "r"(c1), "l"(pol) : "memory");
}
__device__ __forceinline__ void tma_load3_s(uint32_t dst, const CUtensorMap* tm, int c0, int c1, int c2, uint32_t bar, uint64_t pol) {
    asm volatile("cp.async.bulk.tensor.3d.shared::cluster.global.mbarrier::complete_tx::bytes.L2::cache_hint [%0], [%1, {%3, %4, %5}], [%2], %6;"
                 :: "r"(dst), "l"(tm), "r"(bar), "r"(c0), "r"(c1), "r"(c2), "l"(pol) : "memory");
}
__device__ __forceinline__ void tma_store(const CUtensorMap* tm, uint32_t src, int c0, int c1) {
    asm volatile("cp.async.bulk.tensor.2d.global.shared::cta.bulk_group [%0, {%2, %3}], [%1];" :: "l"(tm), "r"(src), "r"(c0), "r"(c1) : "memory");
}
__device__ __forceinline__ void tma_prefetch(const CUtensorMap* tm, int c0, int c1) {
    asm volatile("cp.async.bulk.prefetch.tensor.2d.L2.global [%0, {%1, %2}];" :: "l"(tm), "r"(c0), "r"(c1) : "memory");
}
__device__ __forceinline__ void tm_prefetch(const CUtensorMap* tm) { asm volatile("prefetch.tensormap [%0];" :: "l"(tm) : "memory"); }
__device__ __forceinline__ void wg_fence() { asm volatile("wgmma.fence.sync.aligned;" ::: "memory"); }
__device__ __forceinline__ void wg_commit() { asm volatile("wgmma.commit_group.sync.aligned;" ::: "memory"); }
template <int N> __device__ __forceinline__ void wg_wait() { asm volatile("wgmma.wait_group.sync.aligned %0;" :: "n"(N) : "memory"); }
template <int N> __device__ __forceinline__ void pin(uint32_t (&r)[N]) {
    #pragma unroll
    for (int i = 0; i < N; i++) asm volatile("" : "+r"(r[i]) :: "memory");
}
template <int N> __device__ __forceinline__ void pin(float (&r)[N]) {
    #pragma unroll
    for (int i = 0; i < N; i++) asm volatile("" : "+f"(r[i]) :: "memory");
}
template <int N> __device__ __forceinline__ void reg_inc() { asm volatile("setmaxnreg.inc.sync.aligned.u32 %0;" :: "n"(N)); }
template <int N> __device__ __forceinline__ void reg_dec() { asm volatile("setmaxnreg.dec.sync.aligned.u32 %0;" :: "n"(N)); }
__host__ __device__ constexpr uint64_t desc_plain(uint32_t addr, uint32_t lbo, uint32_t sbo) {
    return (uint64_t)((addr & 0x3FFFF) >> 4) | ((uint64_t)(lbo >> 4) << 16) | ((uint64_t)(sbo >> 4) << 32);
}
__host__ __device__ constexpr uint64_t desc_sw128(uint32_t addr, uint32_t lbo, uint32_t sbo) { return desc_plain(addr, lbo, sbo) | (1ull << 62); }
__host__ __device__ constexpr uint64_t desc_sw64(uint32_t addr, uint32_t lbo, uint32_t sbo) { return desc_plain(addr, lbo, sbo) | (2ull << 62); }

__device__ __forceinline__ uint32_t lds32(uint32_t a) { uint32_t v; asm volatile("ld.shared.b32 %0, [%1];" : "=r"(v) : "r"(a) : "memory"); return v; }
__device__ __forceinline__ uint32_t lds16(uint32_t a) { uint32_t v; asm volatile("ld.shared.u16 %0, [%1];" : "=r"(v) : "r"(a) : "memory"); return v; }
__device__ __forceinline__ float ldsf(uint32_t a) { return __uint_as_float(lds32(a)); }
__device__ __forceinline__ float2 lds64f(uint32_t a) { float2 v; asm volatile("ld.shared.v2.f32 {%0, %1}, [%2];" : "=f"(v.x), "=f"(v.y) : "r"(a) : "memory"); return v; }
__device__ __forceinline__ uint4 lds128(uint32_t a) { uint4 v; asm volatile("ld.shared.v4.b32 {%0, %1, %2, %3}, [%4];" : "=r"(v.x), "=r"(v.y), "=r"(v.z), "=r"(v.w) : "r"(a) : "memory"); return v; }
__device__ __forceinline__ void sts16(uint32_t a, uint32_t v) { asm volatile("st.shared.b16 [%0], %1;" :: "r"(a), "h"((uint16_t)v) : "memory"); }
__device__ __forceinline__ void sts32(uint32_t a, uint32_t v) { asm volatile("st.shared.b32 [%0], %1;" :: "r"(a), "r"(v) : "memory"); }
__device__ __forceinline__ void stsf(uint32_t a, float v) { sts32(a, __float_as_uint(v)); }
__device__ __forceinline__ void sts64(uint32_t a, uint32_t x, uint32_t y) { asm volatile("st.shared.v2.b32 [%0], {%1, %2};" :: "r"(a), "r"(x), "r"(y) : "memory"); }
__device__ __forceinline__ void sts128(uint32_t a, uint32_t x, uint32_t y, uint32_t z, uint32_t w) { asm volatile("st.shared.v4.b32 [%0], {%1, %2, %3, %4};" :: "r"(a), "r"(x), "r"(y), "r"(z), "r"(w) : "memory"); }
__device__ __forceinline__ void stsm4(uint32_t a, uint32_t x, uint32_t y, uint32_t z, uint32_t w) {
    asm volatile("stmatrix.sync.aligned.m8n8.x4.shared.b16 [%0], {%1, %2, %3, %4};" :: "r"(a), "r"(x), "r"(y), "r"(z), "r"(w) : "memory");
}
__device__ __forceinline__ void ldsm4(uint32_t& a0, uint32_t& a1, uint32_t& a2, uint32_t& a3, uint32_t addr) {
    asm volatile("ldmatrix.sync.aligned.m8n8.x4.shared.b16 {%0,%1,%2,%3}, [%4];" : "=r"(a0), "=r"(a1), "=r"(a2), "=r"(a3) : "r"(addr) : "memory");
}
__device__ __forceinline__ void ldsm4t(uint32_t& a0, uint32_t& a1, uint32_t& a2, uint32_t& a3, uint32_t addr) {
    asm volatile("ldmatrix.sync.aligned.m8n8.x4.trans.shared.b16 {%0,%1,%2,%3}, [%4];" : "=r"(a0), "=r"(a1), "=r"(a2), "=r"(a3) : "r"(addr) : "memory");
}
__device__ __forceinline__ void mma_bf16(float (&d)[4], uint32_t a0, uint32_t a1, uint32_t a2, uint32_t a3, uint32_t b0, uint32_t b1) {
    asm("mma.sync.aligned.m16n8k16.row.col.f32.bf16.bf16.f32 {%0,%1,%2,%3}, {%4,%5,%6,%7}, {%8,%9}, {%0,%1,%2,%3};"
        : "+f"(d[0]), "+f"(d[1]), "+f"(d[2]), "+f"(d[3]) : "r"(a0), "r"(a1), "r"(a2), "r"(a3), "r"(b0), "r"(b1));
}
__device__ __forceinline__ void mma_f16(float (&d)[4], uint32_t a0, uint32_t a1, uint32_t a2, uint32_t a3, uint32_t b0, uint32_t b1) {
    asm("mma.sync.aligned.m16n8k16.row.col.f32.f16.f16.f32 {%0,%1,%2,%3}, {%4,%5,%6,%7}, {%8,%9}, {%0,%1,%2,%3};"
        : "+f"(d[0]), "+f"(d[1]), "+f"(d[2]), "+f"(d[3]) : "r"(a0), "r"(a1), "r"(a2), "r"(a3), "r"(b0), "r"(b1));
}
__device__ __forceinline__ void stg128_pred(void* p, const uint4& v, bool on) {
    asm volatile("{\n.reg .pred q;\nsetp.ne.u32 q, %5, 0;\n@q st.global.v4.b32 [%0], {%1, %2, %3, %4};\n}"
                 :: "l"(p), "r"(v.x), "r"(v.y), "r"(v.z), "r"(v.w), "r"((uint32_t)on) : "memory");
}
__device__ __forceinline__ void st_x32(void* p, uint32_t v) { asm volatile("st.relaxed.gpu.global.u32 [%0], %1;" :: "l"(p), "r"(v) : "memory"); }
__device__ __forceinline__ void st_x64(void* p, uint32_t x, uint32_t y) {
    asm volatile("{\n.reg .b64 v;\nmov.b64 v, {%1, %2};\nst.relaxed.gpu.global.b64 [%0], v;\n}" :: "l"(p), "r"(x), "r"(y) : "memory");
}
__device__ __forceinline__ void st_x128(void* p, uint32_t x, uint32_t y, uint32_t z, uint32_t w) {
    asm volatile("{\n.reg .b64 a, b;\n.reg .b128 v;\nmov.b64 a, {%1, %2};\nmov.b64 b, {%3, %4};\nmov.b128 v, {a, b};\nst.relaxed.gpu.global.b128 [%0], v;\n}"
                 :: "l"(p), "r"(x), "r"(y), "r"(z), "r"(w) : "memory");
}
__device__ __forceinline__ uint32_t ld_x32(const void* p) { uint32_t v; asm volatile("ld.relaxed.gpu.global.u32 %0, [%1];" : "=r"(v) : "l"(p) : "memory"); return v; }
__device__ __forceinline__ uint2 ld_x64(const void* p) {
    uint2 v; asm volatile("{\n.reg .b64 a;\nld.relaxed.gpu.global.b64 a, [%2];\nmov.b64 {%0, %1}, a;\n}" : "=r"(v.x), "=r"(v.y) : "l"(p) : "memory"); return v;
}
__device__ __forceinline__ uint4 ld_x128(const void* p) {
    uint4 v;
    asm volatile("{\n.reg .b64 a, b;\n.reg .b128 v;\nld.relaxed.gpu.global.b128 v, [%4];\nmov.b128 {a, b}, v;\nmov.b64 {%0, %1}, a;\nmov.b64 {%2, %3}, b;\n}"
                 : "=r"(v.x), "=r"(v.y), "=r"(v.z), "=r"(v.w) : "l"(p) : "memory");
    return v;
}
__device__ __forceinline__ void poll_tick(uint32_t& n) { asm volatile("{\n.reg .pred p;\nadd.u32 %0, %0, 1;\nsetp.ge.u32 p, %0, 0x800000;\n@p st.global.u32 [%1], %0;\n}" : "+r"(n) : "l"(0ull)); }
__device__ __forceinline__ void ctr_arrive(int* c) { asm volatile("red.release.gpu.global.add.s32 [%0], 1;" :: "l"(c) : "memory"); }
__device__ __forceinline__ void ctr_wait(const int* c, int target) {
    int v;
    uint32_t n = 0;
    #pragma unroll 1
    do {
        asm volatile("ld.acquire.gpu.global.s32 %0, [%1];" : "=r"(v) : "l"(c) : "memory");
        poll_tick(n);
    } while (v < target);
}
__device__ __forceinline__ void flags8_wait(const uint8_t* f, uint64_t mask) {
    uint32_t n = 0;
    uint64_t v;
    #pragma unroll 1
    do { asm volatile("ld.acquire.gpu.global.u64 %0, [%1];" : "=l"(v) : "l"(f) : "memory"); poll_tick(n); } while (v & mask);
}
__device__ __forceinline__ void flags16_wait(const uint8_t* f) {
    uint32_t n = 0;
    uint64_t v;
    #pragma unroll 1
    do {
        asm volatile("{\n.reg .b64 a, b;\n.reg .b128 v;\nld.acquire.gpu.global.b128 v, [%1];\nmov.b128 {a, b}, v;\nor.b64 %0, a, b;\n}" : "=l"(v) : "l"(f) : "memory");
        poll_tick(n);
    } while (v != 0);
}
__device__ __forceinline__ bool any_empty(const uint4& v) { return v.x == EMPTY || v.y == EMPTY || v.z == EMPTY || v.w == EMPTY; }
__device__ __forceinline__ bool warp_any(bool p) { return __any_sync(0xffffffffu, p); }

__device__ __forceinline__ float ex2(float x) { float y; asm("ex2.approx.ftz.f32 %0, %1;" : "=f"(y) : "f"(x)); return y; }
__device__ __forceinline__ float rsq(float x) { float y; asm("rsqrt.approx.ftz.f32 %0, %1;" : "=f"(y) : "f"(x)); return y; }
__device__ __forceinline__ float rcp(float x) { float y; asm("rcp.approx.ftz.f32 %0, %1;" : "=f"(y) : "f"(x)); return y; }
__device__ __forceinline__ uint32_t pack_bf16(float lo, float hi) { uint32_t r; asm("cvt.rn.bf16x2.f32 %0, %1, %2;" : "=r"(r) : "f"(hi), "f"(lo)); return r; }
__device__ __forceinline__ uint32_t pack_f16(float lo, float hi) { uint32_t r; asm("cvt.rn.f16x2.f32 %0, %1, %2;" : "=r"(r) : "f"(hi), "f"(lo)); return r; }
__device__ __forceinline__ float bf_lo(uint32_t v) { return __uint_as_float(v << 16); }
__device__ __forceinline__ float bf_hi(uint32_t v) { return __uint_as_float(v & 0xFFFF0000u); }
__device__ __forceinline__ float bf_round(float x) { return __uint_as_float(pack_bf16(0.f, x)); }
__device__ __forceinline__ void h2_unpack(uint32_t v, float& lo, float& hi) {
    asm("{.reg .f16 l, h; mov.b32 {l, h}, %2; cvt.f32.f16 %0, l; cvt.f32.f16 %1, h;}" : "=f"(lo), "=f"(hi) : "r"(v));
}
__device__ __forceinline__ uint32_t hadd2(uint32_t a, uint32_t b) { uint32_t r; asm("add.rn.f16x2 %0, %1, %2;" : "=r"(r) : "r"(a), "r"(b)); return r; }
__device__ __forceinline__ uint32_t hmax2(uint32_t a, uint32_t b) { uint32_t r; asm("max.f16x2 %0, %1, %2;" : "=r"(r) : "r"(a), "r"(b)); return r; }
__device__ __forceinline__ uint32_t badd2(uint32_t a, uint32_t b) { uint32_t r; asm("add.rn.bf16x2 %0, %1, %2;" : "=r"(r) : "r"(a), "r"(b)); return r; }
__device__ __forceinline__ uint32_t bmul2(uint32_t a, uint32_t b) { uint32_t r; asm("mul.rn.bf16x2 %0, %1, %2;" : "=r"(r) : "r"(a), "r"(b)); return r; }
__device__ __forceinline__ float warp_sum(float v) {
    #pragma unroll
    for (int o = 16; o > 0; o >>= 1) v += __shfl_xor_sync(0xffffffffu, v, o);
    return v;
}
__device__ __forceinline__ float quad_sum(float v) { v += __shfl_xor_sync(0xffffffffu, v, 1); return v + __shfl_xor_sync(0xffffffffu, v, 2); }
__device__ __forceinline__ float quad_max(float v) { v = fmaxf(v, __shfl_xor_sync(0xffffffffu, v, 1)); return fmaxf(v, __shfl_xor_sync(0xffffffffu, v, 2)); }
__device__ __forceinline__ uint32_t redux_max(uint32_t v) { uint32_t r; asm volatile("redux.sync.max.u32 %0, %1, 0xffffffff;" : "=r"(r) : "r"(v)); return r; }
__device__ __forceinline__ uint32_t redux_min(uint32_t v) { uint32_t r; asm volatile("redux.sync.min.u32 %0, %1, 0xffffffff;" : "=r"(r) : "r"(v)); return r; }
__device__ __forceinline__ uint32_t order_bits(float r) { const uint32_t u = __float_as_uint(r); return (u & 0x80000000u) ? ~u : (u | 0x80000000u); }
__device__ __forceinline__ uint32_t ln2(uint32_t v, float rstd, float nb) { return pack_bf16(fmaf(bf_lo(v), rstd, nb), fmaf(bf_hi(v), rstd, nb)); }
__device__ __forceinline__ uint32_t add_ln2(uint32_t v, float rstd, float nb) { return badd2(v, ln2(v, rstd, nb)); }

#define TL(TID, i)
#define CK(TID, i)

__device__ __forceinline__ void wg_gemm_n128(float (&d)[64], uint64_t desca, uint64_t desc) {
    asm volatile("{\n.reg .pred p;\nsetp.ne.b32 p, 1, 0;\n"
        "wgmma.mma_async.sync.aligned.m64n128k16.f32.bf16.bf16 "
        "{%0,%1,%2,%3,%4,%5,%6,%7,%8,%9,%10,%11,%12,%13,%14,%15,%16,%17,%18,%19,%20,%21,%22,%23,%24,%25,%26,%27,%28,%29,%30,%31,%32,%33,%34,%35,%36,%37,%38,%39,%40,%41,%42,%43,%44,%45,%46,%47,%48,%49,%50,%51,%52,%53,%54,%55,%56,%57,%58,%59,%60,%61,%62,%63}, "
        "%64, %65, p, 1, 1, 0, 1;\n}\n"
        : "+f"(d[0]), "+f"(d[1]), "+f"(d[2]), "+f"(d[3]), "+f"(d[4]), "+f"(d[5]), "+f"(d[6]), "+f"(d[7]), "+f"(d[8]), "+f"(d[9]), "+f"(d[10]), "+f"(d[11]),
          "+f"(d[12]), "+f"(d[13]), "+f"(d[14]), "+f"(d[15]), "+f"(d[16]), "+f"(d[17]), "+f"(d[18]), "+f"(d[19]), "+f"(d[20]), "+f"(d[21]), "+f"(d[22]), "+f"(d[23]),
          "+f"(d[24]), "+f"(d[25]), "+f"(d[26]), "+f"(d[27]), "+f"(d[28]), "+f"(d[29]), "+f"(d[30]), "+f"(d[31]), "+f"(d[32]), "+f"(d[33]), "+f"(d[34]), "+f"(d[35]),
          "+f"(d[36]), "+f"(d[37]), "+f"(d[38]), "+f"(d[39]), "+f"(d[40]), "+f"(d[41]), "+f"(d[42]), "+f"(d[43]), "+f"(d[44]), "+f"(d[45]), "+f"(d[46]), "+f"(d[47]),
          "+f"(d[48]), "+f"(d[49]), "+f"(d[50]), "+f"(d[51]), "+f"(d[52]), "+f"(d[53]), "+f"(d[54]), "+f"(d[55]), "+f"(d[56]), "+f"(d[57]), "+f"(d[58]), "+f"(d[59]),
          "+f"(d[60]), "+f"(d[61]), "+f"(d[62]), "+f"(d[63])
        : "l"(desca), "l"(desc));
}
__device__ __forceinline__ void wg_gemm_n192(float (&d)[96], uint64_t desca, uint64_t desc) {
    asm volatile("{\n.reg .pred p;\nsetp.ne.b32 p, 1, 0;\n"
        "wgmma.mma_async.sync.aligned.m64n192k16.f32.bf16.bf16 "
        "{%0,%1,%2,%3,%4,%5,%6,%7,%8,%9,%10,%11,%12,%13,%14,%15,%16,%17,%18,%19,%20,%21,%22,%23,%24,%25,%26,%27,%28,%29,%30,%31,%32,%33,%34,%35,%36,%37,%38,%39,%40,%41,%42,%43,%44,%45,%46,%47,%48,%49,%50,%51,%52,%53,%54,%55,%56,%57,%58,%59,%60,%61,%62,%63,%64,%65,%66,%67,%68,%69,%70,%71,%72,%73,%74,%75,%76,%77,%78,%79,%80,%81,%82,%83,%84,%85,%86,%87,%88,%89,%90,%91,%92,%93,%94,%95}, "
        "%96, %97, p, 1, 1, 0, 1;\n}\n"
        : "+f"(d[0]), "+f"(d[1]), "+f"(d[2]), "+f"(d[3]), "+f"(d[4]), "+f"(d[5]), "+f"(d[6]), "+f"(d[7]), "+f"(d[8]), "+f"(d[9]), "+f"(d[10]), "+f"(d[11]),
          "+f"(d[12]), "+f"(d[13]), "+f"(d[14]), "+f"(d[15]), "+f"(d[16]), "+f"(d[17]), "+f"(d[18]), "+f"(d[19]), "+f"(d[20]), "+f"(d[21]), "+f"(d[22]), "+f"(d[23]),
          "+f"(d[24]), "+f"(d[25]), "+f"(d[26]), "+f"(d[27]), "+f"(d[28]), "+f"(d[29]), "+f"(d[30]), "+f"(d[31]), "+f"(d[32]), "+f"(d[33]), "+f"(d[34]), "+f"(d[35]),
          "+f"(d[36]), "+f"(d[37]), "+f"(d[38]), "+f"(d[39]), "+f"(d[40]), "+f"(d[41]), "+f"(d[42]), "+f"(d[43]), "+f"(d[44]), "+f"(d[45]), "+f"(d[46]), "+f"(d[47]),
          "+f"(d[48]), "+f"(d[49]), "+f"(d[50]), "+f"(d[51]), "+f"(d[52]), "+f"(d[53]), "+f"(d[54]), "+f"(d[55]), "+f"(d[56]), "+f"(d[57]), "+f"(d[58]), "+f"(d[59]),
          "+f"(d[60]), "+f"(d[61]), "+f"(d[62]), "+f"(d[63]), "+f"(d[64]), "+f"(d[65]), "+f"(d[66]), "+f"(d[67]), "+f"(d[68]), "+f"(d[69]), "+f"(d[70]), "+f"(d[71]),
          "+f"(d[72]), "+f"(d[73]), "+f"(d[74]), "+f"(d[75]), "+f"(d[76]), "+f"(d[77]), "+f"(d[78]), "+f"(d[79]), "+f"(d[80]), "+f"(d[81]), "+f"(d[82]), "+f"(d[83]),
          "+f"(d[84]), "+f"(d[85]), "+f"(d[86]), "+f"(d[87]), "+f"(d[88]), "+f"(d[89]), "+f"(d[90]), "+f"(d[91]), "+f"(d[92]), "+f"(d[93]), "+f"(d[94]), "+f"(d[95])
        : "l"(desca), "l"(desc));
}
__device__ __forceinline__ void wg_qk_init(uint32_t (&d)[32], uint32_t a0, uint32_t a1, uint32_t a2, uint32_t a3, uint64_t desc) {
    asm volatile("{\n.reg .pred p;\nsetp.ne.b32 p, 0, 0;\n"
        "wgmma.mma_async.sync.aligned.m64n128k16.f16.f16.f16 "
        "{%0,%1,%2,%3,%4,%5,%6,%7,%8,%9,%10,%11,%12,%13,%14,%15,%16,%17,%18,%19,%20,%21,%22,%23,%24,%25,%26,%27,%28,%29,%30,%31}, "
        "{%32,%33,%34,%35}, %36, p, 1, 1, 0;\n}\n"
        : "=r"(d[0]), "=r"(d[1]), "=r"(d[2]), "=r"(d[3]), "=r"(d[4]), "=r"(d[5]), "=r"(d[6]), "=r"(d[7]), "=r"(d[8]), "=r"(d[9]), "=r"(d[10]), "=r"(d[11]),
          "=r"(d[12]), "=r"(d[13]), "=r"(d[14]), "=r"(d[15]), "=r"(d[16]), "=r"(d[17]), "=r"(d[18]), "=r"(d[19]), "=r"(d[20]), "=r"(d[21]), "=r"(d[22]), "=r"(d[23]),
          "=r"(d[24]), "=r"(d[25]), "=r"(d[26]), "=r"(d[27]), "=r"(d[28]), "=r"(d[29]), "=r"(d[30]), "=r"(d[31])
        : "r"(a0), "r"(a1), "r"(a2), "r"(a3), "l"(desc));
}
__device__ __forceinline__ void wg_qk_acc(uint32_t (&d)[32], uint32_t a0, uint32_t a1, uint32_t a2, uint32_t a3, uint64_t desc) {
    asm volatile("{\n.reg .pred p;\nsetp.ne.b32 p, 1, 0;\n"
        "wgmma.mma_async.sync.aligned.m64n128k16.f16.f16.f16 "
        "{%0,%1,%2,%3,%4,%5,%6,%7,%8,%9,%10,%11,%12,%13,%14,%15,%16,%17,%18,%19,%20,%21,%22,%23,%24,%25,%26,%27,%28,%29,%30,%31}, "
        "{%32,%33,%34,%35}, %36, p, 1, 1, 0;\n}\n"
        : "+r"(d[0]), "+r"(d[1]), "+r"(d[2]), "+r"(d[3]), "+r"(d[4]), "+r"(d[5]), "+r"(d[6]), "+r"(d[7]), "+r"(d[8]), "+r"(d[9]), "+r"(d[10]), "+r"(d[11]),
          "+r"(d[12]), "+r"(d[13]), "+r"(d[14]), "+r"(d[15]), "+r"(d[16]), "+r"(d[17]), "+r"(d[18]), "+r"(d[19]), "+r"(d[20]), "+r"(d[21]), "+r"(d[22]), "+r"(d[23]),
          "+r"(d[24]), "+r"(d[25]), "+r"(d[26]), "+r"(d[27]), "+r"(d[28]), "+r"(d[29]), "+r"(d[30]), "+r"(d[31])
        : "r"(a0), "r"(a1), "r"(a2), "r"(a3), "l"(desc));
}
__device__ __forceinline__ void wg_pv_init(uint32_t (&d)[10], uint32_t a0, uint32_t a1, uint32_t a2, uint32_t a3, uint64_t desc) {
    asm volatile("{\n.reg .pred p;\nsetp.ne.b32 p, 0, 0;\n"
        "wgmma.mma_async.sync.aligned.m64n40k16.f16.f16.f16 "
        "{%0,%1,%2,%3,%4,%5,%6,%7,%8,%9}, "
        "{%10,%11,%12,%13}, %14, p, 1, 1, 1;\n}\n"
        : "=r"(d[0]), "=r"(d[1]), "=r"(d[2]), "=r"(d[3]), "=r"(d[4]), "=r"(d[5]), "=r"(d[6]), "=r"(d[7]), "=r"(d[8]), "=r"(d[9])
        : "r"(a0), "r"(a1), "r"(a2), "r"(a3), "l"(desc));
}
__device__ __forceinline__ void wg_pv_acc(uint32_t (&d)[10], uint32_t a0, uint32_t a1, uint32_t a2, uint32_t a3, uint64_t desc) {
    asm volatile("{\n.reg .pred p;\nsetp.ne.b32 p, 1, 0;\n"
        "wgmma.mma_async.sync.aligned.m64n40k16.f16.f16.f16 "
        "{%0,%1,%2,%3,%4,%5,%6,%7,%8,%9}, "
        "{%10,%11,%12,%13}, %14, p, 1, 1, 1;\n}\n"
        : "+r"(d[0]), "+r"(d[1]), "+r"(d[2]), "+r"(d[3]), "+r"(d[4]), "+r"(d[5]), "+r"(d[6]), "+r"(d[7]), "+r"(d[8]), "+r"(d[9])
        : "r"(a0), "r"(a1), "r"(a2), "r"(a3), "l"(desc));
}

constexpr uint32_t SB = SMEM_BASE;
constexpr uint32_t R_SLOT = 18432, A_RING = SB, A_KP = SB + 73728, A_QX = SB + 81920, A_STB = SB + 98304;
constexpr uint32_t F_GU0 = SB + 98304, F_GU1 = SB + 163840;
__host__ __device__ constexpr uint32_t f_wd(uint32_t i) { return i < 3 ? SB + i * 16384 : A_QX; }
__host__ __device__ constexpr uint32_t o_a(uint32_t s) { return s == 0 ? SB : s == 1 ? A_QX : F_GU0 + (s - 2) * 32768; }
__host__ __device__ constexpr uint32_t o_b(uint32_t s) { return s < 2 ? SB + 16384 + s * 16384 : F_GU0 + 16384 + (s - 2) * 32768; }
constexpr uint32_t XT0 = SB + 49152, XT1 = XT0 + 16384;
constexpr uint32_t Q_ABYTES = 256 * 64 * 2, Q_STB = Q_ABYTES + 192 * 64 * 2;
constexpr uint32_t Q_CS = SB + 3 * Q_STB, Q_VS = Q_CS + 768, Q_RC = Q_VS + 256, Q_FIX = Q_RC + 2048;
constexpr uint32_t SD_VEC = SB + 176128, SD_W = SB + 180224;
static_assert(Q_FIX + 768 <= SD_VEC, "smem");
constexpr uint32_t M_RED = SB + 229376, M_BAR = M_RED + 2048, BAR_SET = 320, M_IVS = M_BAR + 2 * BAR_SET, M_SM = M_IVS + 128;
constexpr uint32_t M_F2 = M_SM;
constexpr uint32_t M_WS = M_SM + 16;
constexpr uint32_t M_SS = M_SM + 24;
constexpr uint32_t M_RT = M_SM + 32;
constexpr uint32_t M_KR = M_SM + 64;
constexpr uint32_t M_SR = M_SM + 128;
constexpr int K_SMEM = M_SR + 128 - SB;
static_assert(K_SMEM == 232448, "smem");
constexpr uint32_t B_QF = 0, B_QE = 24, B_WF = 48, B_KVA = 56, B_KVB = 64, B_ARD = 72, B_BRD = 80, B_AF = 88, B_AE = 120, B_OD = 152,
                   B_OF = 184, B_OE = 216, B_RES = 248, B_GU = 256, B_WD = 272, B_FG = 280, B_FD = 288, B_XS = 296, B_SW = 304, B_XRD = 312;
constexpr int NB_ML = 1, NB_STG = 2, NB_CONS = 3, NB_SIDE = 4;

struct Maps { CUtensorMap x[3], wqkv, o, wo[2], r, g, u, d; };
struct Route { float r, nb, rstd; int idx; };

template <int N>
__device__ __forceinline__ void halve(float (&v)[8], int lane, int bit) {
    const bool up = lane & bit;
    #pragma unroll
    for (int i = 0; i < N; i++) v[i] = (up ? v[N + i] : v[i]) + __shfl_xor_sync(0xffffffffu, up ? v[i] : v[N + i], bit);
}

__device__ __forceinline__ void prep_work(const bf16* __restrict__ x0, const bf16* __restrict__ w_r, uint32_t lb) {
    const int t = tid_now() - 288, c = cta_now(), lane = t & 31, warp = warp_uniform(t >> 5);
    mbar_wait(lb + B_QF, 0);
    #pragma unroll 1
    for (int r = warp; r < 17; r += 3) {
        const uint4* xp = reinterpret_cast<const uint4*>(r < 16 ? x0 + (size_t)(c * 16 + r) * D_ : w_r) + lane;
        uint4 u[4];
        #pragma unroll
        for (int j = 0; j < 4; j++) u[j] = __ldg(xp + j * 32);
        float s0 = 0.f, s1 = 0.f, q0 = 0.f, q1 = 0.f;
        #pragma unroll
        for (int j = 0; j < 4; j++) {
            const uint32_t w[4] = {u[j].x, u[j].y, u[j].z, u[j].w};
            #pragma unroll
            for (int e = 0; e < 4; e++) { const float a = bf_lo(w[e]), b = bf_hi(w[e]); s0 += a; s1 += b; q0 = fmaf(a, a, q0); q1 = fmaf(b, b, q1); }
        }
        s0 += s1; q0 += q1;
        float v = (lane & 16 ? q0 : s0) + __shfl_xor_sync(0xffffffffu, lane & 16 ? s0 : q0, 16);
        #pragma unroll
        for (int o = 8; o > 0; o >>= 1) v += __shfl_xor_sync(0xffffffffu, v, o);
        const float mean = v * (1.f / D_), sq = __shfl_xor_sync(0xffffffffu, mean, 16);
        if (lane == 0) {
            if (r < 16) g_rs0[c * 16 + r] = make_float2(fmaxf(sq - mean * mean, 0.f), mean);
            else stsf(M_WS, v);
        }
    }
    TL(288, 22);
    mbar_wait(lb + B_SW, 0);
    {
        float cs[8], cq[8];
        #pragma unroll
        for (int i = 0; i < 8; i++) { cs[i] = 0.f; cq[i] = 0.f; }
        const uint32_t wb = SD_W + warp * 8192 + (lane >> 3) * 128;
        #pragma unroll 2
        for (int r = 0; r < 32; r++) {
            const uint4 u = lds128(wb + (r >> 4) * 16384 + r * 512 + (((lane & 7) ^ ((r * 4 + (lane >> 3)) & 7)) << 4));
            const uint32_t w[4] = {u.x, u.y, u.z, u.w};
            #pragma unroll
            for (int e = 0; e < 4; e++) {
                const float a = bf_lo(w[e]), b = bf_hi(w[e]);
                cs[2*e] += a; cs[2*e+1] += b; cq[2*e] = fmaf(a, a, cq[2*e]); cq[2*e+1] = fmaf(b, b, cq[2*e+1]);
            }
        }
        halve<4>(cs, lane, 16); halve<2>(cs, lane, 8);
        halve<4>(cq, lane, 16); halve<2>(cq, lane, 8);
        const int col = warp * D_ + (c & 15) * 64 + (lane & 7) * 8 + (lane >> 3) * 2;
        *reinterpret_cast<float2*>(&g_csum[c >> 4][col]) = make_float2(cs[0], cs[1]);
        *reinterpret_cast<float2*>(&g_cssq[c >> 4][col]) = make_float2(cq[0], cq[1]);
    }
    named_sync(NB_SIDE, 96);
    if (t == 0) { TL(288, 23); ctr_arrive(&g_pctr); ctr_wait(&g_pctr, 128); TL(288, 24); }
    named_sync(NB_SIDE, 96);
}

__device__ __forceinline__ void epi_inputs(int L) {
    const int t = tid_now() - 288, c = cta_now(), mt = c >> 4, nt = c & 15, lane = t & 31;
    #pragma unroll 1
    for (int k = 0; k < 2; k++) {
        const int i = t + 96 * k, col = (i >> 6) * D_ + nt * 64 + (i & 63);
        float p[8], z[8];
        #pragma unroll
        for (int j = 0; j < 8; j++) { p[j] = __ldcg(&g_csum[j][col]); z[j] = __ldcg(&g_cssq[j][col]); }
        stsf(Q_CS + i * 4, ((p[0] + p[1]) + (p[2] + p[3])) + ((p[4] + p[5]) + (p[6] + p[7])));
        const float zz = ((z[0] + z[1]) + (z[2] + z[3])) + ((z[4] + z[5]) + (z[6] + z[7]));
        const float zs = warp_sum(zz);
        if (i < 128) { if (lane == 0) stsf(M_F2 + (i >> 5) * 4, zs); }
        else {
            const int e = (int)(__float_as_uint(zz) >> 23) - 127;
            const int sh = min(max(((e + 2) >> 1) + 3, -60), 60);
            sts32(Q_VS + (i - 128) * 4, (uint32_t)(127 - sh) << 23);
            sts16(M_IVS + (i - 128) * 2, (uint32_t)(127 + sh - 4) << 7);
        }
    }
    #pragma unroll 1
    for (int i = t; i < 256; i += 96) {
        uint2 sv;
        uint32_t n = 0;
        #pragma unroll 1
        do { sv = ld_x64((L ? g_x.rs1 : g_rs0) + mt * 256 + i); poll_tick(n); } while (warp_any(sv.x == EMPTY));
        const float2 s = make_float2(__uint_as_float(sv.x), __uint_as_float(sv.y));
        const float a = L ? 1.f + rsq(s.x + LN_EPS) : 1.f;
        sts64(Q_RC + i * 8, __float_as_uint(a * rsq(a * a * s.x + LN_EPS)), __float_as_uint(s.y));
    }
}

__device__ __forceinline__ void ffn_finish(int L, bf16* __restrict__ out) {
    const int t = tid_now() - 288, c = cta_now(), lane = t & 31, warp = warp_uniform(t >> 5);
    const uint4 rv = lds128(M_RT + 16 * L);
    const int idx = (int)rv.w;
    const uint32_t* xsrc = &g_x.cand[L][idx >> 7][(c >> 2) * 16 + (t & 3) * 4 + (c & 3)];
    const uint8_t* fsrc = &g_x.x[L][idx >> 8][((idx >> 7) & 1) * 8 + (c >> 4)];
    uint32_t xw, busy;
    float a[4] = {0.f, 0.f, 0.f, 0.f};
    {
        const float* src = &g_x.ypart[L][c][0][t * 4];
        uint4 v[3];
        uint32_t n = 0;
        #pragma unroll 1
        do {
            v[0] = ld_x128(src); v[1] = ld_x128(src + 384);
            v[2] = make_uint4(0u, 0u, 0u, 0u);
            xw = 0u; busy = 0u;
            if (warp == 0) {
                v[2] = ld_x128(src + 768); xw = ld_x32(xsrc);
                asm volatile("ld.relaxed.gpu.global.u8 %0, [%1];" : "=r"(busy) : "l"(fsrc) : "memory");
            }
            poll_tick(n);
        } while (warp_any(any_empty(v[0]) || any_empty(v[1]) || any_empty(v[2]) || xw == EMPTY || busy != 0));
        #pragma unroll
        for (int i = 0; i < 3; i++) { a[0] += __uint_as_float(v[i].x); a[1] += __uint_as_float(v[i].y); a[2] += __uint_as_float(v[i].z); a[3] += __uint_as_float(v[i].w); }
    }
    #pragma unroll
    for (int o = 2; o < 32; o <<= 1) {
        #pragma unroll
        for (int i = 0; i < 4; i++) a[i] += __shfl_xor_sync(0xffffffffu, a[i], o);
    }
    if (lane < 2) sts128(M_SR + warp * 32 + lane * 16, __float_as_uint(a[0]), __float_as_uint(a[1]), __float_as_uint(a[2]), __float_as_uint(a[3]));
    named_sync(NB_SIDE, 96);
    if (t < 4) {
        const float2 y0 = lds64f(M_SR + t * 8), y1 = lds64f(M_SR + 32 + t * 8), y2 = lds64f(M_SR + 64 + t * 8);
        const uint32_t y = pack_bf16(y0.x + y1.x + y2.x, y0.y + y1.y + y2.y);
        const float rsel = bf_round(rcp(1.f + __expf(-bf_round(__uint_as_float(rv.x)))));
        const uint32_t xn = ln2(xw, __uint_as_float(rv.z), __uint_as_float(rv.y));
        const uint32_t res = badd2(xw, badd2(xn, pack_bf16(bf_lo(y) * rsel, bf_hi(y) * rsel)));
        if (L == 0) st_x32(&g_x.x2row[c * 4 + t], res);
        else reinterpret_cast<uint32_t*>(out + (size_t)idx * D_)[c * 4 + t] = res;
    }
}

__device__ __forceinline__ void fix_row(uint32_t lb) {
    const int t = tid_now() - 288, c = cta_now(), lane = t & 31, warp = warp_uniform(t >> 5);
    uint4 v[2];
    {
        uint32_t n = 0;
        #pragma unroll 1
        do {
            v[0] = ld_x128(g_x.x2row + t * 4);
            v[1] = make_uint4(0u, 0u, 0u, 0u);
            if (warp == 0) v[1] = ld_x128(g_x.x2row + (96 + t) * 4);
            poll_tick(n);
        } while (warp_any(any_empty(v[0]) || any_empty(v[1])));
    }
    const uint32_t w[8] = {v[0].x, v[0].y, v[0].z, v[0].w, v[1].x, v[1].y, v[1].z, v[1].w};
    float su = 0.f, sq = 0.f;
    #pragma unroll
    for (int i = 0; i < 8; i++) { const float a = bf_lo(w[i]), b = bf_hi(w[i]); su += a + b; sq = fmaf(a, a, fmaf(b, b, sq)); }
    su = warp_sum(su); sq = warp_sum(sq);
    if (lane == 0) sts64(M_SR + 96 + warp * 8, __float_as_uint(su), __float_as_uint(sq));
    named_sync(NB_SIDE, 96);
    const float2 s0 = lds64f(M_SR + 96), s1 = lds64f(M_SR + 104), s2 = lds64f(M_SR + 112);
    const float mean = (s0.x + s1.x + s2.x) * (1.f / D_);
    const float rstd = rsq(fmaxf((s0.y + s1.y + s2.y) * (1.f / D_) - mean * mean, 0.f) + LN_EPS);
    #pragma unroll
    for (int i = 0; i < 2; i++) {
        const float nb = -mean * rstd;
        if (i == 0 || warp == 0) sts128(SD_VEC + (t + 96 * i) * 16, ln2(w[4*i], rstd, nb), ln2(w[4*i+1], rstd, nb), ln2(w[4*i+2], rstd, nb), ln2(w[4*i+3], rstd, nb));
    }
    named_sync(NB_SIDE, 96);
    TL(288, 32 + 22);
    mbar_wait(lb + B_SW, 0);
    float a[8];
    #pragma unroll
    for (int i = 0; i < 8; i++) a[i] = 0.f;
    const uint32_t xa = base32(SD_VEC + lane * 2), wa = base32(SD_W + lane * 48 + warp * 16);
    #pragma unroll 2
    for (int b = 0; b < 32; b++) {
        const float x = bf_lo(lds16(xa + b * 64));
        const uint4 u = lds128(wa + b * 1536);
        a[0] = fmaf(x, bf_lo(u.x), a[0]); a[1] = fmaf(x, bf_hi(u.x), a[1]); a[2] = fmaf(x, bf_lo(u.y), a[2]); a[3] = fmaf(x, bf_hi(u.y), a[3]);
        a[4] = fmaf(x, bf_lo(u.z), a[4]); a[5] = fmaf(x, bf_hi(u.z), a[5]); a[6] = fmaf(x, bf_lo(u.w), a[6]); a[7] = fmaf(x, bf_hi(u.w), a[7]);
    }
    halve<4>(a, lane, 16); halve<2>(a, lane, 8); halve<1>(a, lane, 4);
    a[0] = quad_sum(a[0]);
    if ((lane & 3) == 0) st_x32(&g_x.fix[c * 24 + warp * 8 + (lane >> 2)], __float_as_uint(a[0]));
    TL(288, 32 + 23);
    if (((int)lds32(M_RT + 12) >> 8) == (c >> 4)) {
        const float* src = &g_x.fix[(t >> 5) * D_ + (c & 15) * 64 + (t & 31) * 2];
        uint2 f;
        uint32_t n = 0;
        #pragma unroll 1
        do { f = ld_x64(src); poll_tick(n); } while (warp_any(f.x == EMPTY || f.y == EMPTY));
        sts64(Q_FIX + t * 8, f.x, f.y);
    }
}

#define GAPNS 700
__device__ __forceinline__ void flag_clear(uint8_t* f) { asm volatile("st.release.gpu.global.u8 [%0], 0;" :: "l"(f) : "memory"); }
__device__ __forceinline__ void side_role(const Maps& mp, const bf16* __restrict__ x0, const bf16* __restrict__ wo, const bf16* __restrict__ w_down, const bf16* __restrict__ w_r, bf16* __restrict__ out) {
    #pragma unroll 1
    for (int L = 0; L < 2; L++) {
        const uint32_t lb = M_BAR + L * BAR_SET;
        if (L == 0) prep_work(x0, w_r, lb);
        else fix_row(lb);
        epi_inputs(L);
        const int t = tid_now() - 288, c = cta_now(), mt = c >> 4, nt = c & 15, warp = warp_uniform(t >> 5);
        TL(288, L * 32 + 4);
        named_sync(NB_ML, 352);
        #pragma unroll 1
        for (int i = t; i < 512; i += 96) sts128(A_RING + (i >> 7) * R_SLOT + 16384 + (i & 127) * 16, 0x2C002C00u, 0x2C002C00u, 0x2C002C00u, 0x2C002C00u);
        fence_async_smem();
        named_arrive(NB_STG, 352);
        if (elect_one()) {
            if (warp == 2) {
                char* dst = g_kv + (size_t)nt * 32 * KV_TILE;
                const int r0 = ((2 * mt - 1) & 15) * KV_TILE, r1 = 2 * mt * KV_TILE;
                mbar_wait(lb + B_KVA, 0);
                bulk_store(dst + r0, A_KP, 8192);
                bulk_store(dst + r1, A_RING, 16384);
                bulk_store(dst + r1 + 24576, A_RING + R_SLOT + 8192, 8192);
                bulk_commit();
                bulk_wait();
                fence_async_global();
                flag_clear(&g_x.kv[L][nt * 2][mt]);
                mbar_arrive(lb + B_ARD);
                TL(352, L * 32 + 6);
                mbar_sleep(lb + B_AE + 16, 0);
                dst += 16 * KV_TILE;
                bulk_store(dst + r0, A_STB, 8192);
                bulk_store(dst + r1, A_STB + 8192, 16384);
                bulk_store(dst + r1 + 24576, A_STB + 24576, 8192);
                bulk_commit();
                bulk_wait();
                fence_async_global();
                flag_clear(&g_x.kv[L][nt * 2 + 1][mt]);
                const bool ffn = c < NFC;
                const uint64_t pol = policy_evict_first();
                mbar_expect_tx(lb + B_GU, ffn ? 131072 : 0);
                mbar_expect_tx(lb + B_WD, ffn ? 65536 : 0);
                l2_prefetch(reinterpret_cast<const char*>(wo) + (size_t)c * 16384, 16384);
                if (ffn) {
                    #pragma unroll 1
                    for (int i = 0; i < 12; i++) {
                        if (i < 8) tma_load_s(F_GU0 + i * 16384, (i & 1) ? &mp.u : &mp.g, c * 32, (i >> 1) * 256, lb + B_GU, pol);
                        else l2_prefetch(reinterpret_cast<const char*>(w_down) + (size_t)c * 65536 + (i - 8) * 16384, 16384);
                        __nanosleep(GAPNS);
                    }
                }
                mbar_sleep(lb + B_XS, 0);
                tma_store(&mp.x[L + 1], XT0, (c & 7) * 128, (c >> 3) * 128);
                tma_store(&mp.x[L + 1], XT1, (c & 7) * 128 + 64, (c >> 3) * 128);
                bulk_commit();
                bulk_wait();
                fence_async_global();
                flag_clear(&g_x.x[L][mt][nt]);
                mbar_arrive(lb + B_XRD);
                TL(352, L * 32 + 18);
            } else {
                #pragma unroll 1
                for (int p = 0; p < 2; p++) { mbar_sleep(lb + B_OD + (p * 2 + warp) * 8, 0); ctr_arrive(g_x.o[L][mt * 2 + warp][p]); }
            }
        }
        __syncwarp();
        mbar_sleep(lb + B_FD, 0);
        if (c == 0 && t == 0 && L == 0) g_pctr = 0;
        ffn_finish(L, out);
        TL(288, L * 32 + 20);
    }
}

template <int HH>
__device__ __forceinline__ void qkv_epi_head(const float (&acc0)[96], const float (&acc1)[96], const float (&cf)[4], const float (&nm)[4], uint32_t cs, float hs, uint32_t (&pk)[4][4]) {
    #pragma unroll
    for (int jj = 0; jj < 4; jj++) {
        const float2 c2 = lds64f(cs + (HH * 32 + jj * 8) * 4);
        float2 v2 = make_float2(1.f, 1.f);
        if (HH >= 4) v2 = lds64f(cs + (Q_VS - Q_CS) + ((HH & 1) * 32 + jj * 8) * 4);
        #pragma unroll
        for (int i = 0; i < 4; i++) {
            const float* a = (i >> 1) ? acc1 : acc0;
            const float sc = HH < 4 ? cf[i] * hs : cf[i];
            float x = fmaf(nm[i], c2.x, a[4 * (4 * HH + jj) + 2 * (i & 1)]) * sc;
            float y = fmaf(nm[i], c2.y, a[4 * (4 * HH + jj) + 2 * (i & 1) + 1]) * sc;
            if (HH >= 4) { x *= v2.x; y *= v2.y; }
            pk[i][jj] = pack_f16(x, y);
        }
    }
}
__device__ __forceinline__ void stage_kv(uint32_t dst, const uint32_t (&pk)[4][4]) {
    #pragma unroll
    for (int i = 0; i < 4; i++) stsm4(dst + (i >> 1) * 1024 + (i & 1) * 128, pk[i][0], pk[i][1], pk[i][2], pk[i][3]);
}
template <int OFF>
__device__ __forceinline__ void patch_row(float (&acc)[96], uint32_t fx) {
    #pragma unroll
    for (int j = 0; j < 24; j++) { const float2 f = lds64f(fx + j * 32); acc[4 * j + OFF] = f.x; acc[4 * j + OFF + 1] = f.y; }
}
__device__ __forceinline__ void head_scales(float fq, float fk, float& sq, float& sk, float& ss) {
    const bool ok = fq <= 16384.f && fk <= 16384.f && fq * fk <= 50000.f;
    const int a = min(max((((int)(__float_as_uint(fq) >> 23) - 125) >> 1) - 8, -60), 60), b = min(max((((int)(__float_as_uint(fk) >> 23) - 125) >> 1) - 8, -60), 60);
    sq = QSCALE * __uint_as_float((uint32_t)(ok ? 127 : 127 - a) << 23);
    sk = __uint_as_float((uint32_t)(ok ? 127 : 127 - b) << 23);
    ss = ok ? 0.f : __uint_as_float((uint32_t)(127 + a + b) << 23);
}

__device__ __forceinline__ void qkv_phase(int L, uint32_t lb, int wg, uint32_t (&qa)[8], uint32_t (&qb)[8]) {
    float acc0[96], acc1[96];
    #pragma unroll
    for (int i = 0; i < 96; i++) { acc0[i] = 0.f; acc1[i] = 0.f; }
    pin(acc0); pin(acc1);
    const bool leader = (tid_now() & 127) == 0;
    {
        uint32_t st = 0, ph = 0;
        #pragma unroll 1
        for (int k = 0; k < 16; k++) {
            mbar_spin(lb + B_QF + 8 * st, ph);
            const uint32_t sa = SB + st * Q_STB;
            const uint64_t da = desc_sw128(sa + wg * 16384, 16, 1024);
            const uint64_t db = desc_sw128(sa + Q_ABYTES, 8192, 1024);
            wg_fence();
            #pragma unroll
            for (int kk = 0; kk < 4; kk++) {
                wg_gemm_n192(acc0, da + kk * 2, db + kk * 128);
                wg_gemm_n192(acc1, da + (8192 >> 4) + kk * 2, db + kk * 128);
            }
            wg_commit();
            wg_wait<1>();
            if (leader && k > 0) mbar_arrive(lb + B_QE + 8 * (st == 0 ? 2 : st - 1));
            if (++st == 3) { st = 0; ph ^= 1; }
        }
    }
    wg_wait<0>();
    pin(acc0); pin(acc1);
    TL(0, L * 32 + 2); CK(0, L * 32 + 11);
    named_sync(NB_ML, 352);
    TL(0, L * 32 + 3);
    const int tid = tid_now(), lane = tid & 31, w = (tid >> 5) & 3, g = lane >> 2, t = lane & 3;
    const int lr0 = wg * 128 + w * 16 + g;
    float cf[4], nm[4];
    #pragma unroll
    for (int i = 0; i < 4; i++) { const float2 r = lds64f(base32(Q_RC + lr0 * 8) + ((i >> 1) * 64 + (i & 1) * 8) * 8); cf[i] = r.x; nm[i] = -r.y; }
    const uint32_t cs = base32(Q_CS + t * 8);
    if (L) {
        const int d = (int)lds32(M_RT + 12) - ((cta_now() >> 4) * 256 + lr0);
        if (__builtin_expect((d & ~72) == 0, 0)) {
            if (d == 0) { patch_row<0>(acc0, cs + (Q_FIX - Q_CS)); cf[0] = 1.f; nm[0] = 0.f; }
            else if (d == 8) { patch_row<2>(acc0, cs + (Q_FIX - Q_CS)); cf[1] = 1.f; nm[1] = 0.f; }
            else if (d == 64) { patch_row<0>(acc1, cs + (Q_FIX - Q_CS)); cf[2] = 1.f; nm[2] = 0.f; }
            else { patch_row<2>(acc1, cs + (Q_FIX - Q_CS)); cf[3] = 1.f; nm[3] = 0.f; }
        }
        __syncwarp();
    }
    float sqa, ska, sqb, skb;
    {
        const uint4 f = lds128(M_F2);
        float ssa, ssb;
        head_scales(__uint_as_float(f.x), __uint_as_float(f.z), sqa, ska, ssa);
        head_scales(__uint_as_float(f.y), __uint_as_float(f.w), sqb, skb, ssb);
        if (tid == 0) sts64(M_SS, __float_as_uint(ssa), __float_as_uint(ssb));
    }
    const uint32_t ko = base32((lane >> 3) * 2048 + (w * 16 + (lane & 7)) * 16);
    uint32_t pk[4][4];
    qkv_epi_head<2>(acc0, acc1, cf, nm, cs, ska, pk);
    stage_kv((wg ? A_RING : A_KP) + ko, pk);
    qkv_epi_head<4>(acc0, acc1, cf, nm, cs, 1.f, pk);
    stage_kv(A_RING + wg * R_SLOT + 8192 + ko, pk);
    fence_async_smem();
    __syncwarp();
    mbar_arrive_elect(lb + B_KVA);
    qkv_epi_head<3>(acc0, acc1, cf, nm, cs, skb, pk);
    stage_kv(A_STB + wg * 8192 + ko, pk);
    qkv_epi_head<5>(acc0, acc1, cf, nm, cs, 1.f, pk);
    stage_kv(A_STB + 16384 + wg * 8192 + ko, pk);
    qkv_epi_head<1>(acc0, acc1, cf, nm, cs, sqb, pk);
    #pragma unroll
    for (int u = 0; u < 2; u++)
        #pragma unroll
        for (int s = 0; s < 2; s++) sts128(A_QX + (u * 2 + s) * 4096 + tid * 16, pk[2*u][2*s], pk[2*u+1][2*s], pk[2*u][2*s+1], pk[2*u+1][2*s+1]);
    qkv_epi_head<0>(acc0, acc1, cf, nm, cs, sqa, pk);
    #pragma unroll
    for (int s = 0; s < 2; s++) {
        qa[4*s] = pk[0][2*s]; qa[4*s+1] = pk[1][2*s]; qa[4*s+2] = pk[0][2*s+1]; qa[4*s+3] = pk[1][2*s+1];
        qb[4*s] = pk[2][2*s]; qb[4*s+1] = pk[3][2*s]; qb[4*s+2] = pk[2][2*s+1]; qb[4*s+3] = pk[3][2*s+1];
    }
    fence_async_smem();
    named_sync(NB_STG, 352);
    TL(0, L * 32 + 5); CK(0, L * 32 + 12);
}

#define NPOLY 24
__host__ __device__ constexpr bool is_poly(int j) { return ((j + 1) * NPOLY / 32) != (j * NPOLY / 32); }
struct Shift { uint32_t f0, f1, n0, n1, bad; };

__device__ __forceinline__ uint32_t exp2_mufu(uint32_t s, uint32_t nm) {
    uint32_t r;
    asm("ex2.approx.f16x2 %0, %1;" : "=r"(r) : "r"(hadd2(s, nm)));
    return r;
}
__device__ __forceinline__ uint32_t exp2_fix(uint32_t s, uint32_t fm, uint32_t ca, uint32_t& U) {
    uint32_t G, D;
    asm("fma.rn.relu.f16x2 %0, %1, %2, %3;" : "=r"(U) : "r"(s), "r"(0x00400040u), "r"(fm));
    asm("fma.rn.f16x2 %0, %1, %2, %3;" : "=r"(G) : "r"(U & 0x003F003Fu), "r"(ca), "r"(0x98B898B8u));
    asm("{.reg .b32 n; neg.f16x2 n, %1; fma.rn.relu.f16x2 %0, %1, n, %2;}" : "=r"(D) : "r"(G), "r"(0x00570057u));
    return (U << 4) - D;
}
__device__ __forceinline__ void exp_tile(const uint32_t (&S)[32], uint32_t (&P)[32], Shift& h, uint32_t ca) {
    uint32_t pend = 0; bool have = false;
    uint32_t t0 = 0, t1 = 0; int cnt = 0;
    #pragma unroll
    for (int i = 0; i < 32; i++) {
        if (is_poly(i)) {
            uint32_t U;
            P[i] = exp2_fix(S[i], (i & 1) ? h.f1 : h.f0, ca, U);
            if (cnt % 3 == 0) t0 = U; else if (cnt % 3 == 1) t1 = U;
            else {
                uint32_t x; asm("lop3.b32 %0, %1, %2, %3, 0xFE;" : "=r"(x) : "r"(t0), "r"(t1), "r"(U));
                if (have) { asm("lop3.b32 %0, %0, %1, %2, 0xFE;" : "+r"(h.bad) : "r"(pend), "r"(x)); have = false; } else { pend = x; have = true; }
            }
            cnt++;
        } else P[i] = exp2_mufu(S[i], (i & 1) ? h.n1 : h.n0);
    }
    if (have) h.bad |= pend;
    pin(P);
}
__device__ __forceinline__ void unit_start(const uint32_t (&S)[32], Shift& h, uint32_t (&o2)[10]) {
    uint32_t m[4] = {S[0], S[1], S[2], S[3]};
    #pragma unroll
    for (int i = 1; i < 8; i++)
        #pragma unroll
        for (int e = 0; e < 4; e++) m[e] = hmax2(m[e], S[4 * i + e]);
    float a0, a1, c0, c1;
    h2_unpack(hadd2(m[0], m[2]), a0, a1); h2_unpack(hadd2(m[1], m[3]), c0, c1);
    const float big = 3145728.f;
    const float m0 = (fmaf(quad_sum(a0 + a1), 0.0625f, 5.25f) + big) - big, m1 = (fmaf(quad_sum(c0 + c1), 0.0625f, 5.25f) + big) - big;
    h.n0 = pack_f16(-m0, -m0); h.n1 = pack_f16(-m1, -m1);
    const float u0 = (15.f - m0) * 0x1p-18f, u1 = (15.f - m1) * 0x1p-18f;
    h.f0 = pack_f16(u0, u0); h.f1 = pack_f16(u1, u1);
    h.bad = fabsf(m0) <= 480.f && fabsf(m1) <= 480.f ? 0u : 0x8000u;
    #pragma unroll
    for (int i = 0; i < 10; i++) o2[i] = 0u;
}
__device__ __forceinline__ bf16* o_ptr(int pass, int unit) {
    const int c = cta_now(), tid = tid_now();
    const int row = (c >> 4) * 256 + (tid >> 7) * 128 + unit * 64 + ((tid >> 5) & 3) * 16 + ((tid & 31) >> 2);
    return g_o + (row * D_ + pass * 512 + (c & 15) * 32);
}
__device__ __forceinline__ uint32_t unit_end(const uint32_t (&o)[10], uint32_t bad, uint32_t lb, int pass, int unit) {
    const int tid = tid_now(), t = tid & 3;
    float v[20];
    uint32_t z = 0;
    #pragma unroll
    for (int i = 0; i < 10; i++) { h2_unpack(o[i], v[2 * i], v[2 * i + 1]); asm("fma.rn.f16x2 %0, %1, %0, %0;" : "+r"(z) : "r"(o[i])); }
    const float i0 = rcp(v[16]), i1 = rcp(v[18]);
    const uint32_t ia = base32(M_IVS + pass * 64 + t * 4);
    uint32_t r[8];
    #pragma unroll
    for (int j = 0; j < 4; j++) {
        const uint32_t iv = lds32(ia + j * 16);
        r[j] = bmul2(pack_bf16(v[4*j] * i0, v[4*j+1] * i0), iv);
        r[4 + j] = bmul2(pack_bf16(v[4*j+2] * i1, v[4*j+3] * i1), iv);
    }
    const bool good = v[16] >= 0.25f && v[18] >= 0.25f && (((bad & 0xF800F800u) | (z & 0x7FFF7FFFu) | lds32(M_SS + pass * 4)) == 0);
    const bool all = __all_sync(0xffffffffu, good);
    bf16* dst = o_ptr(pass, unit) + t * 8;
    stg128_pred(dst, make_uint4(r[0], r[1], r[2], r[3]), all);
    stg128_pred(dst + 8 * D_, make_uint4(r[4], r[5], r[6], r[7]), all);
    if (__builtin_expect(!all && pass == 0, 0)) {
        #pragma unroll
        for (int s = 0; s < 2; s++) g_qsave[cta_now()][unit * 2 + s][tid] = lds128(A_KP + (unit * 2 + s) * 4096 + tid * 16);
    }
    __syncwarp();
    mbar_arrive_elect_p(lb + B_OD + (pass * 2 + (tid >> 7)) * 8, all);
    return all ? 0u : 1u;
}
__device__ __forceinline__ void swap_q(uint32_t (&q)[8], uint32_t a) {
    asm volatile("{\n.reg .pred p;\nsetp.ne.u32 p, %8, 0;\n"
                 "@p st.shared.v4.b32 [%8 + -8192], {%0, %1, %2, %3};\n@p st.shared.v4.b32 [%8 + -4096], {%4, %5, %6, %7};\n"
                 "@p ld.shared.v4.b32 {%0, %1, %2, %3}, [%8];\n@p ld.shared.v4.b32 {%4, %5, %6, %7}, [%8 + 4096];\n}"
                 : "+r"(q[0]), "+r"(q[1]), "+r"(q[2]), "+r"(q[3]), "+r"(q[4]), "+r"(q[5]), "+r"(q[6]), "+r"(q[7]) : "r"(a) : "memory");
}
static_assert(A_QX == A_KP + 8192, "parking places");
template <bool INIT>
__device__ __forceinline__ void issue_pv(uint32_t (&o)[10], const uint32_t (&P)[32], uint64_t dv) {
    if (INIT) wg_pv_init(o, P[0], P[1], P[2], P[3], dv); else wg_pv_acc(o, P[0], P[1], P[2], P[3], dv);
    #pragma unroll
    for (int k = 1; k < 8; k++) wg_pv_acc(o, P[4*k], P[4*k+1], P[4*k+2], P[4*k+3], dv + k * 16);
}

__device__ __forceinline__ uint4 quad_transpose(uint32_t x0, uint32_t x1, uint32_t x2, uint32_t x3, int t) {
    const bool b0 = t & 1, b1 = t & 2;
    uint32_t s0 = b0 ? x0 : x1, s1 = b0 ? x2 : x3;
    s0 = __shfl_xor_sync(0xffffffffu, s0, 1); s1 = __shfl_xor_sync(0xffffffffu, s1, 1);
    const uint32_t y0 = b0 ? s0 : x0, y1 = b0 ? x1 : s0, y2 = b0 ? s1 : x2, y3 = b0 ? x3 : s1;
    uint32_t u0 = b1 ? y0 : y2, u1 = b1 ? y1 : y3;
    u0 = __shfl_xor_sync(0xffffffffu, u0, 2); u1 = __shfl_xor_sync(0xffffffffu, u1, 2);
    return b1 ? make_uint4(u0, u1, y2, y3) : make_uint4(y0, y1, u0, u1);
}
__device__ __forceinline__ uint32_t movm(uint32_t v) { uint32_t r; asm volatile("movmatrix.sync.aligned.m8n8.trans.b16 %0, %1;" : "=r"(r) : "r"(v)); return r; }
__device__ __forceinline__ void attn_repair(const uint32_t (&q)[8], uint32_t lb, int pass, int unit) {
    const int tid = tid_now(), g = (tid & 31) >> 2, t = tid & 3;
    float ss = ldsf(M_SS + pass * 4);
    if (ss == 0.f) ss = 1.f;
    const uint4 q0 = quad_transpose(q[0], q[2], q[4], q[6], t), q1 = quad_transpose(q[1], q[3], q[5], q[7], t);
    const char* kv = g_kv + (size_t)((cta_now() & 15) * 2 + pass) * 16 * KV_TILE + t * 2048 + g * 16;
    float o[4][4], m0 = -INFINITY, m1 = -INFINITY, l0 = 0.f, l1 = 0.f;
    #pragma unroll
    for (int j = 0; j < 4; j++) { o[j][0] = 0.f; o[j][1] = 0.f; o[j][2] = 0.f; o[j][3] = 0.f; }
    #pragma unroll 1
    for (int b = 0; b < 32; b++) {
        const char* p = kv + (b >> 1) * KV_TILE + (b & 1) * 1024;
        const char* pk = kv + (((b >> 1) - 1) & 15) * KV_TILE + (b & 1) * 1024;
        uint4 kf[8], vf[8];
        #pragma unroll
        for (int i = 0; i < 8; i++) { kf[i] = __ldcg(reinterpret_cast<const uint4*>(pk + i * 128)); vf[i] = __ldcg(reinterpret_cast<const uint4*>(p + 8192 + i * 128)); }
        float s[8][4];
        #pragma unroll
        for (int i = 0; i < 8; i++) {
            s[i][0] = 0.f; s[i][1] = 0.f; s[i][2] = 0.f; s[i][3] = 0.f;
            mma_f16(s[i], q0.x, q1.x, q0.y, q1.y, kf[i].x, kf[i].y); mma_f16(s[i], q0.z, q1.z, q0.w, q1.w, kf[i].z, kf[i].w);
        }
        float t0 = m0, t1 = m1;
        #pragma unroll
        for (int i = 0; i < 8; i++) { t0 = fmaxf(t0, fmaxf(s[i][0], s[i][1])); t1 = fmaxf(t1, fmaxf(s[i][2], s[i][3])); }
        t0 = quad_max(t0); t1 = quad_max(t1);
        const float a0 = ex2((m0 - t0) * ss), a1 = ex2((m1 - t1) * ss);
        m0 = t0; m1 = t1;
        l0 *= a0; l1 *= a1;
        #pragma unroll
        for (int j = 0; j < 4; j++) { o[j][0] *= a0; o[j][1] *= a0; o[j][2] *= a1; o[j][3] *= a1; }
        #pragma unroll
        for (int k = 0; k < 4; k++) {
            uint32_t pf[4];
            #pragma unroll
            for (int e = 0; e < 2; e++) {
                const float p0 = ex2((s[2*k+e][0] - m0) * ss), p1 = ex2((s[2*k+e][1] - m0) * ss), p2 = ex2((s[2*k+e][2] - m1) * ss), p3 = ex2((s[2*k+e][3] - m1) * ss);
                l0 += p0 + p1; l1 += p2 + p3;
                pf[2*e] = pack_f16(p0, p1); pf[2*e+1] = pack_f16(p2, p3);
            }
            mma_f16(o[0], pf[0], pf[1], pf[2], pf[3], movm(vf[2*k].x), movm(vf[2*k+1].x));
            mma_f16(o[1], pf[0], pf[1], pf[2], pf[3], movm(vf[2*k].y), movm(vf[2*k+1].y));
            mma_f16(o[2], pf[0], pf[1], pf[2], pf[3], movm(vf[2*k].z), movm(vf[2*k+1].z));
            mma_f16(o[3], pf[0], pf[1], pf[2], pf[3], movm(vf[2*k].w), movm(vf[2*k+1].w));
        }
    }
    const float i0 = 16.f * rcp(quad_sum(l0)), i1 = 16.f * rcp(quad_sum(l1));
    uint32_t* dst = reinterpret_cast<uint32_t*>(o_ptr(pass, unit)) + t;
    #pragma unroll
    for (int j = 0; j < 4; j++) {
        const uint32_t iv = lds32(M_IVS + (pass * 32 + t * 8 + j * 2) * 2);
        dst[j * 4] = pack_bf16(o[j][0] * i0 * bf_lo(iv), o[j][1] * i0 * bf_hi(iv));
        dst[j * 4 + 4 * D_] = pack_bf16(o[j][2] * i1 * bf_lo(iv), o[j][3] * i1 * bf_hi(iv));
    }
    __syncwarp();
    mbar_arrive_elect(lb + B_OD + (pass * 2 + (tid >> 7)) * 8);
}

__device__ __forceinline__ void load_gu(uint32_t (&f)[64], uint32_t src, int warp, int lane) {
    const uint32_t row = (warp & 3) * 64 + (lane >> 4) * 8 + (lane & 7), ch = (lane >> 3) & 1, sw = (lane >> 1) & 3;
    const uint32_t a0 = base32(src + (warp >> 2) * 32768 + row * 64 + ((ch ^ sw) << 4)), a1 = base32(a0 ^ 32);
    #pragma unroll
    for (int i = 0; i < 16; i++) ldsm4t(f[4*i], f[4*i+1], f[4*i+2], f[4*i+3], ((i & 1) ? a1 : a0) + ((i >> 1) & 1) * 16384 + (i >> 2) * 1024);
}

__device__ __forceinline__ void arrive_loaded(uint32_t bar, const uint32_t (&f)[64], uint32_t zero) {
    uint32_t x = 0;
    #pragma unroll
    for (int i = 0; i < 16; i++) x |= f[4 * i];
    mbar_arrive_elect(bar + (x & zero));
}
__device__ __forceinline__ void flush(uint32_t (&o2)[10], const uint32_t (&o)[10]) {
    #pragma unroll
    for (int i = 0; i < 10; i++) o2[i] = hadd2(o2[i], o[i]);
}
__device__ __forceinline__ void attention_phase(int L, uint32_t lb, uint32_t (&qa)[8], uint32_t (&qb)[8], uint64_t dk0, uint64_t dv0, uint32_t ca, uint32_t (&wa)[64], uint32_t zero) {
    uint32_t SA[32], SB_[32], PA[32], PB[32], oa[10], ob[10], oa2[10], ob2[10];
    Shift ha, hb;
    uint32_t fail = 0;
    ca += lds32(M_SS) >> 31;
    constexpr uint64_t SL = R_SLOT >> 4, KH = 4096 >> 4;
    uint64_t dkd = dk0 + ((A_KP - A_RING) >> 4);
    wg_fence();
    wg_qk_init(SA, qa[0], qa[1], qa[2], qa[3], dkd);
    wg_qk_acc(SA, qa[4], qa[5], qa[6], qa[7], dkd + KH);
    wg_qk_init(SB_, qb[0], qb[1], qb[2], qb[3], dkd);
    wg_commit();
    wg_wait<0>();
    pin(SA); pin(SB_);
    unit_start(SA, ha, oa2);
    exp_tile(SA, PA, ha, ca);
    #pragma unroll
    for (int i = 0; i < 10; i++) { ob[i] = 0u; ob2[i] = 0u; }
    hb = ha;
    #pragma unroll 1
    for (int it = 0; ; it++) {
        const uint32_t ph = it & 1;
        uint32_t qsw = 0;
        #pragma unroll
        for (int u = 0; u < 4; u++) {
            const uint64_t dk = opaque(dk0) + u * SL, dv = opaque(dv0) + u * SL;
            wg_fence();
            if (u == 0) { wg_qk_acc(SB_, qb[4], qb[5], qb[6], qb[7], dkd + KH); wg_commit(); }
            if (u == 0) issue_pv<true>(oa, PA, dv); else issue_pv<false>(oa, PA, dv);
            wg_qk_init(SA, qa[0], qa[1], qa[2], qa[3], dk);
            wg_qk_acc(SA, qa[4], qa[5], qa[6], qa[7], dk + KH);
            wg_commit();
            wg_wait<1>();
            pin(SB_); pin(ob);
            if (u == 0) {
                mbar_arrive_elect_p(lb + B_AE + 24, it);
                flush(ob2, ob);
                if (__builtin_expect((it & 3) == 0, 0)) {
                    if (it) fail |= unit_end(ob2, hb.bad, lb, 0, 1) << 1;
                    unit_start(SB_, hb, ob2);
                }
            } else mbar_arrive_elect(lb + B_AE + 8 * (u - 1));
            if (u == 3) swap_q(qb, qsw ? qsw + 8192 : 0u);
            uint32_t ready = 0;
            if (u < 3) ready = mbar_test(lb + B_AF + 8 * (u + 1), ph);
            exp_tile(SB_, PB, hb, ca);
            wg_fence();
            if (u == 0) issue_pv<true>(ob, PB, dv); else issue_pv<false>(ob, PB, dv);
            wg_qk_init(SB_, qb[0], qb[1], qb[2], qb[3], dk);
            if (u < 3) wg_qk_acc(SB_, qb[4], qb[5], qb[6], qb[7], dk + KH);
            wg_commit();
            if (u < 3) mbar_spin_unless(ready, lb + B_AF + 8 * (u + 1), ph);
            wg_wait<1>();
            pin(SA); pin(oa);
            if (u == 2) { qsw = it == 3 ? A_QX + tid_now() * 16 : 0u; swap_q(qa, qsw); }
            if (u == 3) {
                flush(oa2, oa);
                if (__builtin_expect((it & 3) == 3, 0)) {
                    TL(0, L * 32 + 7 + (it >> 2)); CK(0, L * 32 + 1 + (it >> 2));
                    if (it == 7) goto done;
                    fail |= unit_end(oa2, ha.bad, lb, 0, 0);
                    unit_start(SA, ha, oa2);
                }
            }
            exp_tile(SA, PA, ha, ca);
        }
        mbar_spin(lb + B_AF, ph ^ 1);
        wg_wait<0>();
        dkd = dk0 + 3 * SL;
    }
done:
    mbar_spin(lb + B_GU, 0);
    load_gu(wa, F_GU0, tid_now() >> 5, tid_now() & 31);
    fail |= unit_end(oa2, ha.bad, lb, 1, 0) << 2;
    arrive_loaded(lb + B_FG, wa, zero);
    wg_wait<0>();
    pin(ob);
    mbar_arrive_elect(lb + B_AE + 24);
    flush(ob2, ob);
    fail |= unit_end(ob2, hb.bad, lb, 1, 1) << 3;
    if (__builtin_expect(fail != 0, 0)) {
        #pragma unroll 1
        for (int r = 3; r >= 0; r--) {
            if ((fail >> r) & 1) {
                uint32_t q[8];
                #pragma unroll
                for (int i = 0; i < 8; i++) q[i] = r < 2 ? reinterpret_cast<const uint32_t*>(&g_qsave[cta_now()][r * 2 + (i >> 2)][tid_now()])[i & 3] : (r & 1) ? qb[i] : qa[i];
                attn_repair(q, lb, r >> 1, r & 1);
            }
        }
    }
    TL(0, L * 32 + 9); CK(0, L * 32 + 8);
}

#define OSPLIT 8
__device__ __forceinline__ void oproj_steps(float (&acc)[64], uint32_t lb, int wg, int k0, int k1) {
    const bool leader = (tid_now() & 127) == 0;
    #pragma unroll 1
    for (int k = k0; k < k1; k++) {
        const uint32_t st = k & 3;
        mbar_spin(lb + B_OF + 8 * st, (k >> 2) & 1);
        const uint64_t da = desc_sw128(o_a(st) + wg * 8192, 16, 1024);
        const uint64_t db = desc_sw128(o_b(st), 8192, 1024);
        wg_fence();
        #pragma unroll
        for (int kk = 0; kk < 4; kk++) wg_gemm_n128(acc, da + kk * 2, db + kk * 128);
        wg_commit();
        wg_wait<1>();
        if (leader && k > 0) mbar_arrive(lb + B_OE + 8 * ((k - 1) & 3));
    }
}

__device__ __forceinline__ void stage_tile(const uint32_t (&xa)[4], const uint32_t (&xv)[32], uint32_t lb) {
    #pragma unroll
    for (int m = 0; m < 8; m++) stsm4(xa[m & 3] + (m < 4 ? 0 : XT1 - XT0), xv[4*m], xv[4*m+1], xv[4*m+2], xv[4*m+3]);
    fence_async_smem();
    __syncwarp();
    mbar_arrive_elect(lb + B_XS);
}

__device__ __forceinline__ void tail_phase(int L, uint32_t lb, int wg, const bf16* __restrict__ w_r, const uint32_t (&wa)[64], uint32_t zero) {
    const int c = cta_now(), blk = c >> 3, cb = c & 7, tid = tid_now();
    const int lane = tid & 31, w = (tid >> 5) & 3, g = lane >> 2, t = lane & 3;
    const int lr0 = wg * 64 + w * 16 + g;
    uint32_t xa[4];
    #pragma unroll
    for (int m = 0; m < 4; m++) xa[m] = base32(XT0 + (wg * 64 + w * 16 + (lane & 15)) * 128 + (((lane >> 4) ^ (lane & 7) ^ (2 * m)) << 4));
    uint32_t xv[32];
    const bool ffn = c < NFC;
    uint32_t wb[64], wd[64];
    {
        float acc[64];
        #pragma unroll
        for (int i = 0; i < 64; i++) acc[i] = 0.f;
        pin(acc);
        uint32_t wv[16];
        #pragma unroll
        for (int j = 0; j < 16; j++) { wv[j] = 0x3F803F80u; if (g & 1) wv[j] = __ldg(reinterpret_cast<const uint32_t*>(w_r + cb * 128) + j * 4 + t); }
        float2 rs0 = make_float2(0.f, 0.f), rs1 = rs0;
        if (L) { rs0 = __ldcg(&g_x.rs1[blk * 128 + lr0]); rs1 = __ldcg(&g_x.rs1[blk * 128 + lr0 + 8]); }
        oproj_steps(acc, lb, wg, 0, OSPLIT);
        mbar_spin(lb + B_RES, 0);
        #pragma unroll
        for (int m = 0; m < 8; m++) ldsm4(xv[4*m], xv[4*m+1], xv[4*m+2], xv[4*m+3], xa[m & 3] + (m < 4 ? 0 : XT1 - XT0));
        if (L) {
            const float r0 = rsq(rs0.x + LN_EPS), r1 = rsq(rs1.x + LN_EPS);
            const float n0 = -rs0.y * r0, n1 = -rs1.y * r1;
            #pragma unroll
            for (int j = 0; j < 16; j++) { xv[2*j] = add_ln2(xv[2*j], r0, n0); xv[2*j+1] = add_ln2(xv[2*j+1], r1, n1); }
            const int d = (int)lds32(M_RT + 12) - (blk * 128 + lr0);
            if (__builtin_expect((d & ~8) == 0, 0)) {
                #pragma unroll
                for (int j = 0; j < 16; j++) {
                    const uint32_t sv = __ldcg(&g_x.x2row[cb * 64 + j * 4 + t]);
                    if (d == 0) xv[2*j] = sv; else xv[2*j+1] = sv;
                }
            }
            __syncwarp();
        }
        pin(xv);
        oproj_steps(acc, lb, wg, OSPLIT, 16);
        wg_wait<0>();
        pin(acc);
        TL(0, L * 32 + 11); CK(0, L * 32 + 13);
        float sa[4] = {0.f, 0.f, 0.f, 0.f}, sb[4] = {0.f, 0.f, 0.f, 0.f}, sc[4] = {0.f, 0.f, 0.f, 0.f};
        #pragma unroll
        for (int m = 0; m < 8; m++) {
            #pragma unroll
            for (int i = 0; i < 4; i++) xv[4*m+i] = badd2(xv[4*m+i], pack_bf16(acc[8*m + 2*i], acc[8*m + 2*i + 1]));
            mma_bf16(sa, xv[4*m], xv[4*m+1], xv[4*m+2], xv[4*m+3], wv[2*m], wv[2*m+1]);
            mma_bf16(sb, xv[4*m], xv[4*m+1], xv[4*m+2], xv[4*m+3], xv[4*m], xv[4*m+2]);
            mma_bf16(sc, xv[4*m], xv[4*m+1], xv[4*m+2], xv[4*m+3], xv[4*m+1], xv[4*m+3]);
        }
        if (t == (g >> 1)) {
            st_x128(&g_x.part[L][blk][cb][lr0], __float_as_uint(sa[0]), __float_as_uint((g & 1) ? sb[1] : sb[0]), __float_as_uint(sa[1]), 0u);
            st_x128(&g_x.part[L][blk][cb][lr0 + 8], __float_as_uint(sa[2]), __float_as_uint((g & 1) ? sc[3] : sc[2]), __float_as_uint(sa[3]), 0u);
        }
        __syncwarp();
    }
    TL(0, L * 32 + 12);
    float nb[2], rstd[2], score[2];
    {
        const uint4* src = &g_x.part[L][blk][2 * t][lr0];
        uint4 p[4];
        uint32_t n = 0;
        p[0] = ld_x128(src); p[1] = ld_x128(src + 128); p[2] = ld_x128(src + 8); p[3] = ld_x128(src + 136);
        load_gu(wb, F_GU1, tid >> 5, lane);
        if (L == 0) stage_tile(xa, xv, lb);
        #pragma unroll 1
        while (warp_any((p[0].w | p[1].w | p[2].w | p[3].w) != 0)) {
            p[0] = ld_x128(src); p[1] = ld_x128(src + 128); p[2] = ld_x128(src + 8); p[3] = ld_x128(src + 136);
            poll_tick(n);
        }
        const float ws = ldsf(M_WS);
        #pragma unroll
        for (int h = 0; h < 2; h++) {
            const float su = quad_sum(__uint_as_float(p[2*h].x) + __uint_as_float(p[2*h+1].x));
            const float sq = quad_sum(__uint_as_float(p[2*h].y) + __uint_as_float(p[2*h+1].y));
            const float sd = quad_sum(__uint_as_float(p[2*h].z) + __uint_as_float(p[2*h+1].z));
            const float mean = su * (1.f / D_), var = fmaxf(sq * (1.f / D_) - mean * mean, 0.f);
            rstd[h] = rsq(var + LN_EPS);
            nb[h] = -mean * rstd[h];
            score[h] = rstd[h] * (sd - mean * ws);
            if (L == 0 && cb == 0 && t == h) st_x64(&g_x.rs1[blk * 128 + lr0 + 8 * h], __float_as_uint(var), __float_as_uint(mean));
        }
    }
    TL(0, L * 32 + 13);
    {
        const uint32_t k0 = order_bits(score[0]), k1 = order_bits(score[1]);
        const uint32_t kb = max(k0, k1), m = redux_max(kb);
        const uint32_t mrow = redux_min(kb == m ? (k1 > k0 ? lr0 + 8 : lr0) : 0x7FFFFFFFu);
        if (lane == 0) sts64(M_KR + (tid >> 5) * 8, m, mrow);
        named_sync(NB_CONS, 256);
        const float2 e = lds64f(M_KR + (lane & 7) * 8);
        const uint32_t m2 = redux_max(__float_as_uint(e.x));
        const int d = (int)redux_min(__float_as_uint(e.x) == m2 ? __float_as_uint(e.y) : 0x7FFFFFFFu) - lr0;
        if ((d & ~8) == 0) {
            if (t == 0)
                st_x128(&g_x.hdr[L][cb][blk], __float_as_uint(d ? score[1] : score[0]), __float_as_uint(d ? nb[1] : nb[0]), __float_as_uint(d ? rstd[1] : rstd[0]), blk * 128 + lr0 + d);
            #pragma unroll
            for (int b = 0; b < 4; b++)
                st_x128(&g_x.cand[L][blk][cb * 64 + b * 16 + t * 4], d ? xv[8*b+1] : xv[8*b], d ? xv[8*b+3] : xv[8*b+2], d ? xv[8*b+5] : xv[8*b+4], d ? xv[8*b+7] : xv[8*b+6]);
        }
        __syncwarp();
    }
    if (L) {
        #pragma unroll
        for (int j = 0; j < 16; j++) { xv[2*j] = add_ln2(xv[2*j], rstd[0], nb[0]); xv[2*j+1] = add_ln2(xv[2*j+1], rstd[1], nb[1]); }
        stage_tile(xa, xv, lb);
    }
    {
        mbar_spin(lb + B_WD, 0);
        const uint32_t a0 = f_wd(tid >> 6) + ((tid >> 5) & 1) * 8192 + ((lane >> 4) * 8 + (lane & 7)) * 128, ch = ((lane >> 3) & 1) ^ (lane & 7);
        #pragma unroll
        for (int i = 0; i < 16; i++) ldsm4t(wd[4*i], wd[4*i+1], wd[4*i+2], wd[4*i+3], base32(a0 + ((ch ^ (i & 6)) << 4)) + (i >> 3) * 4096 + (i & 1) * 2048);
        arrive_loaded(lb + B_WF, wd, zero);
    }
    Route rt;
    {
        uint4 e;
        uint32_t n = 0;
        #pragma unroll 1
        do { e = ld_x128(&g_x.hdr[L][cb][lane & 15]); poll_tick(n); } while (warp_any(e.w == EMPTY));
        const uint32_t k = order_bits(__uint_as_float(e.x)), m = redux_max(k);
        rt.idx = (int)redux_min(k == m ? e.w : 0x7FFFFFFFu);
        rt.r = __shfl_sync(0xffffffffu, __uint_as_float(e.x), rt.idx >> 7);
        rt.nb = __shfl_sync(0xffffffffu, __uint_as_float(e.y), rt.idx >> 7);
        rt.rstd = __shfl_sync(0xffffffffu, __uint_as_float(e.z), rt.idx >> 7);
    }
    TL(0, L * 32 + 14);
    if (tid == 0) sts128(M_RT + 16 * L, __float_as_uint(rt.r), __float_as_uint(rt.nb), __float_as_uint(rt.rstd), rt.idx);
    if (ffn) {
        uint4 x[4];
        {
            const uint32_t* src = &g_x.cand[L][rt.idx >> 7][(tid >> 5) * 32 + t * 4];
            uint32_t n = 0;
            #pragma unroll 1
            do {
                x[0] = ld_x128(src); x[1] = ld_x128(src + 16); x[2] = ld_x128(src + 256); x[3] = ld_x128(src + 272);
                poll_tick(n);
            } while (warp_any(x[0].x == EMPTY || x[1].x == EMPTY || x[2].x == EMPTY || x[3].x == EMPTY));
        }
        TL(0, L * 32 + 15);
        float d[4][4];
        #pragma unroll
        for (int i = 0; i < 4; i++) { d[i][0] = 0.f; d[i][1] = 0.f; d[i][2] = 0.f; d[i][3] = 0.f; }
        #pragma unroll
        for (int k = 0; k < 8; k++) {
            const uint32_t b0 = ln2((k & 1) ? x[k >> 1].z : x[k >> 1].x, rt.rstd, rt.nb), b1 = ln2((k & 1) ? x[k >> 1].w : x[k >> 1].y, rt.rstd, rt.nb);
            const uint32_t* f = (k < 4 ? wa : wb) + (k & 3) * 16;
            #pragma unroll
            for (int i = 0; i < 4; i++) mma_bf16(d[i], f[4*i], f[4*i+1], f[4*i+2], f[4*i+3], b0, b1);
        }
        #pragma unroll
        for (int h = 0; h < 2; h++) {
            const float a = (t & 1) ? d[1][2*h] : d[0][2*h], b = (t & 1) ? d[3][2*h] : d[2][2*h];
            stsf(M_RED + ((tid >> 5) * 64 + t * 16 + h * 8 + g) * 4, (t & 2) ? b : a);
        }
        named_sync(NB_CONS, 256);
        TL(0, L * 32 + 16);
        float s0 = 0.f, s1 = 0.f;
        #pragma unroll
        for (int i = 0; i < 8; i++) { const float2 v = lds64f(base32(M_RED + lane * 8) + i * 256); s0 += v.x; s1 += v.y; }
        const uint32_t mine = pack_bf16(s0, s1), other = __shfl_xor_sync(0xffffffffu, mine, 16);
        const uint32_t gv = lane < 16 ? mine : other, uv = lane < 16 ? other : mine;
        const float g0 = bf_lo(gv), g1 = bf_hi(gv);
        const uint32_t hv = bmul2(pack_bf16(g0 * rcp(1.f + __expf(-g0)), g1 * rcp(1.f + __expf(-g1))), uv);
        uint32_t hb[4];
        #pragma unroll
        for (int i = 0; i < 4; i++) hb[i] = __shfl_sync(0xffffffffu, hv, 4 * i + t);
        float y[8][4];
        #pragma unroll
        for (int i = 0; i < 8; i++) {
            y[i][0] = 0.f; y[i][1] = 0.f; y[i][2] = 0.f; y[i][3] = 0.f;
            mma_bf16(y[i], wd[8*i], wd[8*i+1], wd[8*i+2], wd[8*i+3], hb[0], hb[1]);
            mma_bf16(y[i], wd[8*i+4], wd[8*i+5], wd[8*i+6], wd[8*i+7], hb[2], hb[3]);
        }
        float* dst = &g_x.ypart[L][(tid >> 5) * 16 + t * 4][c][g];
        #pragma unroll
        for (int i = 0; i < 2; i++)
            #pragma unroll
            for (int h = 0; h < 2; h++) {
                const float a = (t & 1) ? y[2 + i][2*h] : y[i][2*h], b = (t & 1) ? y[6 + i][2*h] : y[4 + i][2*h];
                st_x32(dst + (i * 2 + h) * (NFC * 8), __float_as_uint((t & 2) ? b : a));
            }
    }
    __syncwarp();
    mbar_arrive_elect(lb + B_FD);
    TL(0, L * 32 + 17);
}

__device__ __forceinline__ void qkv_load_w(const Maps& mp, uint32_t dst, int k, uint32_t fb) { tma_load3(dst, &mp.wqkv, (blockIdx.x & 15) * 64, k * 64, 0, fb); }
__device__ __forceinline__ void qkv_load_x(const CUtensorMap* tx, uint32_t sa, int k, uint32_t fb) {
    #pragma unroll
    for (int a = 0; a < 2; a++) tma_load(sa + a * 16384, tx, k * 64, (blockIdx.x >> 4) * 256 + a * 128, fb);
}
template <int S, bool FIRST>
__device__ __forceinline__ void oproj_load(const Maps& mp, uint32_t lb, int L, int it) {
    const int blk = blockIdx.x >> 3, cb = blockIdx.x & 7;
    const uint32_t fb = lb + B_OF + 8 * S;
    mbar_expect_tx(fb, 32768);
    #pragma unroll
    for (int b = 0; b < 2; b++) tma_load5(o_b(S) + b * 8192, &mp.wo[it >> 1], cb * 128 + b * 64, (it & 1) * 8 + S * 2, fb);
    if (FIRST && !(it & 1)) {
        ctr_wait(g_x.o[L][blk][it >> 1], 15);
        fence_async_global();
        TL(256, L * 32 + 10);
    }
    tma_load(o_a(S), &mp.o, it * 256 + S * 64, blk * 128, fb);
}
#define SWK 3
#define QEARLY 1
__device__ __forceinline__ void producer_role(const Maps& mp, const bf16* __restrict__ x0) {
    const int c = blockIdx.x, mt = c >> 4, nt = c & 15, blk = c >> 3, cb = c & 7;
    const bool ffn = c < NFC;
    const uint64_t pol = policy_evict_first();
    #pragma unroll 1
    for (int L = 0; L < 2; L++) {
        const uint32_t lb = M_BAR + L * BAR_SET;
        const CUtensorMap* tx = &mp.x[L];
        if (L == 0) {
            mbar_wait(lb + B_QF, 0);
            l2_prefetch(x0 + (size_t)c * 16 * D_, 32768);
            mbar_expect_tx(lb + B_SW, 6 * 8192);
            qkv_load_w(mp, SD_W, mt * 2, lb + B_SW);
            qkv_load_w(mp, SD_W + 24576, mt * 2 + 1, lb + B_SW);
        } else {
            mbar_sleep(M_BAR + B_WF, 0);
            mbar_wait(M_BAR + B_XRD, 0);
            #pragma unroll 1
            for (int s = 0; s < 3; s++) {
                if (s == QEARLY) mbar_sleep(M_BAR + B_FD, 0);
                mbar_expect_tx(lb + B_QF + 8 * s, Q_STB);
                qkv_load_w(mp, SB + s * Q_STB + Q_ABYTES, s, lb + B_QF + 8 * s);
                if (s == 0) {
                    flags16_wait(g_x.x[0][mt]);
                    fence_async_global();
                    TL(256, 32);
                }
                qkv_load_x(tx, SB + s * Q_STB, s, lb + B_QF + 8 * s);
            }
            mbar_expect_tx(lb + B_SW, 4 * 12288);
        }
        {
            uint32_t st = 0, ph = 0;
            #pragma unroll 1
            for (int k = 3; k < 16; k++) {
                mbar_sleep(lb + B_QE + 8 * st, ph);
                const uint32_t fb = lb + B_QF + 8 * st, sa = SB + st * Q_STB;
                mbar_expect_tx(fb, Q_STB);
                qkv_load_x(tx, sa, k, fb);
                qkv_load_w(mp, sa + Q_ABYTES, k, fb);
                if (L && k >= SWK && k < SWK + 4) tma_load(SD_W + (k - SWK) * 12288, &mp.r, c * 24, (k - SWK) * 256, lb + B_SW);
                if (++st == 3) { st = 0; ph ^= 1; }
            }
        }
        mbar_sleep(lb + B_KVA, 0);
        TL(256, L * 32 + 26);
        mbar_arrive(lb + B_AF);
        {
            const char* kv = g_kv + (size_t)nt * 32 * KV_TILE;
            const uint8_t* fl = g_x.kv[L][nt * 2];
            #pragma unroll
            for (int j = 1; j < 4; j++) {
                if (j & 1) { flags8_wait(fl, 0xFFull << (8 * ((mt + (j + 1) / 2) & 7))); fence_async_global(); }
                mbar_expect_tx(lb + B_AF + 8 * j, j == 1 ? 8192 : 16384);
                bulk_load(A_RING + j * R_SLOT, kv + ((2 * mt + j) & 15) * KV_TILE, j == 1 ? 8192 : 16384, lb + B_AF + 8 * j);
                if (j == 1) TL(256, L * 32 + 21);
            }
            mbar_wait(lb + B_ARD, 0);
            flags8_wait(fl, ~0ull);
            fence_async_global();
            #pragma unroll 1
            for (int it = 1; it < 8; it++) {
                #pragma unroll
                for (int u = 0; u < 4; u++) {
                    const char* src = kv + ((2 * mt + 4 * it + u) & 15) * KV_TILE;
                    const uint32_t fb = lb + B_AF + 8 * u, dst = A_RING + u * R_SLOT;
                    mbar_sleep(lb + B_AE + 8 * u, (it - 1) & 1);
                    if (u < 3 || (it & 3) != 3) {
                        mbar_expect_tx(fb, 16384);
                        bulk_load(dst, src, 16384, fb);
                    } else {
                        mbar_expect_tx(fb, it == 3 ? 16384 : 8192);
                        bulk_load(dst + 8192, src + 8192, 8192, fb);
                        if (it == 3) {
                            flags8_wait(fl + 128, ~0ull);
                            fence_async_global();
                            bulk_load(dst, src + 16 * KV_TILE, 8192, fb);
                            kv += 16 * KV_TILE;
                        }
                    }
                }
            }
        }
        mbar_sleep(lb + B_AE + 8, 1);
        oproj_load<0, true>(mp, lb, L, 0);
        mbar_sleep(lb + B_AE + 16, 1);
        oproj_load<1, false>(mp, lb, L, 0);
        mbar_wait(lb + B_FG, 0);
        oproj_load<2, false>(mp, lb, L, 0);
        oproj_load<3, false>(mp, lb, L, 0);
        mbar_wait(lb + B_AE + 24, 1);
        mbar_expect_tx(lb + B_RES, 32768);
        tma_load_s(XT0, tx, cb * 128, blk * 128, lb + B_RES, pol);
        tma_load_s(XT1, tx, cb * 128 + 64, blk * 128, lb + B_RES, pol);
        #pragma unroll 1
        for (int it = 1; it < 4; it++) {
            const uint32_t ph = (it - 1) & 1;
            mbar_wait(lb + B_OE, ph);      oproj_load<0, true>(mp, lb, L, it);
            mbar_wait(lb + B_OE + 8, ph);  oproj_load<1, false>(mp, lb, L, it);
            mbar_wait(lb + B_OE + 16, ph); oproj_load<2, false>(mp, lb, L, it);
            mbar_wait(lb + B_OE + 24, ph); oproj_load<3, false>(mp, lb, L, it);
        }
        if (ffn) {
            #pragma unroll 1
            for (int i = 0; i < 4; i++) {
                if (!(i & 1)) mbar_wait(lb + B_OE + 4 * i, 1);
                tma_load3_s(f_wd(i), &mp.d, 0, c * 32, i * 4, lb + B_WD, pol);
            }
        }
    }
}

__global__ void __launch_bounds__(384, 1) k_all(const __grid_constant__ Maps mp, const bf16* __restrict__ x0, const bf16* __restrict__ wo, const bf16* __restrict__ w_down,
                                                const bf16* __restrict__ w_r, bf16* __restrict__ out, const uint64_t dk0, const uint64_t dv0, const uint32_t ca, const uint32_t zero) {
    extern __shared__ __align__(1024) char smem[];
    if (smem_u32(smem) != SB) __trap();
    const int warp = warp_uniform(threadIdx.x >> 5), wg = warp >> 2;
    TL(0, 0);
    if (warp == 8) {
      if (elect_one()) {
        tm_prefetch(&mp.x[0]); tm_prefetch(&mp.wqkv);
        #pragma unroll
        for (int s = 0; s < 3; s++) mbar_init(M_BAR + B_QF + 8 * s, 1);
        fence_mbar_init();
        #pragma unroll 1
        for (int s = 0; s < 3; s++) {
            const uint32_t sa = SB + s * Q_STB, fb = M_BAR + B_QF + 8 * s;
            mbar_expect_tx(fb, Q_STB);
            qkv_load_x(&mp.x[0], sa, s, fb);
            qkv_load_w(mp, sa + Q_ABYTES, s, fb);
        }
      }
      __syncwarp();
    } else if (warp == 9 || warp == 10) {
        if (elect_one()) {
            const uint32_t lb = M_BAR + (warp - 9) * BAR_SET;
            #pragma unroll
            for (uint32_t o = 0; o <= B_XRD; o += 8) {
                const bool two = (o >= B_QE && o < B_QE + 24) || (o >= B_OE && o < B_OE + 32);
                const bool eight = o == B_KVA || o == B_KVB || (o >= B_AE && o < B_OD + 32) || o == B_FG || o == B_FD || o == B_XS || o == B_WF;
                if (o >= B_QE || warp == 10) mbar_init(lb + o, two ? 2 : eight ? 8 : 1);
            }
            fence_mbar_init();
        }
        __syncwarp();
    } else if (wg < 2) {
        #pragma unroll
        for (int i = 0; i < 3; i++) g_u.fill[blockIdx.x][i][threadIdx.x] = make_uint4(EMPTY, EMPTY, EMPTY, EMPTY);
    }
    __syncthreads();
    if (wg == 2) {
        reg_dec<40>();
        if (warp > 8) side_role(mp, x0, wo, w_down, w_r, out);
        else if (elect_one()) producer_role(mp, x0);
    } else {
        reg_inc<232>();
        #pragma unroll 1
        for (int L = 0; L < 2; L++)
        {
            const uint32_t lb = M_BAR + L * BAR_SET;
            uint32_t qa[8], qb[8], wa[64];
            qkv_phase(L, lb, wg, qa, qb);
            attention_phase(L, lb, qa, qb, dk0, dv0, ca, wa, zero);
            tail_phase(L, lb, wg, w_r, wa, zero);
        }
    }
}

typedef CUresult (*EncodeFn)(CUtensorMap*, CUtensorMapDataType, cuuint32_t, void*, const cuuint64_t*, const cuuint64_t*, const cuuint32_t*,
                             const cuuint32_t*, CUtensorMapInterleave, CUtensorMapSwizzle, CUtensorMapL2promotion, CUtensorMapFloatOOBfill);

void make_map(EncodeFn enc, CUtensorMap* tm, const void* ptr, int rank, const cuuint64_t* dims, const cuuint64_t* strides, const cuuint32_t* box, CUtensorMapSwizzle sw) {
    const cuuint32_t es[5] = {1, 1, 1, 1, 1};
    enc(tm, CU_TENSOR_MAP_DATA_TYPE_BFLOAT16, rank, const_cast<void*>(ptr), dims, strides, box, es, CU_TENSOR_MAP_INTERLEAVE_NONE, sw,
        box[0] == 64 ? CU_TENSOR_MAP_L2_PROMOTION_L2_128B : CU_TENSOR_MAP_L2_PROMOTION_NONE, CU_TENSOR_MAP_FLOAT_OOB_FILL_NONE);
}
void make_map2(EncodeFn enc, CUtensorMap* tm, const void* ptr, uint64_t cols, uint64_t rows, uint32_t bc, uint32_t br, CUtensorMapSwizzle sw) {
    const cuuint64_t dims[2] = {cols, rows}, strides[1] = {cols * 2};
    const cuuint32_t box[2] = {bc, br};
    make_map(enc, tm, ptr, 2, dims, strides, box, sw);
}

}

extern "C" void kernel_launch(void* const* d_in, const int* in_sizes, int n_in, void* d_out, int out_size) {
    const bf16* x0 = (const bf16*)d_in[0];
    const bf16* wqkv = (const bf16*)d_in[1];
    const bf16* wo = (const bf16*)d_in[2];
    const bf16* w_r = (const bf16*)d_in[4];
    const bf16* w_gate = (const bf16*)d_in[5];
    const bf16* w_up = (const bf16*)d_in[6];
    const bf16* w_down = (const bf16*)d_in[7];

    EncodeFn enc = nullptr;
    cudaDriverEntryPointQueryResult qr;
    cudaGetDriverEntryPoint("cuTensorMapEncodeTiled", (void**)&enc, cudaEnableDefault, &qr);
    void *p_o, *p_x1;
    cudaGetSymbolAddress(&p_o, g_o); cudaGetSymbolAddress(&p_x1, g_x1);
    const CUtensorMapSwizzle S128 = CU_TENSOR_MAP_SWIZZLE_128B, S64 = CU_TENSOR_MAP_SWIZZLE_64B, S0 = CU_TENSOR_MAP_SWIZZLE_NONE;
    Maps mp;
    make_map2(enc, &mp.x[0], x0, D_, S_, 64, 128, S128); make_map2(enc, &mp.x[1], p_x1, D_, S_, 64, 128, S128);
    make_map2(enc, &mp.x[2], d_out, D_, S_, 64, 128, S128);
    make_map2(enc, &mp.o, p_o, D_, S_, 64, 128, S128);
    {
        const cuuint64_t dims[3] = {D_, D_, 3}, strides[2] = {3 * D_ * 2, D_ * 2};
        const cuuint32_t box[3] = {64, 64, 3};
        make_map(enc, &mp.wqkv, wqkv, 3, dims, strides, box, S128);
    }
    make_map2(enc, &mp.r, wqkv, 3 * D_, D_, 24, 256, S0);
    make_map2(enc, &mp.g, w_gate, FF, D_, 32, 256, S64); make_map2(enc, &mp.u, w_up, FF, D_, 32, 256, S64);
    for (int p = 0; p < 2; p++) {
        const cuuint64_t dims[5] = {D_, 2, 4, 4, 16}, strides[4] = {D_ * 2, 8 * D_ * 2, 2 * D_ * 2, 64 * D_ * 2};
        const cuuint32_t box[5] = {64, 2, 4, 4, 2};
        make_map(enc, &mp.wo[p], wo + (size_t)p * 32 * D_, 5, dims, strides, box, S128);
    }
    {
        const cuuint64_t dims[3] = {64, FF, 16}, strides[2] = {D_ * 2, 128};
        const cuuint32_t box[3] = {64, 32, 4};
        make_map(enc, &mp.d, w_down, 3, dims, strides, box, S128);
    }
    cudaFuncSetAttribute(k_all, cudaFuncAttributeMaxDynamicSharedMemorySize, K_SMEM);
    k_all<<<128, 384, K_SMEM, cudaStreamPerThread>>>(mp, x0, wo, w_down, w_r, (bf16*)d_out, desc_plain(A_RING, 2048, 128), desc_plain(A_RING + 8192, 128, 2048), 0x64A264A2u, 0u);
}
```

```cpp
#include <cuda_runtime.h>
#include <cuda_bf16.h>
#include <cuda_fp16.h>
#include <cuda.h>
#include <cudaTypedefs.h>
#include <stdint.h>

namespace {

typedef __nv_bfloat16 bf16;

constexpr int S_ = 2048, D_ = 1024, NH = 32, FF = 3584, NFC = FF / 32;
constexpr float LN_EPS = 1e-5f;
constexpr float QSCALE = 0.17677669529663687f * 1.4426950408889634f;
constexpr uint32_t EMPTY = 0xFFFFFFFFu;

constexpr int KV_TILE = 16384;
__device__ __align__(1024) char g_kv[NH * 16 * KV_TILE];
__device__ __align__(1024) bf16 g_o[S_ * D_];
__device__ __align__(1024) bf16 g_x1[S_ * D_];
__device__ __align__(16) float2 g_cs[8][3 * D_];
__device__ __align__(16) float2 g_rs0[S_];
__device__ uint4 g_qsave[128][4][256];
struct Xchg {
    uint4 part[2][16][8][128];
    float ypart[2][128][NFC][8];
    uint32_t cand[2][16][D_ / 2];
    uint4 hdr[2][8][16];
    float2 rs1[S_];
    float fix[3 * D_];
    uint32_t x2row[D_ / 2];
    uint8_t kv[2][NH][128];
    int o[2][16][2][32];
    uint8_t x[2][8][128];
};
union XchgFill { Xchg x; uint4 fill[128][3][256]; };
static_assert(sizeof(Xchg) <= sizeof(uint4) * 128 * 768, "exchange area");
__device__ __align__(128) XchgFill g_u;
#define g_x g_u.x
__device__ int g_pctr;

constexpr uint32_t SMEM_BASE = 1024;

__device__ __forceinline__ int tid_now() { int v; asm volatile("mov.u32 %0, %%tid.x;" : "=r"(v)); return v; }
__device__ __forceinline__ int cta_now() { int v; asm volatile("mov.u32 %0, %%ctaid.x;" : "=r"(v)); return v; }
__device__ __forceinline__ uint64_t opaque(uint64_t v) { uint64_t r; asm volatile("mov.b64 %0, %1;" : "=l"(r) : "l"(v)); return r; }
__device__ __forceinline__ uint32_t base32(uint32_t v) { uint32_t r; asm("mov.b32 %0, %1;" : "=r"(r) : "r"(v)); return r; }
__device__ __forceinline__ uint32_t smem_u32(const void* p) { return (uint32_t)__cvta_generic_to_shared(p); }
__device__ __forceinline__ void mbar_init(uint32_t bar, int cnt) { asm volatile("mbarrier.init.shared::cta.b64 [%0], %1;" :: "r"(bar), "r"(cnt) : "memory"); }
__device__ __forceinline__ void mbar_expect_tx(uint32_t bar, uint32_t bytes) { asm volatile("mbarrier.arrive.expect_tx.shared::cta.b64 _, [%0], %1;" :: "r"(bar), "r"(bytes) : "memory"); }
__device__ __forceinline__ void mbar_arrive(uint32_t bar) { asm volatile("mbarrier.arrive.shared::cta.b64 _, [%0];" :: "r"(bar) : "memory"); }
__device__ __forceinline__ void mbar_sleep(uint32_t bar, uint32_t parity) {
    asm volatile("{\n.reg .pred p;\n.reg .u32 n;\nmov.u32 n, 0;\n"
                 "LAB_WAIT:\nmbarrier.try_wait.parity.shared::cta.b64 p, [%0], %1, 0x10000;\n@p bra LAB_DONE;\n"
                 "add.u32 n, n, 1;\nsetp.lt.u32 p, n, 0x10000;\n@p bra LAB_WAIT;\ntrap;\nLAB_DONE:\n}" :: "r"(bar), "r"(parity) : "memory");
}
__device__ __forceinline__ void mbar_nap(uint32_t bar, uint32_t parity) {
    asm volatile("{\n.reg .pred p;\nLAB_WAIT:\nmbarrier.try_wait.parity.shared::cta.b64 p, [%0], %1, 0x10000;\n@!p bra LAB_WAIT;\n}" :: "r"(bar), "r"(parity) : "memory");
}
__device__ __forceinline__ void mbar_spin(uint32_t bar, uint32_t parity) {
    asm volatile("{\n.reg .pred p;\nLAB_WAIT:\nmbarrier.try_wait.parity.shared::cta.b64 p, [%0], %1;\n@!p bra LAB_WAIT;\n}" :: "r"(bar), "r"(parity) : "memory");
}
__device__ __forceinline__ uint32_t mbar_test(uint32_t bar, uint32_t parity) {
    uint32_t ok;
    asm volatile("{\n.reg .pred p;\nmbarrier.test_wait.parity.shared::cta.b64 p, [%1], %2;\nselp.u32 %0, 1, 0, p;\n}" : "=r"(ok) : "r"(bar), "r"(parity) : "memory");
    return ok;
}
__device__ __forceinline__ void mbar_spin_unless(uint32_t ok, uint32_t bar, uint32_t parity) {
    asm volatile("{\n.reg .pred p;\nsetp.ne.u32 p, %2, 0;\n@p bra LAB_DONE;\nLAB_WAIT:\nmbarrier.try_wait.parity.shared::cta.b64 p, [%0], %1;\n@!p bra LAB_WAIT;\nLAB_DONE:\n}"
                 :: "r"(bar), "r"(parity), "r"(ok) : "memory");
}
__device__ __forceinline__ bool elect_one() {
    uint32_t r;
    asm volatile("{\n.reg .pred p;\nelect.sync _|p, 0xffffffff;\nselp.u32 %0, 1, 0, p;\n}" : "=r"(r));
    return r != 0;
}
__device__ __forceinline__ void mbar_arrive_elect(uint32_t bar) {
    asm volatile("{\n.reg .pred p;\nelect.sync _|p, 0xffffffff;\n@p mbarrier.arrive.shared::cta.b64 _, [%0];\n}" :: "r"(bar) : "memory");
}
__device__ __forceinline__ void mbar_arrive_elect_p(uint32_t bar, uint32_t on) {
    asm volatile("{\n.reg .pred p, q;\nelect.sync _|p, 0xffffffff;\nsetp.ne.and.u32 q, %1, 0, p;\n@q mbarrier.arrive.shared::cta.b64 _, [%0];\n}" :: "r"(bar), "r"(on) : "memory");
}
__device__ __forceinline__ int warp_uniform(int v) { return __shfl_sync(0xffffffffu, v, 0); }
__device__ __forceinline__ void fence_mbar_init() { asm volatile("fence.mbarrier_init.release.cluster;" ::: "memory"); }
__device__ __forceinline__ void fence_async_smem() { asm volatile("fence.proxy.async.shared::cta;" ::: "memory"); }
__device__ __forceinline__ void fence_async_global() { asm volatile("fence.proxy.async.global;" ::: "memory"); }
__device__ __forceinline__ void named_sync(int id, int n) { asm volatile("bar.sync %0, %1;" :: "r"(id), "r"(n) : "memory"); }
__device__ __forceinline__ void named_arrive(int id, int n) { asm volatile("bar.arrive %0, %1;" :: "r"(id), "r"(n) : "memory"); }
__device__ __forceinline__ void bulk_load(uint32_t dst, const void* src, uint32_t bytes, uint32_t bar) {
    asm volatile("cp.async.bulk.shared::cluster.global.mbarrier::complete_tx::bytes [%0], [%1], %2, [%3];" :: "r"(dst), "l"(src), "r"(bytes), "r"(bar) : "memory");
}
__device__ __forceinline__ void bulk_store(void* dst, uint32_t src, uint32_t bytes) {
    asm volatile("cp.async.bulk.global.shared::cta.bulk_group [%0], [%1], %2;" :: "l"(dst), "r"(src), "r"(bytes) : "memory");
}
__device__ __forceinline__ void bulk_commit() { asm volatile("cp.async.bulk.commit_group;" ::: "memory"); }
__device__ __forceinline__ void bulk_wait() { asm volatile("cp.async.bulk.wait_group 0;" ::: "memory"); }
__device__ __forceinline__ void l2_prefetch(const void* src, uint32_t bytes) {
    asm volatile("cp.async.bulk.prefetch.L2.global [%0], %1;" :: "l"(src), "r"(bytes) : "memory");
}
__device__ __forceinline__ void tma_load(uint32_t dst, const CUtensorMap* tm, int c0, int c1, uint32_t bar) {
    asm volatile("cp.async.bulk.tensor.2d.shared::cluster.global.mbarrier::complete_tx::bytes [%0], [%1, {%3, %4}], [%2];"
                 :: "r"(dst), "l"(tm), "r"(bar), "r"(c0), "r"(c1) : "memory");
}
__device__ __forceinline__ void tma_load3(uint32_t dst, const CUtensorMap* tm, int c0, int c1, int c2, uint32_t bar) {
    asm volatile("cp.async.bulk.tensor.3d.shared::cluster.global.mbarrier::complete_tx::bytes [%0], [%1, {%3, %4, %5}], [%2];"
                 :: "r"(dst), "l"(tm), "r"(bar), "r"(c0), "r"(c1), "r"(c2) : "memory");
}
__device__ __forceinline__ void tma_load5(uint32_t dst, const CUtensorMap* tm, int c0, int c4, uint32_t bar) {
    asm volatile("cp.async.bulk.tensor.5d.shared::cluster.global.mbarrier::complete_tx::bytes [%0], [%1, {%3, %5, %5, %5, %4}], [%2];"
                 :: "r"(dst), "l"(tm), "r"(bar), "r"(c0), "r"(c4), "r"(0) : "memory");
}
__device__ __forceinline__ uint64_t policy_evict_first() { uint64_t p; asm volatile("createpolicy.fractional.L2::evict_first.b64 %0, 1.0;" : "=l"(p)); return p; }
__device__ __forceinline__ void tma_load_s(uint32_t dst, const CUtensorMap* tm, int c0, int c1, uint32_t bar, uint64_t pol) {
    asm volatile("cp.async.bulk.tensor.2d.shared::cluster.global.mbarrier::complete_tx::bytes.L2::cache_hint [%0], [%1, {%3, %4}], [%2], %5;"
                 :: "r"(dst), "l"(tm), "r"(bar), "r"(c0), "r"(c1), "l"(pol) : "memory");
}
__device__ __forceinline__ void tma_load3_s(uint32_t dst, const CUtensorMap* tm, int c0, int c1, int c2, uint32_t bar, uint64_t pol) {
    asm volatile("cp.async.bulk.tensor.3d.shared::cluster.global.mbarrier::complete_tx::bytes.L2::cache_hint [%0], [%1, {%3, %4, %5}], [%2], %6;"
                 :: "r"(dst), "l"(tm), "r"(bar), "r"(c0), "r"(c1), "r"(c2), "l"(pol) : "memory");
}
__device__ __forceinline__ void tma_store(const CUtensorMap* tm, uint32_t src, int c0, int c1) {
    asm volatile("cp.async.bulk.tensor.2d.global.shared::cta.bulk_group [%0, {%2, %3}], [%1];" :: "l"(tm), "r"(src), "r"(c0), "r"(c1) : "memory");
}
__device__ __forceinline__ void tma_prefetch(const CUtensorMap* tm, int c0, int c1) {
    asm volatile("cp.async.bulk.prefetch.tensor.2d.L2.global [%0, {%1, %2}];" :: "l"(tm), "r"(c0), "r"(c1) : "memory");
}
__device__ __forceinline__ void tm_prefetch(const CUtensorMap* tm) { asm volatile("prefetch.tensormap [%0];" :: "l"(tm) : "memory"); }
__device__ __forceinline__ void wg_fence() { asm volatile("wgmma.fence.sync.aligned;" ::: "memory"); }
__device__ __forceinline__ void wg_commit() { asm volatile("wgmma.commit_group.sync.aligned;" ::: "memory"); }
template <int N> __device__ __forceinline__ void wg_wait() { asm volatile("wgmma.wait_group.sync.aligned %0;" :: "n"(N) : "memory"); }
template <int N> __device__ __forceinline__ void pin(uint32_t (&r)[N]) {
    #pragma unroll
    for (int i = 0; i < N; i++) asm volatile("" : "+r"(r[i]) :: "memory");
}
template <int N> __device__ __forceinline__ void pin(float (&r)[N]) {
    #pragma unroll
    for (int i = 0; i < N; i++) asm volatile("" : "+f"(r[i]) :: "memory");
}
template <int N> __device__ __forceinline__ void reg_inc() { asm volatile("setmaxnreg.inc.sync.aligned.u32 %0;" :: "n"(N)); }
template <int N> __device__ __forceinline__ void reg_dec() { asm volatile("setmaxnreg.dec.sync.aligned.u32 %0;" :: "n"(N)); }
__host__ __device__ constexpr uint64_t desc_plain(uint32_t addr, uint32_t lbo, uint32_t sbo) {
    return (uint64_t)((addr & 0x3FFFF) >> 4) | ((uint64_t)(lbo >> 4) << 16) | ((uint64_t)(sbo >> 4) << 32);
}
__host__ __device__ constexpr uint64_t desc_sw128(uint32_t addr, uint32_t lbo, uint32_t sbo) { return desc_plain(addr, lbo, sbo) | (1ull << 62); }
__host__ __device__ constexpr uint64_t desc_sw64(uint32_t addr, uint32_t lbo, uint32_t sbo) { return desc_plain(addr, lbo, sbo) | (2ull << 62); }

__device__ __forceinline__ uint32_t lds32(uint32_t a) { uint32_t v; asm volatile("ld.shared.b32 %0, [%1];" : "=r"(v) : "r"(a) : "memory"); return v; }
__device__ __forceinline__ uint32_t lds16(uint32_t a) { uint32_t v; asm volatile("ld.shared.u16 %0, [%1];" : "=r"(v) : "r"(a) : "memory"); return v; }
__device__ __forceinline__ float ldsf(uint32_t a) { return __uint_as_float(lds32(a)); }
__device__ __forceinline__ float2 lds64f(uint32_t a) { float2 v; asm volatile("ld.shared.v2.f32 {%0, %1}, [%2];" : "=f"(v.x), "=f"(v.y) : "r"(a) : "memory"); return v; }
__device__ __forceinline__ uint4 lds128(uint32_t a) { uint4 v; asm volatile("ld.shared.v4.b32 {%0, %1, %2, %3}, [%4];" : "=r"(v.x), "=r"(v.y), "=r"(v.z), "=r"(v.w) : "r"(a) : "memory"); return v; }
__device__ __forceinline__ void sts16(uint32_t a, uint32_t v) { asm volatile("st.shared.b16 [%0], %1;" :: "r"(a), "h"((uint16_t)v) : "memory"); }
__device__ __forceinline__ void sts32(uint32_t a, uint32_t v) { asm volatile("st.shared.b32 [%0], %1;" :: "r"(a), "r"(v) : "memory"); }
__device__ __forceinline__ void stsf(uint32_t a, float v) { sts32(a, __float_as_uint(v)); }
__device__ __forceinline__ void sts64(uint32_t a, uint32_t x, uint32_t y) { asm volatile("st.shared.v2.b32 [%0], {%1, %2};" :: "r"(a), "r"(x), "r"(y) : "memory"); }
__device__ __forceinline__ void sts128(uint32_t a, uint32_t x, uint32_t y, uint32_t z, uint32_t w) { asm volatile("st.shared.v4.b32 [%0], {%1, %2, %3, %4};" :: "r"(a), "r"(x), "r"(y), "r"(z), "r"(w) : "memory"); }
__device__ __forceinline__ void stsm4(uint32_t a, uint32_t x, uint32_t y, uint32_t z, uint32_t w) {
    asm volatile("stmatrix.sync.aligned.m8n8.x4.shared.b16 [%0], {%1, %2, %3, %4};" :: "r"(a), "r"(x), "r"(y), "r"(z), "r"(w) : "memory");
}
__device__ __forceinline__ void ldsm4(uint32_t& a0, uint32_t& a1, uint32_t& a2, uint32_t& a3, uint32_t addr) {
    asm volatile("ldmatrix.sync.aligned.m8n8.x4.shared.b16 {%0,%1,%2,%3}, [%4];" : "=r"(a0), "=r"(a1), "=r"(a2), "=r"(a3) : "r"(addr) : "memory");
}
__device__ __forceinline__ void ldsm4t(uint32_t& a0, uint32_t& a1, uint32_t& a2, uint32_t& a3, uint32_t addr) {
    asm volatile("ldmatrix.sync.aligned.m8n8.x4.trans.shared.b16 {%0,%1,%2,%3}, [%4];" : "=r"(a0), "=r"(a1), "=r"(a2), "=r"(a3) : "r"(addr) : "memory");
}
__device__ __forceinline__ void mma_bf16(float (&d)[4], uint32_t a0, uint32_t a1, uint32_t a2, uint32_t a3, uint32_t b0, uint32_t b1) {
    asm("mma.sync.aligned.m16n8k16.row.col.f32.bf16.bf16.f32 {%0,%1,%2,%3}, {%4,%5,%6,%7}, {%8,%9}, {%0,%1,%2,%3};"
        : "+f"(d[0]), "+f"(d[1]), "+f"(d[2]), "+f"(d[3]) : "r"(a0), "r"(a1), "r"(a2), "r"(a3), "r"(b0), "r"(b1));
}
__device__ __forceinline__ void mma_bf16_k8(float (&d)[4], uint32_t a0, uint32_t a1, uint32_t b0) {
    asm("mma.sync.aligned.m16n8k8.row.col.f32.bf16.bf16.f32 {%0,%1,%2,%3}, {%4,%5}, {%6}, {%0,%1,%2,%3};"
        : "+f"(d[0]), "+f"(d[1]), "+f"(d[2]), "+f"(d[3]) : "r"(a0), "r"(a1), "r"(b0));
}
__device__ __forceinline__ void mma_f16(float (&d)[4], uint32_t a0, uint32_t a1, uint32_t a2, uint32_t a3, uint32_t b0, uint32_t b1) {
    asm("mma.sync.aligned.m16n8k16.row.col.f32.f16.f16.f32 {%0,%1,%2,%3}, {%4,%5,%6,%7}, {%8,%9}, {%0,%1,%2,%3};"
        : "+f"(d[0]), "+f"(d[1]), "+f"(d[2]), "+f"(d[3]) : "r"(a0), "r"(a1), "r"(a2), "r"(a3), "r"(b0), "r"(b1));
}
__device__ __forceinline__ void stg128_pred(void* p, const uint4& v, bool on) {
    asm volatile("{\n.reg .pred q;\nsetp.ne.u32 q, %5, 0;\n@q st.global.v4.b32 [%0], {%1, %2, %3, %4};\n}"
                 :: "l"(p), "r"(v.x), "r"(v.y), "r"(v.z), "r"(v.w), "r"((uint32_t)on) : "memory");
}
__device__ __forceinline__ void st_x32(void* p, uint32_t v) { asm volatile("st.relaxed.gpu.global.u32 [%0], %1;" :: "l"(p), "r"(v) : "memory"); }
__device__ __forceinline__ void st_x64(void* p, uint32_t x, uint32_t y) {
    asm volatile("{\n.reg .b64 v;\nmov.b64 v, {%1, %2};\nst.relaxed.gpu.global.b64 [%0], v;\n}" :: "l"(p), "r"(x), "r"(y) : "memory");
}
__device__ __forceinline__ void st_x128(void* p, uint32_t x, uint32_t y, uint32_t z, uint32_t w) {
    asm volatile("{\n.reg .b64 a, b;\n.reg .b128 v;\nmov.b64 a, {%1, %2};\nmov.b64 b, {%3, %4};\nmov.b128 v, {a, b};\nst.relaxed.gpu.global.b128 [%0], v;\n}"
                 :: "l"(p), "r"(x), "r"(y), "r"(z), "r"(w) : "memory");
}
__device__ __forceinline__ uint32_t ld_x32(const void* p) { uint32_t v; asm volatile("ld.relaxed.gpu.global.u32 %0, [%1];" : "=r"(v) : "l"(p) : "memory"); return v; }
__device__ __forceinline__ uint2 ld_x64(const void* p) {
    uint2 v; asm volatile("{\n.reg .b64 a;\nld.relaxed.gpu.global.b64 a, [%2];\nmov.b64 {%0, %1}, a;\n}" : "=r"(v.x), "=r"(v.y) : "l"(p) : "memory"); return v;
}
__device__ __forceinline__ uint4 ld_x128(const void* p) {
    uint4 v;
    asm volatile("{\n.reg .b64 a, b;\n.reg .b128 v;\nld.relaxed.gpu.global.b128 v, [%4];\nmov.b128 {a, b}, v;\nmov.b64 {%0, %1}, a;\nmov.b64 {%2, %3}, b;\n}"
                 : "=r"(v.x), "=r"(v.y), "=r"(v.z), "=r"(v.w) : "l"(p) : "memory");
    return v;
}
__device__ __forceinline__ void poll_tick(uint32_t& n) { asm volatile("{\n.reg .pred p;\nadd.u32 %0, %0, 1;\nsetp.ge.u32 p, %0, 0x800000;\n@p st.global.u32 [%1], %0;\n}" : "+r"(n) : "l"(0ull)); }
__device__ __forceinline__ void ctr_arrive(int* c) { asm volatile("red.release.gpu.global.add.s32 [%0], 1;" :: "l"(c) : "memory"); }
__device__ __forceinline__ void ctr_wait(const int* c, int target) {
    int v;
    uint32_t n = 0;
    #pragma unroll 1
    do {
        asm volatile("ld.acquire.gpu.global.s32 %0, [%1];" : "=r"(v) : "l"(c) : "memory");
        poll_tick(n);
    } while (v < target);
}
__device__ __forceinline__ void flag_wait(const uint8_t* f) {
    uint32_t n = 0, v;
    #pragma unroll 1
    do { asm volatile("ld.acquire.gpu.global.u8 %0, [%1];" : "=r"(v) : "l"(f) : "memory"); poll_tick(n); } while (v);
}
__device__ __forceinline__ void flags16_wait(const uint8_t* f) {
    uint32_t n = 0;
    uint64_t v;
    #pragma unroll 1
    do {
        asm volatile("{\n.reg .b64 a, b;\n.reg .b128 v;\nld.acquire.gpu.global.b128 v, [%1];\nmov.b128 {a, b}, v;\nor.b64 %0, a, b;\n}" : "=l"(v) : "l"(f) : "memory");
        poll_tick(n);
    } while (v != 0);
}
__device__ __forceinline__ bool any_empty(const uint4& v) { return v.x == EMPTY || v.y == EMPTY || v.z == EMPTY || v.w == EMPTY; }
__device__ __forceinline__ bool warp_any(bool p) { return __any_sync(0xffffffffu, p); }

__device__ __forceinline__ float ex2(float x) { float y; asm("ex2.approx.ftz.f32 %0, %1;" : "=f"(y) : "f"(x)); return y; }
__device__ __forceinline__ float rsq(float x) { float y; asm("rsqrt.approx.ftz.f32 %0, %1;" : "=f"(y) : "f"(x)); return y; }
__device__ __forceinline__ float rcp(float x) { float y; asm("rcp.approx.ftz.f32 %0, %1;" : "=f"(y) : "f"(x)); return y; }
__device__ __forceinline__ uint32_t pack_bf16(float lo, float hi) { uint32_t r; asm("cvt.rn.bf16x2.f32 %0, %1, %2;" : "=r"(r) : "f"(hi), "f"(lo)); return r; }
__device__ __forceinline__ uint32_t pack_f16(float lo, float hi) { uint32_t r; asm("cvt.rn.f16x2.f32 %0, %1, %2;" : "=r"(r) : "f"(hi), "f"(lo)); return r; }
__device__ __forceinline__ float bf_lo(uint32_t v) { return __uint_as_float(v << 16); }
__device__ __forceinline__ float bf_hi(uint32_t v) { return __uint_as_float(v & 0xFFFF0000u); }
__device__ __forceinline__ float bf_round(float x) { return __uint_as_float(pack_bf16(0.f, x)); }
__device__ __forceinline__ void h2_unpack(uint32_t v, float& lo, float& hi) {
    asm("{.reg .f16 l, h; mov.b32 {l, h}, %2; cvt.f32.f16 %0, l; cvt.f32.f16 %1, h;}" : "=f"(lo), "=f"(hi) : "r"(v));
}
__device__ __forceinline__ uint32_t hadd2(uint32_t a, uint32_t b) { uint32_t r; asm("add.rn.f16x2 %0, %1, %2;" : "=r"(r) : "r"(a), "r"(b)); return r; }
__device__ __forceinline__ uint32_t hmax2(uint32_t a, uint32_t b) { uint32_t r; asm("max.f16x2 %0, %1, %2;" : "=r"(r) : "r"(a), "r"(b)); return r; }
__device__ __forceinline__ uint32_t badd2(uint32_t a, uint32_t b) { uint32_t r; asm("add.rn.bf16x2 %0, %1, %2;" : "=r"(r) : "r"(a), "r"(b)); return r; }
__device__ __forceinline__ uint32_t bmul2(uint32_t a, uint32_t b) { uint32_t r; asm("mul.rn.bf16x2 %0, %1, %2;" : "=r"(r) : "r"(a), "r"(b)); return r; }
__device__ __forceinline__ float warp_sum(float v) {
    #pragma unroll
    for (int o = 16; o > 0; o >>= 1) v += __shfl_xor_sync(0xffffffffu, v, o);
    return v;
}
__device__ __forceinline__ float quad_sum(float v) { v += __shfl_xor_sync(0xffffffffu, v, 1); return v + __shfl_xor_sync(0xffffffffu, v, 2); }
__device__ __forceinline__ float quad_max(float v) { v = fmaxf(v, __shfl_xor_sync(0xffffffffu, v, 1)); return fmaxf(v, __shfl_xor_sync(0xffffffffu, v, 2)); }
__device__ __forceinline__ uint32_t redux_max(uint32_t v) { uint32_t r; asm volatile("redux.sync.max.u32 %0, %1, 0xffffffff;" : "=r"(r) : "r"(v)); return r; }
__device__ __forceinline__ uint32_t redux_min(uint32_t v) { uint32_t r; asm volatile("redux.sync.min.u32 %0, %1, 0xffffffff;" : "=r"(r) : "r"(v)); return r; }
__device__ __forceinline__ uint32_t order_bits(float r) { const uint32_t u = __float_as_uint(r); return (u & 0x80000000u) ? ~u : (u | 0x80000000u); }
struct Ln2 { uint32_t nm, rh, rl, c; };
__device__ __forceinline__ Ln2 ln2_coef(float mean, float rstd) {
    const uint32_t a = pack_bf16(-mean, rstd), b = pack_bf16((-mean - bf_lo(a)) * rstd, rstd - bf_hi(a));
    return {__byte_perm(a, 0, 0x1010), __byte_perm(a, 0, 0x3232), __byte_perm(b, 0, 0x3232), __byte_perm(b, 0, 0x1010)};
}
__device__ __forceinline__ uint32_t bfma2(uint32_t a, uint32_t b, uint32_t c) { uint32_t r; asm("fma.rn.bf16x2 %0, %1, %2, %3;" : "=r"(r) : "r"(a), "r"(b), "r"(c)); return r; }
__device__ __forceinline__ uint32_t ln2(uint32_t v, const Ln2& k) { const uint32_t d = badd2(v, k.nm); return bfma2(d, k.rh, bfma2(d, k.rl, k.c)); }
__device__ __forceinline__ uint32_t add_ln2(uint32_t v, const Ln2& k) { return badd2(v, ln2(v, k)); }

#define TL(TID, i)
#define CK(TID, i)

__device__ __forceinline__ void wg_gemm_n128(float (&d)[64], uint64_t desca, uint64_t desc) {
    asm volatile("{\n.reg .pred p;\nsetp.ne.b32 p, 1, 0;\n"
        "wgmma.mma_async.sync.aligned.m64n128k16.f32.bf16.bf16 "
        "{%0,%1,%2,%3,%4,%5,%6,%7,%8,%9,%10,%11,%12,%13,%14,%15,%16,%17,%18,%19,%20,%21,%22,%23,%24,%25,%26,%27,%28,%29,%30,%31,%32,%33,%34,%35,%36,%37,%38,%39,%40,%41,%42,%43,%44,%45,%46,%47,%48,%49,%50,%51,%52,%53,%54,%55,%56,%57,%58,%59,%60,%61,%62,%63}, "
        "%64, %65, p, 1, 1, 0, 1;\n}\n"
        : "+f"(d[0]), "+f"(d[1]), "+f"(d[2]), "+f"(d[3]), "+f"(d[4]), "+f"(d[5]), "+f"(d[6]), "+f"(d[7]), "+f"(d[8]), "+f"(d[9]), "+f"(d[10]), "+f"(d[11]),
          "+f"(d[12]), "+f"(d[13]), "+f"(d[14]), "+f"(d[15]), "+f"(d[16]), "+f"(d[17]), "+f"(d[18]), "+f"(d[19]), "+f"(d[20]), "+f"(d[21]), "+f"(d[22]), "+f"(d[23]),
          "+f"(d[24]), "+f"(d[25]), "+f"(d[26]), "+f"(d[27]), "+f"(d[28]), "+f"(d[29]), "+f"(d[30]), "+f"(d[31]), "+f"(d[32]), "+f"(d[33]), "+f"(d[34]), "+f"(d[35]),
          "+f"(d[36]), "+f"(d[37]), "+f"(d[38]), "+f"(d[39]), "+f"(d[40]), "+f"(d[41]), "+f"(d[42]), "+f"(d[43]), "+f"(d[44]), "+f"(d[45]), "+f"(d[46]), "+f"(d[47]),
          "+f"(d[48]), "+f"(d[49]), "+f"(d[50]), "+f"(d[51]), "+f"(d[52]), "+f"(d[53]), "+f"(d[54]), "+f"(d[55]), "+f"(d[56]), "+f"(d[57]), "+f"(d[58]), "+f"(d[59]),
          "+f"(d[60]), "+f"(d[61]), "+f"(d[62]), "+f"(d[63])
        : "l"(desca), "l"(desc));
}
__device__ __forceinline__ void wg_gemm_n192(float (&d)[96], uint64_t desca, uint64_t desc) {
    asm volatile("{\n.reg .pred p;\nsetp.ne.b32 p, 1, 0;\n"
        "wgmma.mma_async.sync.aligned.m64n192k16.f32.bf16.bf16 "
        "{%0,%1,%2,%3,%4,%5,%6,%7,%8,%9,%10,%11,%12,%13,%14,%15,%16,%17,%18,%19,%20,%21,%22,%23,%24,%25,%26,%27,%28,%29,%30,%31,%32,%33,%34,%35,%36,%37,%38,%39,%40,%41,%42,%43,%44,%45,%46,%47,%48,%49,%50,%51,%52,%53,%54,%55,%56,%57,%58,%59,%60,%61,%62,%63,%64,%65,%66,%67,%68,%69,%70,%71,%72,%73,%74,%75,%76,%77,%78,%79,%80,%81,%82,%83,%84,%85,%86,%87,%88,%89,%90,%91,%92,%93,%94,%95}, "
        "%96, %97, p, 1, 1, 0, 1;\n}\n"
        : "+f"(d[0]), "+f"(d[1]), "+f"(d[2]), "+f"(d[3]), "+f"(d[4]), "+f"(d[5]), "+f"(d[6]), "+f"(d[7]), "+f"(d[8]), "+f"(d[9]), "+f"(d[10]), "+f"(d[11]),
          "+f"(d[12]), "+f"(d[13]), "+f"(d[14]), "+f"(d[15]), "+f"(d[16]), "+f"(d[17]), "+f"(d[18]), "+f"(d[19]), "+f"(d[20]), "+f"(d[21]), "+f"(d[22]), "+f"(d[23]),
          "+f"(d[24]), "+f"(d[25]), "+f"(d[26]), "+f"(d[27]), "+f"(d[28]), "+f"(d[29]), "+f"(d[30]), "+f"(d[31]), "+f"(d[32]), "+f"(d[33]), "+f"(d[34]), "+f"(d[35]),
          "+f"(d[36]), "+f"(d[37]), "+f"(d[38]), "+f"(d[39]), "+f"(d[40]), "+f"(d[41]), "+f"(d[42]), "+f"(d[43]), "+f"(d[44]), "+f"(d[45]), "+f"(d[46]), "+f"(d[47]),
          "+f"(d[48]), "+f"(d[49]), "+f"(d[50]), "+f"(d[51]), "+f"(d[52]), "+f"(d[53]), "+f"(d[54]), "+f"(d[55]), "+f"(d[56]), "+f"(d[57]), "+f"(d[58]), "+f"(d[59]),
          "+f"(d[60]), "+f"(d[61]), "+f"(d[62]), "+f"(d[63]), "+f"(d[64]), "+f"(d[65]), "+f"(d[66]), "+f"(d[67]), "+f"(d[68]), "+f"(d[69]), "+f"(d[70]), "+f"(d[71]),
          "+f"(d[72]), "+f"(d[73]), "+f"(d[74]), "+f"(d[75]), "+f"(d[76]), "+f"(d[77]), "+f"(d[78]), "+f"(d[79]), "+f"(d[80]), "+f"(d[81]), "+f"(d[82]), "+f"(d[83]),
          "+f"(d[84]), "+f"(d[85]), "+f"(d[86]), "+f"(d[87]), "+f"(d[88]), "+f"(d[89]), "+f"(d[90]), "+f"(d[91]), "+f"(d[92]), "+f"(d[93]), "+f"(d[94]), "+f"(d[95])
        : "l"(desca), "l"(desc));
}
__device__ __forceinline__ void wg_gemm_n192_init(float (&d)[96], uint64_t desca, uint64_t desc) {
    asm volatile("{\n.reg .pred p;\nsetp.ne.b32 p, 0, 0;\n"
        "wgmma.mma_async.sync.aligned.m64n192k16.f32.bf16.bf16 "
        "{%0,%1,%2,%3,%4,%5,%6,%7,%8,%9,%10,%11,%12,%13,%14,%15,%16,%17,%18,%19,%20,%21,%22,%23,%24,%25,%26,%27,%28,%29,%30,%31,%32,%33,%34,%35,%36,%37,%38,%39,%40,%41,%42,%43,%44,%45,%46,%47,%48,%49,%50,%51,%52,%53,%54,%55,%56,%57,%58,%59,%60,%61,%62,%63,%64,%65,%66,%67,%68,%69,%70,%71,%72,%73,%74,%75,%76,%77,%78,%79,%80,%81,%82,%83,%84,%85,%86,%87,%88,%89,%90,%91,%92,%93,%94,%95}, "
        "%96, %97, p, 1, 1, 0, 1;\n}\n"
        : "=f"(d[0]), "=f"(d[1]), "=f"(d[2]), "=f"(d[3]), "=f"(d[4]), "=f"(d[5]), "=f"(d[6]), "=f"(d[7]), "=f"(d[8]), "=f"(d[9]), "=f"(d[10]), "=f"(d[11]),
          "=f"(d[12]), "=f"(d[13]), "=f"(d[14]), "=f"(d[15]), "=f"(d[16]), "=f"(d[17]), "=f"(d[18]), "=f"(d[19]), "=f"(d[20]), "=f"(d[21]), "=f"(d[22]), "=f"(d[23]),
          "=f"(d[24]), "=f"(d[25]), "=f"(d[26]), "=f"(d[27]), "=f"(d[28]), "=f"(d[29]), "=f"(d[30]), "=f"(d[31]), "=f"(d[32]), "=f"(d[33]), "=f"(d[34]), "=f"(d[35]),
          "=f"(d[36]), "=f"(d[37]), "=f"(d[38]), "=f"(d[39]), "=f"(d[40]), "=f"(d[41]), "=f"(d[42]), "=f"(d[43]), "=f"(d[44]), "=f"(d[45]), "=f"(d[46]), "=f"(d[47]),
          "=f"(d[48]), "=f"(d[49]), "=f"(d[50]), "=f"(d[51]), "=f"(d[52]), "=f"(d[53]), "=f"(d[54]), "=f"(d[55]), "=f"(d[56]), "=f"(d[57]), "=f"(d[58]), "=f"(d[59]),
          "=f"(d[60]), "=f"(d[61]), "=f"(d[62]), "=f"(d[63]), "=f"(d[64]), "=f"(d[65]), "=f"(d[66]), "=f"(d[67]), "=f"(d[68]), "=f"(d[69]), "=f"(d[70]), "=f"(d[71]),
          "=f"(d[72]), "=f"(d[73]), "=f"(d[74]), "=f"(d[75]), "=f"(d[76]), "=f"(d[77]), "=f"(d[78]), "=f"(d[79]), "=f"(d[80]), "=f"(d[81]), "=f"(d[82]), "=f"(d[83]),
          "=f"(d[84]), "=f"(d[85]), "=f"(d[86]), "=f"(d[87]), "=f"(d[88]), "=f"(d[89]), "=f"(d[90]), "=f"(d[91]), "=f"(d[92]), "=f"(d[93]), "=f"(d[94]), "=f"(d[95])
        : "l"(desca), "l"(desc));
}
__device__ __forceinline__ void wg_qk_init(uint32_t (&d)[32], uint32_t a0, uint32_t a1, uint32_t a2, uint32_t a3, uint64_t desc) {
    asm volatile("{\n.reg .pred p;\nsetp.ne.b32 p, 0, 0;\n"
        "wgmma.mma_async.sync.aligned.m64n128k16.f16.f16.f16 "
        "{%0,%1,%2,%3,%4,%5,%6,%7,%8,%9,%10,%11,%12,%13,%14,%15,%16,%17,%18,%19,%20,%21,%22,%23,%24,%25,%26,%27,%28,%29,%30,%31}, "
        "{%32,%33,%34,%35}, %36, p, 1, 1, 0;\n}\n"
        : "=r"(d[0]), "=r"(d[1]), "=r"(d[2]), "=r"(d[3]), "=r"(d[4]), "=r"(d[5]), "=r"(d[6]), "=r"(d[7]), "=r"(d[8]), "=r"(d[9]), "=r"(d[10]), "=r"(d[11]),
          "=r"(d[12]), "=r"(d[13]), "=r"(d[14]), "=r"(d[15]), "=r"(d[16]), "=r"(d[17]), "=r"(d[18]), "=r"(d[19]), "=r"(d[20]), "=r"(d[21]), "=r"(d[22]), "=r"(d[23]),
          "=r"(d[24]), "=r"(d[25]), "=r"(d[26]), "=r"(d[27]), "=r"(d[28]), "=r"(d[29]), "=r"(d[30]), "=r"(d[31])
        : "r"(a0), "r"(a1), "r"(a2), "r"(a3), "l"(desc));
}
__device__ __forceinline__ void wg_qk_acc(uint32_t (&d)[32], uint32_t a0, uint32_t a1, uint32_t a2, uint32_t a3, uint64_t desc) {
    asm volatile("{\n.reg .pred p;\nsetp.ne.b32 p, 1, 0;\n"
        "wgmma.mma_async.sync.aligned.m64n128k16.f16.f16.f16 "
        "{%0,%1,%2,%3,%4,%5,%6,%7,%8,%9,%10,%11,%12,%13,%14,%15,%16,%17,%18,%19,%20,%21,%22,%23,%24,%25,%26,%27,%28,%29,%30,%31}, "
        "{%32,%33,%34,%35}, %36, p, 1, 1, 0;\n}\n"
        : "+r"(d[0]), "+r"(d[1]), "+r"(d[2]), "+r"(d[3]), "+r"(d[4]), "+r"(d[5]), "+r"(d[6]), "+r"(d[7]), "+r"(d[8]), "+r"(d[9]), "+r"(d[10]), "+r"(d[11]),
          "+r"(d[12]), "+r"(d[13]), "+r"(d[14]), "+r"(d[15]), "+r"(d[16]), "+r"(d[17]), "+r"(d[18]), "+r"(d[19]), "+r"(d[20]), "+r"(d[21]), "+r"(d[22]), "+r"(d[23]),
          "+r"(d[24]), "+r"(d[25]), "+r"(d[26]), "+r"(d[27]), "+r"(d[28]), "+r"(d[29]), "+r"(d[30]), "+r"(d[31])
        : "r"(a0), "r"(a1), "r"(a2), "r"(a3), "l"(desc));
}
__device__ __forceinline__ void wg_pv_init(uint32_t (&d)[10], uint32_t a0, uint32_t a1, uint32_t a2, uint32_t a3, uint64_t desc) {
    asm volatile("{\n.reg .pred p;\nsetp.ne.b32 p, 0, 0;\n"
        "wgmma.mma_async.sync.aligned.m64n40k16.f16.f16.f16 "
        "{%0,%1,%2,%3,%4,%5,%6,%7,%8,%9}, "
        "{%10,%11,%12,%13}, %14, p, 1, 1, 1;\n}\n"
        : "=r"(d[0]), "=r"(d[1]), "=r"(d[2]), "=r"(d[3]), "=r"(d[4]), "=r"(d[5]), "=r"(d[6]), "=r"(d[7]), "=r"(d[8]), "=r"(d[9])
        : "r"(a0), "r"(a1), "r"(a2), "r"(a3), "l"(desc));
}
__device__ __forceinline__ void wg_pv_acc(uint32_t (&d)[10], uint32_t a0, uint32_t a1, uint32_t a2, uint32_t a3, uint64_t desc) {
    asm volatile("{\n.reg .pred p;\nsetp.ne.b32 p, 1, 0;\n"
        "wgmma.mma_async.sync.aligned.m64n40k16.f16.f16.f16 "
        "{%0,%1,%2,%3,%4,%5,%6,%7,%8,%9}, "
        "{%10,%11,%12,%13}, %14, p, 1, 1, 1;\n}\n"
        : "+r"(d[0]), "+r"(d[1]), "+r"(d[2]), "+r"(d[3]), "+r"(d[4]), "+r"(d[5]), "+r"(d[6]), "+r"(d[7]), "+r"(d[8]), "+r"(d[9])
        : "r"(a0), "r"(a1), "r"(a2), "r"(a3), "l"(desc));
}

constexpr uint32_t SB = SMEM_BASE;
constexpr uint32_t R_SLOT = 18432, A_RING = SB, A_KP = SB + 73728, A_QX = SB + 81920, A_STB = SB + 98304;
constexpr uint32_t F_GU0 = SB + 98304, F_GU1 = SB + 163840;
__host__ __device__ constexpr uint32_t f_wd(uint32_t i) { return i < 3 ? SB + i * 16384 : A_QX; }
__host__ __device__ constexpr uint32_t o_a(uint32_t s) { return s == 0 ? SB : s == 1 ? A_QX : F_GU0 + (s - 2) * 32768; }
__host__ __device__ constexpr uint32_t o_b(uint32_t s) { return s < 2 ? SB + 16384 + s * 16384 : F_GU0 + 16384 + (s - 2) * 32768; }
constexpr uint32_t XT0 = SB + 49152, XT1 = XT0 + 16384;
constexpr uint32_t Q_ABYTES = 256 * 64 * 2, Q_STB = Q_ABYTES + 192 * 64 * 2;
constexpr uint32_t Q_CS = SB + 3 * Q_STB, Q_VS = Q_CS + 768, Q_RC = Q_VS + 256, Q_FIX = Q_RC + 2048;
constexpr uint32_t SD_VEC = SB + 176128, SD_W = SB + 180224;
static_assert(Q_FIX + 768 <= SD_VEC, "smem");
constexpr uint32_t M_RED = SB + 229376, M_BAR = M_RED + 2048, BAR_SET = 320, M_IVS = M_BAR + 2 * BAR_SET, M_SM = M_IVS + 128;
constexpr uint32_t M_F2 = M_SM;
constexpr uint32_t M_WS = M_SM + 16;
constexpr uint32_t M_SS = M_SM + 24;
constexpr uint32_t M_RT = M_SM + 32;
constexpr uint32_t M_KR = M_SM + 64;
constexpr uint32_t M_SR = M_SM + 128;
constexpr int K_SMEM = M_SR + 128 - SB;
static_assert(K_SMEM == 232448, "smem");
constexpr uint32_t B_QF = 0, B_AF = 24, B_OF = 56, B_RES = 88, B_GU = 96, B_WD = 104, B_SW = 112, B_ONE = 120, B_QE = 128, B_OE = 152, B_PX = 184,
                   B_AE = 208, B_OD = 240, B_FG = 272, B_FD = 280, B_XS = 288, B_WF = 296, B_KS = 304, B_END = 320;
constexpr int NB_ML = 1, NB_CONS = 2, NB_SIDE = 3, NB_EPI = 4;

struct Maps { CUtensorMap x[3], wqkv, o, wo[2], r, g, u, d; };
struct Route { float r, mean, rstd; int idx; };

template <int N>
__device__ __forceinline__ void halve(float (&v)[8], int lane, int bit) {
    const bool up = lane & bit;
    #pragma unroll
    for (int i = 0; i < N; i++) v[i] = (up ? v[N + i] : v[i]) + __shfl_xor_sync(0xffffffffu, up ? v[i] : v[N + i], bit);
}

__device__ __forceinline__ void prep_work(const bf16* __restrict__ x0, const bf16* __restrict__ w_r, uint32_t lb) {
    const int t = tid_now() - 288, c = cta_now(), lane = t & 31, warp = warp_uniform(t >> 5);
    const uint32_t wb = SD_W + warp * 8192;
    mbar_nap(lb + B_SW, 0);
    {
        float cs[8], cq[8];
        #pragma unroll
        for (int i = 0; i < 8; i++) { cs[i] = 0.f; cq[i] = 0.f; }
        #pragma unroll 1
        for (int h = 0; h < 2; h++) {
            #pragma unroll 2
            for (int r = 0; r < 16; r++) {
                const uint4 u = lds128(wb + h * 24576 + (lane >> 3) * 128 + r * 512 + (((lane & 7) ^ ((r * 4 + (lane >> 3)) & 7)) << 4));
                const uint32_t w[4] = {u.x, u.y, u.z, u.w};
                #pragma unroll
                for (int e = 0; e < 4; e++) {
                    const float a = bf_lo(w[e]), b = bf_hi(w[e]);
                    cs[2*e] += a; cs[2*e+1] += b; cq[2*e] = fmaf(a, a, cq[2*e]); cq[2*e+1] = fmaf(b, b, cq[2*e+1]);
                }
            }
            fence_async_smem();
            __syncwarp();
            if (elect_one()) {
                const uint32_t bytes = h == 0 ? 8192 : warp < 2 ? 4096 : 2048;
                mbar_expect_tx(lb + B_PX + warp * 8, bytes);
                bulk_load(wb + h * 24576, h && warp == 2 ? w_r : x0 + (size_t)(c * 16 + (h ? 12 + warp * 2 : warp * 4)) * D_, bytes, lb + B_PX + warp * 8);
            }
            __syncwarp();
        }
        halve<4>(cs, lane, 16); halve<2>(cs, lane, 8);
        halve<4>(cq, lane, 16); halve<2>(cq, lane, 8);
        *reinterpret_cast<float4*>(&g_cs[c >> 4][warp * D_ + (c & 15) * 64 + (lane & 7) * 8 + (lane >> 3) * 2]) = make_float4(cs[0], cq[0], cs[1], cq[1]);
    }
    TL(288, 22);
    mbar_nap(lb + B_PX + warp * 8, 0);
    #pragma unroll 1
    for (int i = 0; i < (warp < 2 ? 6 : 5); i++) {
        const int r = i < 4 ? warp * 4 + i : 8 + warp * 2 + i;
        float s0 = 0.f, s1 = 0.f, q0 = 0.f, q1 = 0.f;
        #pragma unroll 2
        for (int j = 0; j < 4; j++) {
            const uint4 u = lds128(wb + (i >> 2) * 16384 + i * 2048 + j * 512 + lane * 16);
            const uint32_t w[4] = {u.x, u.y, u.z, u.w};
            #pragma unroll
            for (int e = 0; e < 4; e++) { const float a = bf_lo(w[e]), b = bf_hi(w[e]); s0 += a; s1 += b; q0 = fmaf(a, a, q0); q1 = fmaf(b, b, q1); }
        }
        s0 += s1; q0 += q1;
        float v = (lane & 16 ? q0 : s0) + __shfl_xor_sync(0xffffffffu, lane & 16 ? s0 : q0, 16);
        #pragma unroll
        for (int o = 8; o > 0; o >>= 1) v += __shfl_xor_sync(0xffffffffu, v, o);
        const float mean = v * (1.f / D_), sq = __shfl_xor_sync(0xffffffffu, mean, 16);
        if (lane == 0) {
            if (r < 16) g_rs0[c * 16 + r] = make_float2(fmaxf(sq - mean * mean, 0.f), mean);
            else stsf(M_WS, v);
        }
    }
    named_sync(NB_SIDE, 96);
    if (t == 0) { TL(288, 23); ctr_arrive(&g_pctr); ctr_wait(&g_pctr, 128); TL(288, 24); }
    named_sync(NB_SIDE, 96);
}

__device__ __forceinline__ void head_scales(float fq, float fk, float& sq, float& sk, float& ss) {
    const bool ok = fq <= 16384.f && fk <= 16384.f && fq * fk <= 50000.f;
    const int a = min(max((((int)(__float_as_uint(fq) >> 23) - 125) >> 1) - 8, -60), 60), b = min(max((((int)(__float_as_uint(fk) >> 23) - 125) >> 1) - 8, -60), 60);
    sq = QSCALE * __uint_as_float((uint32_t)(ok ? 127 : 127 - a) << 23);
    sk = __uint_as_float((uint32_t)(ok ? 127 : 127 - b) << 23);
    ss = ok ? 0.f : __uint_as_float((uint32_t)(127 + a + b) << 23);
}

__device__ __forceinline__ void epi_inputs(int L, const bf16* __restrict__ w_r) {
    const int t = tid_now() - 288, c = cta_now(), mt = c >> 4, nt = c & 15, lane = t & 31;
    const uint32_t wr = t < 64 ? __ldg(reinterpret_cast<const uint32_t*>(w_r) + (c & 7) * 64 + t) : 0x3F803F80u;
    #pragma unroll 1
    for (int k = 0; k < 3; k++) {
        const int i = t + 96 * k, col = (i >> 6) * D_ + nt * 64 + (i & 63);
        const float2* rsp = (L ? g_x.rs1 : g_rs0) + mt * 256 + (i & 255);
        uint2 sv = ld_x64(rsp);
        if (k < 2) {
            float2 p[8];
            #pragma unroll
            for (int j = 0; j < 8; j++) p[j] = __ldcg(&g_cs[j][col]);
            stsf(Q_CS + i * 4, ((p[0].x + p[1].x) + (p[2].x + p[3].x)) + ((p[4].x + p[5].x) + (p[6].x + p[7].x)));
            const float zz = ((p[0].y + p[1].y) + (p[2].y + p[3].y)) + ((p[4].y + p[5].y) + (p[6].y + p[7].y));
            const float zs = warp_sum(zz);
            if (i < 128) { if (lane == 0) stsf(M_SR + (i >> 5) * 4, zs); }
            else {
                const int e = (int)(__float_as_uint(zz) >> 23) - 127;
                const int sh = min(max(((e + 2) >> 1) + 3, -60), 60);
                sts32(Q_VS + (i - 128) * 4, (uint32_t)(127 - sh) << 23);
                sts16(M_IVS + ((i & 32) + (i & 6) * 4 + ((i >> 2) & 6) + (i & 1)) * 2, (uint32_t)(127 + sh - 4) << 7);
            }
        }
        else {
            named_sync(NB_SIDE, 96);
            if (t < 2) {
                float sq, sk, ss;
                head_scales(ldsf(M_SR + t * 4), ldsf(M_SR + 8 + t * 4), sq, sk, ss);
                stsf(M_F2 + t * 4, sq); stsf(M_F2 + 8 + t * 4, sk); stsf(M_SS + t * 4, ss);
            }
            __syncwarp();
        }
        uint32_t n = 0;
        #pragma unroll 1
        while (warp_any(sv.x == EMPTY)) { sv = ld_x64(rsp); poll_tick(n); }
        const float var = __uint_as_float(sv.x), a = L ? 1.f + rsq(var + LN_EPS) : 1.f;
        sts64(Q_RC + (i & 255) * 8, __float_as_uint(a * rsq(a * a * var + LN_EPS)), sv.y ^ 0x80000000u);
    }
    if (t < 68) sts32(M_RED + t * 4, wr);
}

__device__ __forceinline__ void ffn_finish(int L, bf16* __restrict__ out) {
    const int t = tid_now() - 288, c = cta_now(), lane = t & 31, warp = warp_uniform(t >> 5);
    TL(288, L * 32 + 29);
    const uint4 rv = lds128(M_RT + 16 * L);
    const int idx = (int)rv.w;
    const uint32_t* xsrc = &g_x.cand[L][idx >> 7][(c >> 2) * 16 + (t & 3) * 4 + (c & 3)];
    const uint8_t* fsrc = &g_x.x[L][idx >> 8][((idx >> 7) & 1) * 8 + (c >> 4)];
    uint32_t xw, busy;
    float a[4] = {0.f, 0.f, 0.f, 0.f};
    {
        const float* src = &g_x.ypart[L][c][0][t * 4];
        uint4 v[3];
        uint32_t n = 0;
        #pragma unroll 1
        do {
            v[0] = ld_x128(src); v[1] = ld_x128(src + 384);
            v[2] = make_uint4(0u, 0u, 0u, 0u);
            xw = 0u; busy = 0u;
            if (warp == 0) {
                v[2] = ld_x128(src + 768); xw = ld_x32(xsrc);
                asm volatile("ld.relaxed.gpu.global.u8 %0, [%1];" : "=r"(busy) : "l"(fsrc) : "memory");
            }
            poll_tick(n);
        } while (warp_any(any_empty(v[0]) || any_empty(v[1]) || any_empty(v[2]) || xw == EMPTY || busy != 0));
        TL(288, L * 32 + 30); TL(352, L * 32 + 31);
        #pragma unroll
        for (int i = 0; i < 3; i++) { a[0] += __uint_as_float(v[i].x); a[1] += __uint_as_float(v[i].y); a[2] += __uint_as_float(v[i].z); a[3] += __uint_as_float(v[i].w); }
    }
    #pragma unroll
    for (int o = 2; o < 32; o <<= 1) {
        #pragma unroll
        for (int i = 0; i < 4; i++) a[i] += __shfl_xor_sync(0xffffffffu, a[i], o);
    }
    if (lane < 2) sts128(M_SR + warp * 32 + lane * 16, __float_as_uint(a[0]), __float_as_uint(a[1]), __float_as_uint(a[2]), __float_as_uint(a[3]));
    named_sync(NB_SIDE, 96);
    if (t < 4) {
        const float2 y0 = lds64f(M_SR + t * 8), y1 = lds64f(M_SR + 32 + t * 8), y2 = lds64f(M_SR + 64 + t * 8);
        const uint32_t y = pack_bf16(y0.x + y1.x + y2.x, y0.y + y1.y + y2.y);
        const float rsel = bf_round(rcp(1.f + __expf(-bf_round(__uint_as_float(rv.x)))));
        const uint32_t xn = ln2(xw, ln2_coef(__uint_as_float(rv.y), __uint_as_float(rv.z)));
        const uint32_t res = badd2(xw, badd2(xn, pack_bf16(bf_lo(y) * rsel, bf_hi(y) * rsel)));
        if (L == 0) st_x32(&g_x.x2row[c * 4 + t], res);
        reinterpret_cast<uint32_t*>(L ? out : g_x1)[idx * (D_ / 2) + c * 4 + t] = res;
    }
}

__device__ __forceinline__ void fix_row(uint32_t lb) {
    const int t = tid_now() - 288, c = cta_now(), lane = t & 31, warp = warp_uniform(t >> 5);
    uint4 v[2];
    {
        uint32_t n = 0;
        #pragma unroll 1
        do {
            v[0] = ld_x128(g_x.x2row + t * 4);
            v[1] = make_uint4(0u, 0u, 0u, 0u);
            if (warp == 0) v[1] = ld_x128(g_x.x2row + (96 + t) * 4);
            poll_tick(n);
        } while (warp_any(any_empty(v[0]) || any_empty(v[1])));
    }
    const uint32_t w[8] = {v[0].x, v[0].y, v[0].z, v[0].w, v[1].x, v[1].y, v[1].z, v[1].w};
    float su = 0.f, sq = 0.f;
    #pragma unroll
    for (int i = 0; i < 8; i++) { const float a = bf_lo(w[i]), b = bf_hi(w[i]); su += a + b; sq = fmaf(a, a, fmaf(b, b, sq)); }
    su = warp_sum(su); sq = warp_sum(sq);
    if (lane == 0) sts64(M_SR + 96 + warp * 8, __float_as_uint(su), __float_as_uint(sq));
    named_sync(NB_SIDE, 96);
    const float2 s0 = lds64f(M_SR + 96), s1 = lds64f(M_SR + 104), s2 = lds64f(M_SR + 112);
    const float mean = (s0.x + s1.x + s2.x) * (1.f / D_);
    const float rstd = rsq(fmaxf((s0.y + s1.y + s2.y) * (1.f / D_) - mean * mean, 0.f) + LN_EPS);
    const Ln2 k = ln2_coef(mean, rstd);
    #pragma unroll
    for (int i = 0; i < 2; i++)
        if (i == 0 || warp == 0) sts128(SD_VEC + (t + 96 * i) * 16, ln2(w[4*i], k), ln2(w[4*i+1], k), ln2(w[4*i+2], k), ln2(w[4*i+3], k));
    named_sync(NB_SIDE, 96);
    TL(288, 32 + 22);
    mbar_nap(lb + B_SW, 0);
    float a[8];
    #pragma unroll
    for (int i = 0; i < 8; i++) a[i] = 0.f;
    const uint32_t xa = base32(SD_VEC + lane * 2), wa = base32(SD_W + lane * 48 + warp * 16);
    #pragma unroll 2
    for (int b = 0; b < 32; b++) {
        const float x = bf_lo(lds16(xa + b * 64));
        const uint4 u = lds128(wa + b * 1536);
        a[0] = fmaf(x, bf_lo(u.x), a[0]); a[1] = fmaf(x, bf_hi(u.x), a[1]); a[2] = fmaf(x, bf_lo(u.y), a[2]); a[3] = fmaf(x, bf_hi(u.y), a[3]);
        a[4] = fmaf(x, bf_lo(u.z), a[4]); a[5] = fmaf(x, bf_hi(u.z), a[5]); a[6] = fmaf(x, bf_lo(u.w), a[6]); a[7] = fmaf(x, bf_hi(u.w), a[7]);
    }
    halve<4>(a, lane, 16); halve<2>(a, lane, 8); halve<1>(a, lane, 4);
    a[0] = quad_sum(a[0]);
    if ((lane & 3) == 0) st_x32(&g_x.fix[c * 24 + warp * 8 + (lane >> 2)], __float_as_uint(a[0]));
    TL(288, 32 + 23);
    if (((int)lds32(M_RT + 12) >> 8) == (c >> 4)) {
        const float* src = &g_x.fix[(t >> 5) * D_ + (c & 15) * 64 + (t & 31) * 2];
        uint2 f;
        uint32_t n = 0;
        #pragma unroll 1
        do { f = ld_x64(src); poll_tick(n); } while (warp_any(f.x == EMPTY || f.y == EMPTY));
        sts64(Q_FIX + t * 8, f.x, f.y);
    }
}

#define PFXNS 1000
#define GAPNS 900
__device__ __forceinline__ void publish(uint8_t* f) {
    bulk_commit();
    bulk_wait();
    fence_async_global();
    asm volatile("st.release.gpu.global.u8 [%0], 0;" :: "l"(f) : "memory");
}
__device__ __forceinline__ void side_role(const Maps& mp, const bf16* __restrict__ x0, const bf16* __restrict__ wo, const bf16* __restrict__ w_down, const bf16* __restrict__ w_r, bf16* __restrict__ out) {
    #pragma unroll 1
    for (int L = 0; L < 2; L++) {
        const uint32_t lb = M_BAR + L * BAR_SET;
        if (L == 0) prep_work(x0, w_r, lb);
        else fix_row(lb);
        epi_inputs(L, w_r);
        const int t = tid_now() - 288, c = cta_now(), mt = c >> 4, nt = c & 15, warp = warp_uniform(t >> 5);
        TL(288, L * 32 + 4);
        named_arrive(NB_EPI, 224);
        named_arrive(NB_EPI + 1, 224);
        if (warp == 0) {
            named_sync(NB_ML, 288);
            #pragma unroll
            for (int i = 0; i < 16; i++) sts128(base32(A_RING + 16384 + t * 16) + (i >> 2) * R_SLOT + (i & 3) * 512, 0x2C002C00u, 0x2C002C00u, 0x2C002C00u, 0x2C002C00u);
            fence_async_smem();
            __syncwarp();
            mbar_arrive_elect(lb + B_ONE);
        }
        if (elect_one()) {
            #pragma unroll 1
            for (int n = warp - 1; n >= 0 && n < 3 * warp - 2; n++) {
                char* dst = g_kv + (size_t)(nt * 2 + (n >> 1)) * 16 * KV_TILE;
                const int tile = 2 * mt + (n & 1);
                if (n < 3) mbar_nap(lb + (n == 2 ? B_AE + 16 : B_KS + 8 * n), 0);
                bulk_store(dst + ((tile - 1) & 15) * KV_TILE, n == 0 ? A_KP : n == 1 ? A_RING : A_STB + (n - 2) * 8192, 8192);
                bulk_store(dst + tile * KV_TILE + 8192, n < 2 ? A_RING + 8192 + n * R_SLOT : A_STB + n * 8192, 8192);
                publish(&g_x.kv[L][nt * 2 + (n >> 1)][tile]);
                if (n == 1) TL(352, L * 32 + 6);
                if (n == 0) TL(320, L * 32 + 27);
            }
            if (warp == 2) {
                const bool ffn = c < NFC;
                const uint64_t pol = policy_evict_first();
                mbar_expect_tx(lb + B_GU, ffn ? 131072 : 0);
                mbar_expect_tx(lb + B_WD, ffn ? 65536 : 0);
                l2_prefetch(reinterpret_cast<const char*>(wo) + (size_t)c * 16384, 16384);
                if (ffn) {
                    #pragma unroll 1
                    for (int i = 0; i < 12; i++) {
                        if (i < 8) tma_load_s(F_GU0 + i * 16384, (i & 1) ? &mp.u : &mp.g, c * 32, (i >> 1) * 256, lb + B_GU, pol);
                        else l2_prefetch(reinterpret_cast<const char*>(w_down) + (size_t)c * 65536 + (i - 8) * 16384, 16384);
                        __nanosleep(GAPNS);
                    }
                }
                mbar_nap(lb + B_OD, 0);
                __nanosleep(PFXNS);
                l2_prefetch(g_u.fill[c], sizeof(g_u.fill[0]));
                mbar_nap(lb + B_XS, 0);
                tma_store(&mp.x[L + 1], XT0, (c & 7) * 128, (c >> 3) * 128);
                tma_store(&mp.x[L + 1], XT1, (c & 7) * 128 + 64, (c >> 3) * 128);
                publish(&g_x.x[L][mt][nt]);
                TL(352, L * 32 + 18);
            } else {
                #pragma unroll 1
                for (int p = 0; p < 2; p++) { mbar_sleep(lb + B_OD + (p * 2 + warp) * 8, 0); ctr_arrive(g_x.o[L][mt * 2 + warp][p]); TL(288, L * 32 + 19); }
            }
        }
        __syncwarp();
        mbar_sleep(lb + B_FD, 0);
        if (c == 0 && t == 0 && L == 0) g_pctr = 0;
        ffn_finish(L, out);
        TL(288, L * 32 + 20);
    }
}

struct Cols { float2 c[4], v[4]; };
template <int HH>
__device__ __forceinline__ void load_cols(Cols& k, uint32_t cs) {
    #pragma unroll
    for (int jj = 0; jj < 4; jj++) {
        k.c[jj] = lds64f(cs + (HH * 32 + jj * 8) * 4);
        if (HH >= 4) k.v[jj] = lds64f(cs + (Q_VS - Q_CS) + ((HH & 1) * 32 + jj * 8) * 4);
    }
}
template <int HH>
__device__ __forceinline__ void qkv_epi_head(const float (&acc0)[96], const float (&acc1)[96], const float (&cf)[4], const float (&nm)[4], const Cols& k, float hs, uint32_t (&pk)[4][4]) {
    #pragma unroll
    for (int jj = 0; jj < 4; jj++) {
        #pragma unroll
        for (int i = 0; i < 4; i++) {
            const float* a = (i >> 1) ? acc1 : acc0;
            const float sc = HH < 4 ? cf[i] * hs : cf[i];
            float x = fmaf(nm[i], k.c[jj].x, a[4 * (4 * HH + jj) + 2 * (i & 1)]) * sc;
            float y = fmaf(nm[i], k.c[jj].y, a[4 * (4 * HH + jj) + 2 * (i & 1) + 1]) * sc;
            if (HH >= 4) { x *= k.v[jj].x; y *= k.v[jj].y; }
            pk[i][jj] = pack_f16(x, y);
        }
    }
}
__device__ __forceinline__ void stage_kv(uint32_t dst, const uint32_t (&pk)[4][4]) {
    #pragma unroll
    for (int i = 0; i < 4; i++) stsm4(dst + (i >> 1) * 1024 + (i & 1) * 128, pk[i][0], pk[i][1], pk[i][2], pk[i][3]);
}
template <int OFF>
__device__ __forceinline__ void patch_row(float (&acc)[96], uint32_t fx) {
    #pragma unroll
    for (int j = 0; j < 24; j++) { const float2 f = lds64f(fx + j * 32); acc[4 * j + OFF] = f.x; acc[4 * j + OFF + 1] = f.y; }
}
#define QLEAD 2
template <bool INIT>
__device__ __forceinline__ void qkv_step(float (&acc0)[96], float (&acc1)[96], uint64_t da, uint64_t db) {
    wg_fence();
    #pragma unroll
    for (int kk = 0; kk < 4; kk++) {
        if (INIT && kk == 0) { wg_gemm_n192_init(acc0, da, db); wg_gemm_n192_init(acc1, da + (8192 >> 4), db); }
        else { wg_gemm_n192(acc0, da + kk * 2, db + kk * 128); wg_gemm_n192(acc1, da + (8192 >> 4) + kk * 2, db + kk * 128); }
    }
    wg_commit();
}
__device__ __forceinline__ void qkv_phase(int L, uint32_t lb, int wg, uint32_t (&qa)[8], uint32_t (&qb)[8], uint32_t (&SA)[32], uint32_t (&SB_)[32]) {
    float acc0[96], acc1[96];
    {
        const bool leader = (tid_now() & 127) == 0;
        const uint64_t da0 = opaque(desc_sw128(SB + wg * 16384, 16, 1024)), db0 = opaque(desc_sw128(SB + Q_ABYTES, 8192, 1024));
        mbar_spin(lb + B_QF, 0);
        TL(0, L * 32 + 1); CK(0, L * 32 + 10);
        qkv_step<true>(acc0, acc1, da0, db0);
        uint32_t st = 1, ph = 0;
        #pragma unroll 1
        for (int k = 1; k < 16; k++) {
            mbar_spin(lb + B_QF + 8 * st, ph);
            if (k == 16 - QLEAD && wg) named_sync(NB_CONS, 256);
            qkv_step<false>(acc0, acc1, da0 + st * (Q_STB >> 4), db0 + st * (Q_STB >> 4));
            if (k == 15 && !wg) named_arrive(NB_CONS, 256);
            wg_wait<1>();
            if (leader) mbar_arrive(lb + B_QE + 8 * (st == 0 ? 2 : st - 1));
            if (++st == 3) { st = 0; ph ^= 1; }
        }
    }
    named_sync(NB_EPI + wg, 224);
    const int tid = tid_now(), lane = tid & 31, w = (tid >> 5) & 3, g = lane >> 2, t = lane & 3;
    const int lr0 = wg * 128 + w * 16 + g;
    float cf[4], nm[4];
    #pragma unroll
    for (int i = 0; i < 4; i++) { const float2 r = lds64f(base32(Q_RC + lr0 * 8) + ((i >> 1) * 64 + (i & 1) * 8) * 8); cf[i] = r.x; nm[i] = r.y; }
    const uint32_t cs = base32(Q_CS + t * 8);
    const int d = L ? (int)lds32(M_RT + 12) - ((cta_now() >> 4) * 256 + lr0) : -1;
    const uint4 hs = lds128(M_F2);
    const uint32_t ko = base32((lane >> 3) * 2048 + (w * 16 + (lane & 7)) * 16);
    Cols k0, k1;
    load_cols<2>(k0, cs);
    wg_wait<0>();
    pin(acc0); pin(acc1);
    TL(128, L * 32 + 2); CK(128, L * 32 + 11);
    named_arrive(NB_ML, 288);
    if ((tid & 127) == 0) mbar_arrive(lb + B_QE);
    if (__builtin_expect((d & ~72) == 0, 0)) {
        if (d == 0) { patch_row<0>(acc0, cs + (Q_FIX - Q_CS)); cf[0] = 1.f; nm[0] = 0.f; }
        else if (d == 8) { patch_row<2>(acc0, cs + (Q_FIX - Q_CS)); cf[1] = 1.f; nm[1] = 0.f; }
        else if (d == 64) { patch_row<0>(acc1, cs + (Q_FIX - Q_CS)); cf[2] = 1.f; nm[2] = 0.f; }
        else { patch_row<2>(acc1, cs + (Q_FIX - Q_CS)); cf[3] = 1.f; nm[3] = 0.f; }
    }
    __syncwarp();
    uint32_t pk[4][4];
    qkv_epi_head<2>(acc0, acc1, cf, nm, k0, __uint_as_float(hs.z), pk);
    load_cols<4>(k1, cs);
    mbar_spin(lb + B_QE + 8 - 8 * wg, wg);
    stage_kv((wg ? A_RING : A_KP) + ko, pk);
    qkv_epi_head<4>(acc0, acc1, cf, nm, k1, 1.f, pk);
    load_cols<3>(k0, cs);
    stage_kv(A_RING + wg * R_SLOT + 8192 + ko, pk);
    fence_async_smem();
    __syncwarp();
    mbar_arrive_elect(lb + B_KS + 8 * wg);
    qkv_epi_head<3>(acc0, acc1, cf, nm, k0, __uint_as_float(hs.w), pk);
    load_cols<0>(k1, cs);
    load_cols<5>(k0, cs);
    stage_kv(A_STB + wg * 8192 + ko, pk);
    qkv_epi_head<0>(acc0, acc1, cf, nm, k1, __uint_as_float(hs.x), pk);
    #pragma unroll
    for (int s = 0; s < 2; s++) {
        qa[4*s] = pk[0][2*s]; qa[4*s+1] = pk[1][2*s]; qa[4*s+2] = pk[0][2*s+1]; qa[4*s+3] = pk[1][2*s+1];
        qb[4*s] = pk[2][2*s]; qb[4*s+1] = pk[3][2*s]; qb[4*s+2] = pk[2][2*s+1]; qb[4*s+3] = pk[3][2*s+1];
    }
    mbar_spin(lb + B_KS, 0);
    {
        constexpr uint64_t dk = desc_plain(A_KP, 2048, 128);
        wg_fence();
        wg_qk_init(SA, qa[0], qa[1], qa[2], qa[3], dk);
        wg_qk_acc(SA, qa[4], qa[5], qa[6], qa[7], dk + 256);
        wg_qk_init(SB_, qb[0], qb[1], qb[2], qb[3], dk);
        wg_commit();
    }
    qkv_epi_head<5>(acc0, acc1, cf, nm, k0, 1.f, pk);
    load_cols<1>(k1, cs);
    stage_kv(A_STB + 16384 + wg * 8192 + ko, pk);
    qkv_epi_head<1>(acc0, acc1, cf, nm, k1, __uint_as_float(hs.y), pk);
    #pragma unroll
    for (int u = 0; u < 2; u++)
        #pragma unroll
        for (int s = 0; s < 2; s++) sts128(A_QX + (u * 2 + s) * 4096 + tid * 16, pk[2*u][2*s], pk[2*u+1][2*s], pk[2*u][2*s+1], pk[2*u+1][2*s+1]);
    fence_async_smem();
    wg_wait<0>();
    pin(SA); pin(SB_);
    TL(128, L * 32 + 5); CK(128, L * 32 + 12);
}

#define PMASK 0x000AAAAAu
#define IMASK 0x10101010u
__host__ __device__ constexpr bool is_poly(int j) { return !((PMASK >> j) & 1); }
struct Shift { uint32_t f0, f1, n0, n1, bad; };

__device__ __forceinline__ uint32_t exp2_mufu(uint32_t s, uint32_t nm) {
    uint32_t r;
    asm("ex2.approx.f16x2 %0, %1;" : "=r"(r) : "r"(hadd2(s, nm)));
    return r;
}
__device__ __forceinline__ uint32_t exp2_fix(uint32_t s, uint32_t fm, uint32_t ca, uint32_t& U, bool mul, uint32_t sixteen) {
    uint32_t G, D;
    asm("fma.rn.relu.f16x2 %0, %1, %2, %3;" : "=r"(U) : "r"(s), "r"(0x00400040u), "r"(fm));
    asm("fma.rn.f16x2 %0, %1, %2, %3;" : "=r"(G) : "r"(U & 0x003F003Fu), "r"(ca), "r"(0x98B898B8u));
    asm("{.reg .b32 n; neg.f16x2 n, %1; fma.rn.relu.f16x2 %0, %1, n, %2;}" : "=r"(D) : "r"(G), "r"(0x00570057u));
    if (mul) return U * sixteen - D;
    return (U << 4) - D;
}
__device__ __forceinline__ uint32_t or3(uint32_t a, uint32_t b, uint32_t c) { uint32_t r; asm("lop3.b32 %0, %1, %2, %3, 0xFE;" : "=r"(r) : "r"(a), "r"(b), "r"(c)); return r; }
__device__ __forceinline__ void exp_tile(const uint32_t (&S)[32], uint32_t (&P)[32], Shift& h, uint32_t ca, uint32_t sixteen) {
    uint32_t U[33];
    int n = 0;
    #pragma unroll
    for (int i = 0; i < 32; i++) {
        if (is_poly(i)) P[i] = exp2_fix(S[i], (i & 1) ? h.f1 : h.f0, ca, U[n++], (IMASK >> i) & 1, sixteen);
        else P[i] = exp2_mufu(S[i], (i & 1) ? h.n1 : h.n0);
    }
    U[n] = 0u;
    #pragma unroll
    for (int i = 0; i < 32; i += 6) {
        if (i + 5 <= n) h.bad = or3(h.bad, or3(U[i], U[i + 1], U[i + 2]), or3(U[i + 3], U[i + 4], U[i + 5]));
        else
        {
            #pragma unroll
            for (int j = i; j < i + 6; j += 2) if (j < n) h.bad = or3(h.bad, U[j], U[j + 1]);
        }
    }
    pin(P);
}
__device__ __forceinline__ uint32_t hfma2(uint32_t a, uint32_t b, uint32_t c) { uint32_t r; asm("fma.rn.f16x2 %0, %1, %2, %3;" : "=r"(r) : "r"(a), "r"(b), "r"(c)); return r; }
__device__ __forceinline__ void unit_start(const uint32_t (&S)[32], Shift& h, uint32_t (&o2)[10]) {
    uint32_t m[4] = {S[0], S[1], S[2], S[3]};
    #pragma unroll
    for (int i = 1; i < 8; i++)
        #pragma unroll
        for (int e = 0; e < 4; e++) m[e] = hmax2(m[e], S[4 * i + e]);
    const uint32_t a = hadd2(m[0], m[2]), c = hadd2(m[1], m[3]);
    uint32_t x = hadd2(__byte_perm(a, c, 0x5410), __byte_perm(a, c, 0x7632));
    x = hadd2(x, __shfl_xor_sync(0xffffffffu, x, 1));
    x = hadd2(x, __shfl_xor_sync(0xffffffffu, x, 2));
    const uint32_t T = hfma2(x, 0xAC00AC00u, 0x5DEB5DEBu);
    const uint32_t n = hadd2(T, 0xDE00DE00u), f = hfma2(n, 0x00400040u, 0x03C003C0u);
    h.n0 = __byte_perm(n, 0, 0x1010); h.n1 = __byte_perm(n, 0, 0x3232);
    h.f0 = __byte_perm(f, 0, 0x1010); h.f1 = __byte_perm(f, 0, 0x3232);
    h.bad = T ^ 0x58005800u;
    #pragma unroll
    for (int i = 0; i < 10; i++) o2[i] = 0u;
}
__device__ __forceinline__ uint32_t o_offset() {
    const int c = cta_now(), tid = tid_now();
    return ((c >> 4) * 256 + (tid & 128) + ((tid >> 1) & 48) + ((tid >> 2) & 7)) * (D_ * 2) + (c & 15) * 64 + (tid & 3) * 16;
}
template <int PASS, int UNIT>
__device__ __forceinline__ void unit_end(const uint32_t (&o)[10], uint32_t bad, uint32_t lb, uint32_t oo, uint32_t& fail) {
    float v[20];
    #pragma unroll
    for (int i = 0; i < 10; i++) h2_unpack(o[i], v[2 * i], v[2 * i + 1]);
    const float i0 = rcp(v[16]), i1 = rcp(v[18]);
    const uint4 iv = lds128(M_IVS + PASS * 64 + (oo & 48));
    uint32_t r[8], z = 0;
    #pragma unroll
    for (int j = 0; j < 4; j++) {
        r[j] = pack_bf16(v[4*j] * i0, v[4*j+1] * i0); r[4 + j] = pack_bf16(v[4*j+2] * i1, v[4*j+3] * i1);
        z = bfma2(r[j], r[4 + j], z);
    }
    const bool good = o[8] - 0x34003400u < 0x48000000u && o[9] - 0x34003400u < 0x48000000u &&
                      ((bad & 0xF800F800u) | (bmul2(z, 0u) & 0x7FFF7FFFu) | (fail & (1u << (2 * PASS + UNIT)))) == 0;
    const bool all = __all_sync(0xffffffffu, good);
    char* dst = reinterpret_cast<char*>(g_o) + oo + (UNIT * 64 * D_ + PASS * 512) * 2;
    stg128_pred(dst, make_uint4(bmul2(r[0], iv.x), bmul2(r[1], iv.y), bmul2(r[2], iv.z), bmul2(r[3], iv.w)), all);
    stg128_pred(dst + 16 * D_, make_uint4(bmul2(r[4], iv.x), bmul2(r[5], iv.y), bmul2(r[6], iv.z), bmul2(r[7], iv.w)), all);
    if (__builtin_expect(!all, 0)) {
        fail |= 1u << (2 * PASS + UNIT);
        if (PASS == 0) {
            #pragma unroll
            for (int s = 0; s < 2; s++) g_qsave[cta_now()][UNIT * 2 + s][tid_now()] = lds128(A_KP + (UNIT * 2 + s) * 4096 + tid_now() * 16);
        }
    }
    __syncwarp();
    mbar_arrive_elect_p(lb + PASS * 16, all);
}
__device__ __forceinline__ void swap_q(uint32_t (&q)[8], uint32_t a) {
    asm volatile("{\n.reg .pred p;\nsetp.ne.u32 p, %8, 0;\n"
                 "@p st.shared.v4.b32 [%8 + -8192], {%0, %1, %2, %3};\n@p st.shared.v4.b32 [%8 + -4096], {%4, %5, %6, %7};\n"
                 "@p ld.shared.v4.b32 {%0, %1, %2, %3}, [%8];\n@p ld.shared.v4.b32 {%4, %5, %6, %7}, [%8 + 4096];\n}"
                 : "+r"(q[0]), "+r"(q[1]), "+r"(q[2]), "+r"(q[3]), "+r"(q[4]), "+r"(q[5]), "+r"(q[6]), "+r"(q[7]) : "r"(a) : "memory");
}
static_assert(A_QX == A_KP + 8192, "parking places");
template <bool INIT>
__device__ __forceinline__ void issue_pv(uint32_t (&o)[10], const uint32_t (&P)[32], uint64_t dv) {
    if (INIT) wg_pv_init(o, P[0], P[1], P[2], P[3], dv); else wg_pv_acc(o, P[0], P[1], P[2], P[3], dv);
    #pragma unroll
    for (int k = 1; k < 8; k++) wg_pv_acc(o, P[4*k], P[4*k+1], P[4*k+2], P[4*k+3], dv + k * 16);
}

__device__ __forceinline__ uint4 quad_transpose(uint32_t x0, uint32_t x1, uint32_t x2, uint32_t x3, int t) {
    const bool b0 = t & 1, b1 = t & 2;
    uint32_t s0 = b0 ? x0 : x1, s1 = b0 ? x2 : x3;
    s0 = __shfl_xor_sync(0xffffffffu, s0, 1); s1 = __shfl_xor_sync(0xffffffffu, s1, 1);
    const uint32_t y0 = b0 ? s0 : x0, y1 = b0 ? x1 : s0, y2 = b0 ? s1 : x2, y3 = b0 ? x3 : s1;
    uint32_t u0 = b1 ? y0 : y2, u1 = b1 ? y1 : y3;
    u0 = __shfl_xor_sync(0xffffffffu, u0, 2); u1 = __shfl_xor_sync(0xffffffffu, u1, 2);
    return b1 ? make_uint4(u0, u1, y2, y3) : make_uint4(y0, y1, u0, u1);
}
__device__ __forceinline__ uint32_t movm(uint32_t v) { uint32_t r; asm volatile("movmatrix.sync.aligned.m8n8.trans.b16 %0, %1;" : "=r"(r) : "r"(v)); return r; }
__device__ __forceinline__ void attn_repair(const uint32_t (&q)[8], uint32_t lb, int pass, int unit) {
    const int tid = tid_now(), g = (tid & 31) >> 2, t = tid & 3;
    float ss = ldsf(M_SS + pass * 4);
    if (ss == 0.f) ss = 1.f;
    const uint4 q0 = quad_transpose(q[0], q[2], q[4], q[6], t), q1 = quad_transpose(q[1], q[3], q[5], q[7], t);
    const char* kv = g_kv + (size_t)((cta_now() & 15) * 2 + pass) * 16 * KV_TILE + t * 2048 + g * 16;
    float o[4][4], m0 = -INFINITY, m1 = -INFINITY, l0 = 0.f, l1 = 0.f;
    #pragma unroll
    for (int j = 0; j < 4; j++) { o[j][0] = 0.f; o[j][1] = 0.f; o[j][2] = 0.f; o[j][3] = 0.f; }
    #pragma unroll 1
    for (int b = 0; b < 32; b++) {
        const char* p = kv + (b >> 1) * KV_TILE + (b & 1) * 1024;
        const char* pk = kv + (((b >> 1) - 1) & 15) * KV_TILE + (b & 1) * 1024;
        uint4 kf[8], vf[8];
        #pragma unroll
        for (int i = 0; i < 8; i++) { kf[i] = __ldcg(reinterpret_cast<const uint4*>(pk + i * 128)); vf[i] = __ldcg(reinterpret_cast<const uint4*>(p + 8192 + i * 128)); }
        float s[8][4];
        #pragma unroll
        for (int i = 0; i < 8; i++) {
            s[i][0] = 0.f; s[i][1] = 0.f; s[i][2] = 0.f; s[i][3] = 0.f;
            mma_f16(s[i], q0.x, q1.x, q0.y, q1.y, kf[i].x, kf[i].y); mma_f16(s[i], q0.z, q1.z, q0.w, q1.w, kf[i].z, kf[i].w);
        }
        float t0 = m0, t1 = m1;
        #pragma unroll
        for (int i = 0; i < 8; i++) { t0 = fmaxf(t0, fmaxf(s[i][0], s[i][1])); t1 = fmaxf(t1, fmaxf(s[i][2], s[i][3])); }
        t0 = quad_max(t0); t1 = quad_max(t1);
        const float a0 = ex2((m0 - t0) * ss), a1 = ex2((m1 - t1) * ss);
        m0 = t0; m1 = t1;
        l0 *= a0; l1 *= a1;
        #pragma unroll
        for (int j = 0; j < 4; j++) { o[j][0] *= a0; o[j][1] *= a0; o[j][2] *= a1; o[j][3] *= a1; }
        #pragma unroll
        for (int k = 0; k < 4; k++) {
            uint32_t pf[4];
            #pragma unroll
            for (int e = 0; e < 2; e++) {
                const float p0 = ex2((s[2*k+e][0] - m0) * ss), p1 = ex2((s[2*k+e][1] - m0) * ss), p2 = ex2((s[2*k+e][2] - m1) * ss), p3 = ex2((s[2*k+e][3] - m1) * ss);
                l0 += p0 + p1; l1 += p2 + p3;
                pf[2*e] = pack_f16(p0, p1); pf[2*e+1] = pack_f16(p2, p3);
            }
            mma_f16(o[0], pf[0], pf[1], pf[2], pf[3], movm(vf[2*k].x), movm(vf[2*k+1].x));
            mma_f16(o[1], pf[0], pf[1], pf[2], pf[3], movm(vf[2*k].y), movm(vf[2*k+1].y));
            mma_f16(o[2], pf[0], pf[1], pf[2], pf[3], movm(vf[2*k].z), movm(vf[2*k+1].z));
            mma_f16(o[3], pf[0], pf[1], pf[2], pf[3], movm(vf[2*k].w), movm(vf[2*k+1].w));
        }
    }
    const float i0 = 16.f * rcp(quad_sum(l0)), i1 = 16.f * rcp(quad_sum(l1));
    uint32_t* dst = reinterpret_cast<uint32_t*>(reinterpret_cast<char*>(g_o) + (o_offset() & ~48u) + (unit * 64 * D_ + pass * 512) * 2) + t;
    #pragma unroll
    for (int j = 0; j < 4; j++) {
        const uint32_t iv = lds32(M_IVS + pass * 64 + j * 16 + t * 4);
        dst[j * 4] = pack_bf16(o[j][0] * i0 * bf_lo(iv), o[j][1] * i0 * bf_hi(iv));
        dst[j * 4 + 4 * D_] = pack_bf16(o[j][2] * i1 * bf_lo(iv), o[j][3] * i1 * bf_hi(iv));
    }
    __syncwarp();
    mbar_arrive_elect(lb + B_OD + (pass * 2 + (tid >> 7)) * 8);
}

__device__ __forceinline__ void load_gu(uint32_t (&f)[64], uint32_t src, int warp, int lane) {
    const uint32_t row = (warp & 3) * 64 + (lane >> 4) * 8 + (lane & 7), ch = (lane >> 3) & 1, sw = (lane >> 1) & 3;
    const uint32_t a0 = base32(src + (warp >> 2) * 32768 + row * 64 + ((ch ^ sw) << 4)), a1 = base32(a0 ^ 32);
    #pragma unroll
    for (int i = 0; i < 16; i++) ldsm4t(f[4*i], f[4*i+1], f[4*i+2], f[4*i+3], ((i & 1) ? a1 : a0) + ((i >> 1) & 1) * 16384 + (i >> 2) * 1024);
}

__device__ __forceinline__ void arrive_loaded(uint32_t bar, const uint32_t (&f)[64], uint32_t zero) {
    uint32_t x = 0;
    #pragma unroll
    for (int i = 0; i < 16; i++) x |= f[4 * i];
    mbar_arrive_elect(bar + (x & zero));
}
__device__ __forceinline__ void flush(uint32_t (&o2)[10], const uint32_t (&o)[10]) {
    #pragma unroll
    for (int i = 0; i < 10; i++) o2[i] = hadd2(o2[i], o[i]);
}
__device__ __forceinline__ void attention_phase(int L, uint32_t lb, int wg, uint32_t (&qa)[8], uint32_t (&qb)[8], uint32_t (&SA)[32], uint32_t (&SB_)[32], uint64_t dk0, uint64_t dv0, uint32_t ca, uint32_t (&wa)[64], uint32_t zero, uint32_t sixteen) {
    uint32_t PA[32], PB[32], oa[10], ob[10], oa2[10], ob2[10];
    Shift ha, hb;
    uint32_t fail = (lds32(M_SS) ? 3u : 0u) | (lds32(M_SS + 4) ? 12u : 0u);
    ca += base32(fail) >> 4;
    const uint32_t oo = o_offset(), odb = lb + B_OD + wg * 8;
    constexpr uint64_t SL = R_SLOT >> 4, KH = 4096 >> 4;
    uint64_t dkd = dk0 + ((A_KP - A_RING) >> 4);
    unit_start(SA, ha, oa2);
    exp_tile(SA, PA, ha, ca, sixteen);
    #pragma unroll
    for (int i = 0; i < 10; i++) { ob[i] = 0u; ob2[i] = 0u; }
    hb = ha;
    mbar_spin(lb + B_KS + 8, 0);
    mbar_spin(lb + B_ONE, 0);
    #pragma unroll 1
    for (int it = 0; ; it++) {
        const uint32_t ph = it & 1;
        uint32_t qsw = 0;
        #pragma unroll
        for (int u = 0; u < 4; u++) {
            const uint64_t dk = opaque(dk0) + u * SL, dv = opaque(dv0) + u * SL;
            wg_fence();
            if (u == 0) { wg_qk_acc(SB_, qb[4], qb[5], qb[6], qb[7], dkd + KH); wg_commit(); }
            if (u == 0) issue_pv<true>(oa, PA, dv); else issue_pv<false>(oa, PA, dv);
            wg_qk_init(SA, qa[0], qa[1], qa[2], qa[3], dk);
            wg_qk_acc(SA, qa[4], qa[5], qa[6], qa[7], dk + KH);
            wg_commit();
            wg_wait<1>();
            pin(SB_); pin(ob);
            if (u == 0) {
                mbar_arrive_elect_p(lb + B_AE + 24, it);
                flush(ob2, ob);
                if (__builtin_expect((it & 3) == 0, 0)) {
                    if (it) unit_end<0, 1>(ob2, hb.bad, odb, oo, fail);
                    unit_start(SB_, hb, ob2);
                }
            } else mbar_arrive_elect(lb + B_AE + 8 * (u - 1));
            if (u == 3) swap_q(qb, qsw ? qsw + 8192 : 0u);
            uint32_t ready = 0;
            if (u < 3) ready = mbar_test(lb + B_AF + 8 * (u + 1), ph);
            exp_tile(SB_, PB, hb, ca, sixteen);
            wg_fence();
            if (u == 0) issue_pv<true>(ob, PB, dv); else issue_pv<false>(ob, PB, dv);
            wg_qk_init(SB_, qb[0], qb[1], qb[2], qb[3], dk);
            if (u < 3) wg_qk_acc(SB_, qb[4], qb[5], qb[6], qb[7], dk + KH);
            wg_commit();
            if (u < 3) mbar_spin_unless(ready, lb + B_AF + 8 * (u + 1), ph);
            wg_wait<1>();
            pin(SA); pin(oa);
            if (u == 2) { qsw = it == 3 ? A_QX + tid_now() * 16 : 0u; swap_q(qa, qsw); }
            if (u == 3) {
                flush(oa2, oa);
                if (__builtin_expect((it & 3) == 3, 0)) {
                    TL(0, L * 32 + 7 + (it >> 2)); CK(0, L * 32 + 1 + (it >> 2));
                    if (it == 7) goto done;
                    unit_end<0, 0>(oa2, ha.bad, odb, oo, fail);
                    unit_start(SA, ha, oa2);
                }
            }
            exp_tile(SA, PA, ha, ca, sixteen);
        }
        mbar_spin(lb + B_AF, ph ^ 1);
        wg_wait<0>();
        dkd = dk0 + 3 * SL;
    }
done:
    mbar_spin(lb + B_GU, 0);
    load_gu(wa, F_GU0, tid_now() >> 5, tid_now() & 31);
    unit_end<1, 0>(oa2, ha.bad, odb, oo, fail);
    arrive_loaded(lb + B_FG, wa, zero);
    wg_wait<0>();
    pin(ob);
    mbar_arrive_elect(lb + B_AE + 24);
    flush(ob2, ob);
    unit_end<1, 1>(ob2, hb.bad, odb, oo, fail);
    if (__builtin_expect(fail != 0, 0)) {
        #pragma unroll 1
        for (int r = 3; r >= 0; r--) {
            if ((fail >> r) & 1) {
                uint32_t q[8];
                #pragma unroll
                for (int i = 0; i < 8; i++) q[i] = r < 2 ? reinterpret_cast<const uint32_t*>(&g_qsave[cta_now()][r * 2 + (i >> 2)][tid_now()])[i & 3] : (r & 1) ? qb[i] : qa[i];
                attn_repair(q, lb, r >> 1, r & 1);
            }
        }
    }
    TL(0, L * 32 + 9); CK(0, L * 32 + 8);
}

#define OSPLIT 8
__device__ __forceinline__ void oproj_steps(float (&acc)[64], uint32_t lb, int wg, int k0, int k1) {
    const bool leader = (tid_now() & 127) == 0;
    #pragma unroll 1
    for (int k = k0; k < k1; k++) {
        const uint32_t st = k & 3;
        mbar_spin(lb + B_OF + 8 * st, (k >> 2) & 1);
        const uint64_t da = desc_sw128(o_a(st) + wg * 8192, 16, 1024);
        const uint64_t db = desc_sw128(o_b(st), 8192, 1024);
        wg_fence();
        #pragma unroll
        for (int kk = 0; kk < 4; kk++) wg_gemm_n128(acc, da + kk * 2, db + kk * 128);
        wg_commit();
        wg_wait<1>();
        if (leader && k > 0) mbar_arrive(lb + B_OE + 8 * ((k - 1) & 3));
    }
}

__device__ __forceinline__ void stage_tile(const uint32_t (&xa)[4], const uint32_t (&xv)[32], uint32_t lb) {
    #pragma unroll
    for (int m = 0; m < 8; m++) stsm4(xa[m & 3] + (m < 4 ? 0 : XT1 - XT0), xv[4*m], xv[4*m+1], xv[4*m+2], xv[4*m+3]);
    fence_async_smem();
    __syncwarp();
    mbar_arrive_elect(lb + B_XS);
}

__device__ __forceinline__ void tail_phase(int L, uint32_t lb, int wg, const uint32_t (&wa)[64], uint32_t zero) {
    const int c = cta_now(), blk = c >> 3, cb = c & 7, tid = tid_now();
    const int lane = tid & 31, w = (tid >> 5) & 3, g = lane >> 2, t = lane & 3;
    const int lr0 = wg * 64 + w * 16 + g;
    uint32_t xa[4];
    #pragma unroll
    for (int m = 0; m < 4; m++) xa[m] = base32(XT0 + (wg * 64 + w * 16 + (lane & 15)) * 128 + (((lane >> 4) ^ (lane & 7) ^ (2 * m)) << 4));
    uint32_t xv[32];
    const bool ffn = c < NFC;
    uint32_t wb[64], wd[64];
    {
        float acc[64];
        #pragma unroll
        for (int i = 0; i < 64; i++) acc[i] = 0.f;
        pin(acc);
        float2 rs0 = make_float2(0.f, 0.f), rs1 = rs0;
        if (L) { rs0 = __ldcg(&g_x.rs1[blk * 128 + lr0]); rs1 = __ldcg(&g_x.rs1[blk * 128 + lr0 + 8]); }
        oproj_steps(acc, lb, wg, 0, OSPLIT);
        mbar_spin(lb + B_RES, 0);
        #pragma unroll
        for (int m = 0; m < 8; m++) ldsm4(xv[4*m], xv[4*m+1], xv[4*m+2], xv[4*m+3], xa[m & 3] + (m < 4 ? 0 : XT1 - XT0));
        if (L) {
            const int d = (int)lds32(M_RT + 12) - (blk * 128 + lr0);
            const Ln2 k0 = ln2_coef(rs0.y, d == 0 ? 0.f : rsq(rs0.x + LN_EPS)), k1 = ln2_coef(rs1.y, d == 8 ? 0.f : rsq(rs1.x + LN_EPS));
            #pragma unroll
            for (int j = 0; j < 16; j++) { xv[2*j] = add_ln2(xv[2*j], k0); xv[2*j+1] = add_ln2(xv[2*j+1], k1); }
        }
        pin(xv);
        oproj_steps(acc, lb, wg, OSPLIT, 16);
        uint32_t wv[16];
        #pragma unroll
        for (int i = 0; i < 4; i++) ldsm4(wv[4*i], wv[4*i+1], wv[4*i+2], wv[4*i+3], (lane & 1) ? M_RED + (lane >> 3) * 16 + i * 64 : M_RED + 256);
        wg_wait<0>();
        pin(acc);
        TL(0, L * 32 + 11); CK(0, L * 32 + 13);
        float sa[4] = {0.f, 0.f, 0.f, 0.f}, sb[4] = {0.f, 0.f, 0.f, 0.f}, sc[4] = {0.f, 0.f, 0.f, 0.f};
        float sd[4] = {0.f, 0.f, 0.f, 0.f}, se[4] = {0.f, 0.f, 0.f, 0.f};
        #pragma unroll
        for (int m = 0; m < 8; m++) {
            #pragma unroll
            for (int i = 0; i < 4; i++) xv[4*m+i] = badd2(xv[4*m+i], pack_bf16(acc[8*m + 2*i], acc[8*m + 2*i + 1]));
            mma_bf16(sa, xv[4*m], xv[4*m+1], xv[4*m+2], xv[4*m+3], wv[2*m], wv[2*m+1]);
            mma_bf16_k8(sb, xv[4*m], xv[4*m+1], xv[4*m]); mma_bf16_k8(sc, xv[4*m], xv[4*m+1], xv[4*m+1]);
            mma_bf16_k8(sd, xv[4*m+2], xv[4*m+3], xv[4*m+2]); mma_bf16_k8(se, xv[4*m+2], xv[4*m+3], xv[4*m+3]);
        }
        if (t == (g >> 1)) {
            st_x128(&g_x.part[L][blk][cb][lr0], __float_as_uint(sa[0]), __float_as_uint((g & 1) ? sb[1] + sd[1] : sb[0] + sd[0]), __float_as_uint(sa[1]), 0u);
            st_x128(&g_x.part[L][blk][cb][lr0 + 8], __float_as_uint(sa[2]), __float_as_uint((g & 1) ? sc[3] + se[3] : sc[2] + se[2]), __float_as_uint(sa[3]), 0u);
        }
        __syncwarp();
    }
    TL(0, L * 32 + 12);
    float mean[2], rstd[2], score[2];
    {
        const uint4* src = &g_x.part[L][blk][2 * t][lr0];
        uint4 p[4];
        uint32_t n = 0;
        p[0] = ld_x128(src); p[1] = ld_x128(src + 128); p[2] = ld_x128(src + 8); p[3] = ld_x128(src + 136);
        load_gu(wb, F_GU1, tid >> 5, lane);
        if (L == 0) stage_tile(xa, xv, lb);
        #pragma unroll 1
        while (warp_any((p[0].w | p[1].w | p[2].w | p[3].w) != 0)) {
            p[0] = ld_x128(src); p[1] = ld_x128(src + 128); p[2] = ld_x128(src + 8); p[3] = ld_x128(src + 136);
            poll_tick(n);
        }
        const float ws = ldsf(M_WS);
        #pragma unroll
        for (int h = 0; h < 2; h++) {
            const float su = quad_sum(__uint_as_float(p[2*h].x) + __uint_as_float(p[2*h+1].x));
            const float sq = quad_sum(__uint_as_float(p[2*h].y) + __uint_as_float(p[2*h+1].y));
            const float sd = quad_sum(__uint_as_float(p[2*h].z) + __uint_as_float(p[2*h+1].z));
            mean[h] = su * (1.f / D_);
            const float var = fmaxf(sq * (1.f / D_) - mean[h] * mean[h], 0.f);
            rstd[h] = rsq(var + LN_EPS);
            score[h] = rstd[h] * (sd - mean[h] * ws);
            if (L == 0 && cb == 0 && t == h) st_x64(&g_x.rs1[blk * 128 + lr0 + 8 * h], __float_as_uint(var), __float_as_uint(mean[h]));
        }
    }
    TL(0, L * 32 + 13);
    {
        const uint32_t k0 = order_bits(score[0]), k1 = order_bits(score[1]);
        const uint32_t kb = max(k0, k1), m = redux_max(kb);
        const uint32_t mrow = redux_min(kb == m ? (k1 > k0 ? lr0 + 8 : lr0) : 0x7FFFFFFFu);
        if (lane == 0) sts64(M_KR + (tid >> 5) * 8, m, mrow);
        named_sync(NB_CONS, 256);
        const float2 e = lds64f(M_KR + (lane & 7) * 8);
        const uint32_t m2 = redux_max(__float_as_uint(e.x));
        const int d = (int)redux_min(__float_as_uint(e.x) == m2 ? __float_as_uint(e.y) : 0x7FFFFFFFu) - lr0;
        if ((d & ~8) == 0) {
            if (t == 0)
                st_x128(&g_x.hdr[L][cb][blk], __float_as_uint(d ? score[1] : score[0]), __float_as_uint(d ? mean[1] : mean[0]), __float_as_uint(d ? rstd[1] : rstd[0]), blk * 128 + lr0 + d);
            #pragma unroll
            for (int b = 0; b < 4; b++)
                st_x128(&g_x.cand[L][blk][cb * 64 + b * 16 + t * 4], d ? xv[8*b+1] : xv[8*b], d ? xv[8*b+3] : xv[8*b+2], d ? xv[8*b+5] : xv[8*b+4], d ? xv[8*b+7] : xv[8*b+6]);
        }
        __syncwarp();
    }
    if (L) {
        const Ln2 k0 = ln2_coef(mean[0], rstd[0]), k1 = ln2_coef(mean[1], rstd[1]);
        #pragma unroll
        for (int j = 0; j < 16; j++) { xv[2*j] = add_ln2(xv[2*j], k0); xv[2*j+1] = add_ln2(xv[2*j+1], k1); }
        stage_tile(xa, xv, lb);
    }
    {
        mbar_spin(lb + B_WD, 0);
        const uint32_t a0 = f_wd(tid >> 6) + ((tid >> 5) & 1) * 8192 + ((lane >> 4) * 8 + (lane & 7)) * 128, ch = ((lane >> 3) & 1) ^ (lane & 7);
        #pragma unroll
        for (int i = 0; i < 16; i++) ldsm4t(wd[4*i], wd[4*i+1], wd[4*i+2], wd[4*i+3], base32(a0 + ((ch ^ (i & 6)) << 4)) + (i >> 3) * 4096 + (i & 1) * 2048);
        arrive_loaded(lb + B_WF, wd, zero);
    }
    Route rt;
    {
        uint4 e;
        uint32_t n = 0;
        #pragma unroll 1
        do { e = ld_x128(&g_x.hdr[L][cb][lane & 15]); poll_tick(n); } while (warp_any(e.w == EMPTY));
        const uint32_t k = order_bits(__uint_as_float(e.x)), m = redux_max(k);
        rt.idx = (int)redux_min(k == m ? e.w : 0x7FFFFFFFu);
        rt.r = __shfl_sync(0xffffffffu, __uint_as_float(e.x), rt.idx >> 7);
        rt.mean = __shfl_sync(0xffffffffu, __uint_as_float(e.y), rt.idx >> 7);
        rt.rstd = __shfl_sync(0xffffffffu, __uint_as_float(e.z), rt.idx >> 7);
    }
    TL(0, L * 32 + 14);
    if (tid == 0) sts128(M_RT + 16 * L, __float_as_uint(rt.r), __float_as_uint(rt.mean), __float_as_uint(rt.rstd), rt.idx);
    if (ffn) {
        const Ln2 kx = ln2_coef(rt.mean, rt.rstd);
        uint4 x[4];
        {
            const uint32_t* src = &g_x.cand[L][rt.idx >> 7][(tid >> 5) * 32 + t * 4];
            uint32_t n = 0;
            #pragma unroll 1
            do {
                x[0] = ld_x128(src); x[1] = ld_x128(src + 16); x[2] = ld_x128(src + 256); x[3] = ld_x128(src + 272);
                poll_tick(n);
            } while (warp_any(x[0].x == EMPTY || x[1].x == EMPTY || x[2].x == EMPTY || x[3].x == EMPTY));
        }
        TL(0, L * 32 + 15);
        float d[4][4];
        #pragma unroll
        for (int i = 0; i < 4; i++) { d[i][0] = 0.f; d[i][1] = 0.f; d[i][2] = 0.f; d[i][3] = 0.f; }
        #pragma unroll
        for (int k = 0; k < 8; k++) {
            const uint32_t b0 = ln2((k & 1) ? x[k >> 1].z : x[k >> 1].x, kx), b1 = ln2((k & 1) ? x[k >> 1].w : x[k >> 1].y, kx);
            const uint32_t* f = (k < 4 ? wa : wb) + (k & 3) * 16;
            #pragma unroll
            for (int i = 0; i < 4; i++) mma_bf16(d[i], f[4*i], f[4*i+1], f[4*i+2], f[4*i+3], b0, b1);
        }
        #pragma unroll
        for (int h = 0; h < 2; h++) {
            const float a = (t & 1) ? d[1][2*h] : d[0][2*h], b = (t & 1) ? d[3][2*h] : d[2][2*h];
            stsf(M_RED + ((tid >> 5) * 64 + t * 16 + h * 8 + g) * 4, (t & 2) ? b : a);
        }
        named_sync(NB_CONS, 256);
        TL(0, L * 32 + 16);
        float s0 = 0.f, s1 = 0.f;
        #pragma unroll
        for (int i = 0; i < 8; i++) { const float2 v = lds64f(base32(M_RED + lane * 8) + i * 256); s0 += v.x; s1 += v.y; }
        const uint32_t mine = pack_bf16(s0, s1), other = __shfl_xor_sync(0xffffffffu, mine, 16);
        const uint32_t gv = lane < 16 ? mine : other, uv = lane < 16 ? other : mine;
        const float g0 = bf_lo(gv), g1 = bf_hi(gv);
        const uint32_t hv = bmul2(pack_bf16(g0 * rcp(1.f + __expf(-g0)), g1 * rcp(1.f + __expf(-g1))), uv);
        uint32_t hb[4];
        #pragma unroll
        for (int i = 0; i < 4; i++) hb[i] = __shfl_sync(0xffffffffu, hv, 4 * i + t);
        float y[8][4];
        #pragma unroll
        for (int i = 0; i < 8; i++) {
            y[i][0] = 0.f; y[i][1] = 0.f; y[i][2] = 0.f; y[i][3] = 0.f;
            mma_bf16(y[i], wd[8*i], wd[8*i+1], wd[8*i+2], wd[8*i+3], hb[0], hb[1]);
            mma_bf16(y[i], wd[8*i+4], wd[8*i+5], wd[8*i+6], wd[8*i+7], hb[2], hb[3]);
        }
        float* dst = &g_x.ypart[L][(tid >> 5) * 16 + t * 4][c][g];
        #pragma unroll
        for (int i = 0; i < 2; i++)
            #pragma unroll
            for (int h = 0; h < 2; h++) {
                const float a = (t & 1) ? y[2 + i][2*h] : y[i][2*h], b = (t & 1) ? y[6 + i][2*h] : y[4 + i][2*h];
                st_x32(dst + (i * 2 + h) * (NFC * 8), __float_as_uint((t & 2) ? b : a));
            }
    }
    __syncwarp();
    mbar_arrive_elect(lb + B_FD);
    TL(0, L * 32 + 17);
}

__device__ __forceinline__ void qkv_load_w(const Maps& mp, uint32_t dst, int k, uint32_t fb) { tma_load3(dst, &mp.wqkv, (blockIdx.x & 15) * 64, k * 64, 0, fb); }
__device__ __forceinline__ void qkv_load_x(const CUtensorMap* tx, uint32_t sa, int k, uint32_t fb) {
    #pragma unroll
    for (int a = 0; a < 2; a++) tma_load(sa + a * 16384, tx, k * 64, (blockIdx.x >> 4) * 256 + a * 128, fb);
}
#define RESIT 0
__device__ __forceinline__ void producer_role(const Maps& mp, const bf16* __restrict__ x0) {
    const int c = blockIdx.x, mt = c >> 4, nt = c & 15, blk = c >> 3, cb = c & 7;
    const uint64_t pol = policy_evict_first();
    #pragma unroll 1
    for (int L = 0; L < 2; L++) {
        const uint32_t lb = M_BAR + L * BAR_SET;
        const CUtensorMap* tx = &mp.x[L];
        mbar_expect_tx(lb + B_SW, 49152);
        if (L == 0) {
            mbar_nap(lb + B_QF, 0);
            l2_prefetch(x0 + (size_t)c * 16 * D_, 32768);
            qkv_load_w(mp, SD_W, mt * 2, lb + B_SW);
            qkv_load_w(mp, SD_W + 24576, mt * 2 + 1, lb + B_SW);
        } else {
            mbar_nap(M_BAR + B_WF, 0);
            flags16_wait(g_x.x[0][mt]);
            fence_async_global();
            TL(256, 32);
        }
        {
            uint32_t st = 0, ph = L;
            #pragma unroll 1
            for (int k = L ? 0 : 3; k < 16; k++) {
                mbar_sleep(k == 1 ? M_BAR + B_FD : lb + B_QE + 8 * st, k == 1 ? 0 : ph);
                const uint32_t fb = lb + B_QF + 8 * st, sa = SB + st * Q_STB;
                mbar_expect_tx(fb, Q_STB);
                qkv_load_x(tx, sa, k, fb);
                qkv_load_w(mp, sa + Q_ABYTES, k, fb);
                if (L && k >= 3 && k < 7) tma_load(SD_W + (k - 3) * 12288, &mp.r, c * 24, (k - 3) * 256, lb + B_SW);
                if (++st == 3) { st = 0; ph ^= 1; }
            }
        }
        mbar_sleep(lb + B_QE, 1);
        TL(256, L * 32 + 26);
        mbar_arrive(lb + B_AF);
        {
            const char* kv = g_kv + (size_t)nt * 32 * KV_TILE;
            const uint8_t* fl = g_x.kv[L][nt * 2];
            #pragma unroll 1
            for (int j = 1; j < 4; j++) {
                flag_wait(fl + ((2 * mt + j + 1) & 15));
                fence_async_global();
                const uint32_t bytes = j == 1 ? 8192 : 16384;
                mbar_expect_tx(lb + B_AF + 8 * j, bytes);
                bulk_load(A_RING + j * R_SLOT, kv + ((2 * mt + j) & 15) * KV_TILE, bytes, lb + B_AF + 8 * j);
                if (j == 1) TL(256, L * 32 + 21);
            }
            flags16_wait(fl);
            fence_async_global();
            #pragma unroll 1
            for (int it = 1; it < 8; it++) {
                #pragma unroll
                for (int u = 0; u < 4; u++) {
                    const char* src = kv + ((2 * mt + 4 * it + u) & 15) * KV_TILE;
                    const uint32_t fb = lb + B_AF + 8 * u, dst = A_RING + u * R_SLOT;
                    mbar_nap(lb + B_AE + 8 * u, (it - 1) & 1);
                    mbar_expect_tx(fb, 16384);
                    if (u < 3) bulk_load(dst, src, 16384, fb);
                    else {
                        bulk_load(dst + 8192, src + 8192, 8192, fb);
                        if (it == 3) {
                            flags16_wait(fl + 128);
                            fence_async_global();
                            kv += 16 * KV_TILE; src += 16 * KV_TILE;
                        }
                        bulk_load(dst, src, 8192, fb);
                    }
                }
            }
        }
        #pragma unroll 1
        for (int it = 0; it < 4; it++) {
            #pragma unroll
            for (int s = 0; s < 4; s++) {
                mbar_spin(lb + (it ? B_OE + 8 * s : s < 2 ? B_AE + 8 + 8 * s : B_FG), it ? (it - 1) & 1 : s < 2);
                const uint32_t fb = lb + B_OF + 8 * s;
                mbar_expect_tx(fb, 32768);
                #pragma unroll
                for (int b = 0; b < 2; b++)
                    tma_load5(o_b(s) + b * 8192, &mp.wo[it >> 1], cb * 128 + b * 64, (it & 1) * 8 + s * 2, fb);
                if (s == 0 && !(it & 1)) {
                    TL(256, L * 32 + 28);
                    ctr_wait(g_x.o[L][blk][it >> 1], 15);
                    fence_async_global();
                    TL(256, L * 32 + 10);
                }
                tma_load(o_a(s), &mp.o, it * 256 + s * 64, blk * 128, fb);
            }
            if (it == RESIT) {
                mbar_spin(lb + B_AE + 24, 1);
                mbar_expect_tx(lb + B_RES, 32768);
                tma_load_s(XT0, tx, cb * 128, blk * 128, lb + B_RES, pol);
                tma_load_s(XT1, tx, cb * 128 + 64, blk * 128, lb + B_RES, pol);
            }
        }
        if (c < NFC) {
            #pragma unroll 1
            for (int i = 0; i < 4; i++) {
                mbar_spin(lb + B_OE + 8 * (i >> 1), 1);
                tma_load3_s(f_wd(i), &mp.d, 0, c * 32, i * 4, lb + B_WD, pol);
            }
        }
    }
}

__global__ void __launch_bounds__(384, 1) k_all(const __grid_constant__ Maps mp, const bf16* __restrict__ x0, const bf16* __restrict__ wo, const bf16* __restrict__ w_down,
                                                const bf16* __restrict__ w_r, bf16* __restrict__ out, const uint64_t dk0, const uint64_t dv0, const uint32_t ca, const uint32_t zero, const uint32_t sixteen) {
    extern __shared__ __align__(1024) char smem[];
    if (smem_u32(smem) != SB) __trap();
    const int warp = warp_uniform(threadIdx.x >> 5), wg = warp >> 2;
    TL(0, 0);
    if (warp == 8) {
      if (elect_one()) {
        tm_prefetch(&mp.x[0]); tm_prefetch(&mp.wqkv);
        #pragma unroll
        for (int s = 0; s < 3; s++) { mbar_init(M_BAR + B_QF + 8 * s, 1); mbar_init(M_BAR + BAR_SET + B_QF + 8 * s, 1); }
        fence_mbar_init();
        #pragma unroll 1
        for (int s = 0; s < 3; s++) {
            const uint32_t sa = SB + s * Q_STB, fb = M_BAR + B_QF + 8 * s;
            mbar_expect_tx(fb, Q_STB);
            qkv_load_x(&mp.x[0], sa, s, fb);
            qkv_load_w(mp, sa + Q_ABYTES, s, fb);
        }
      }
      __syncwarp();
    } else if (warp > 8) {
        if (elect_one()) {
            const uint32_t o0 = warp == 9 ? B_AF : warp == 10 ? B_QE : B_AE, o1 = warp == 9 ? B_QE : warp == 10 ? B_AE : B_END, cnt = warp == 9 ? 1 : warp == 10 ? 2 : 8;
            #pragma unroll 1
            for (uint32_t o = o0; o < o1; o += 8) { const uint32_t n = o >= B_KS ? 4 : cnt; mbar_init(M_BAR + o, n); mbar_init(M_BAR + BAR_SET + o, n); }
            fence_mbar_init();
        }
        __syncwarp();
    } else if (wg < 2) {
        #pragma unroll
        for (int i = 0; i < 3; i++) g_u.fill[blockIdx.x][i][threadIdx.x] = make_uint4(EMPTY, EMPTY, EMPTY, EMPTY);
    }
    __syncthreads();
    if (wg == 2) {
        reg_dec<40>();
        if (warp > 8) side_role(mp, x0, wo, w_down, w_r, out);
        else if (elect_one()) producer_role(mp, x0);
    } else {
        reg_inc<232>();
        #pragma unroll 1
        for (int L = 0; L < 2; L++)
        {
            const uint32_t lb = M_BAR + L * BAR_SET;
            uint32_t qa[8], qb[8], sa[32], sb[32], wa[64];
            qkv_phase(L, lb, wg, qa, qb, sa, sb);
            attention_phase(L, lb, wg, qa, qb, sa, sb, dk0, dv0, ca, wa, zero, sixteen);
            tail_phase(L, lb, wg, wa, zero);
        }
    }
}

typedef CUresult (*EncodeFn)(CUtensorMap*, CUtensorMapDataType, cuuint32_t, void*, const cuuint64_t*, const cuuint64_t*, const cuuint32_t*,
                             const cuuint32_t*, CUtensorMapInterleave, CUtensorMapSwizzle, CUtensorMapL2promotion, CUtensorMapFloatOOBfill);

void make_map(EncodeFn enc, CUtensorMap* tm, const void* ptr, int rank, const cuuint64_t* dims, const cuuint64_t* strides, const cuuint32_t* box, CUtensorMapSwizzle sw) {
    const cuuint32_t es[5] = {1, 1, 1, 1, 1};
    enc(tm, CU_TENSOR_MAP_DATA_TYPE_BFLOAT16, rank, const_cast<void*>(ptr), dims, strides, box, es, CU_TENSOR_MAP_INTERLEAVE_NONE, sw,
        box[0] == 64 ? CU_TENSOR_MAP_L2_PROMOTION_L2_128B : CU_TENSOR_MAP_L2_PROMOTION_NONE, CU_TENSOR_MAP_FLOAT_OOB_FILL_NONE);
}
void make_map2(EncodeFn enc, CUtensorMap* tm, const void* ptr, uint64_t cols, uint64_t rows, uint32_t bc, uint32_t br, CUtensorMapSwizzle sw) {
    const cuuint64_t dims[2] = {cols, rows}, strides[1] = {cols * 2};
    const cuuint32_t box[2] = {bc, br};
    make_map(enc, tm, ptr, 2, dims, strides, box, sw);
}

}

extern "C" void kernel_launch(void* const* d_in, const int* in_sizes, int n_in, void* d_out, int out_size) {
    const bf16* x0 = (const bf16*)d_in[0];
    const bf16* wqkv = (const bf16*)d_in[1];
    const bf16* wo = (const bf16*)d_in[2];
    const bf16* w_r = (const bf16*)d_in[4];
    const bf16* w_gate = (const bf16*)d_in[5];
    const bf16* w_up = (const bf16*)d_in[6];
    const bf16* w_down = (const bf16*)d_in[7];

    EncodeFn enc = nullptr;
    cudaDriverEntryPointQueryResult qr;
    cudaGetDriverEntryPoint("cuTensorMapEncodeTiled", (void**)&enc, cudaEnableDefault, &qr);
    void *p_o, *p_x1;
    cudaGetSymbolAddress(&p_o, g_o); cudaGetSymbolAddress(&p_x1, g_x1);
    const CUtensorMapSwizzle S128 = CU_TENSOR_MAP_SWIZZLE_128B, S64 = CU_TENSOR_MAP_SWIZZLE_64B, S0 = CU_TENSOR_MAP_SWIZZLE_NONE;
    Maps mp;
    make_map2(enc, &mp.x[0], x0, D_, S_, 64, 128, S128); make_map2(enc, &mp.x[1], p_x1, D_, S_, 64, 128, S128);
    make_map2(enc, &mp.x[2], d_out, D_, S_, 64, 128, S128);
    make_map2(enc, &mp.o, p_o, D_, S_, 64, 128, S128);
    {
        const cuuint64_t dims[3] = {D_, D_, 3}, strides[2] = {3 * D_ * 2, D_ * 2};
        const cuuint32_t box[3] = {64, 64, 3};
        make_map(enc, &mp.wqkv, wqkv, 3, dims, strides, box, S128);
    }
    make_map2(enc, &mp.r, wqkv, 3 * D_, D_, 24, 256, S0);
    make_map2(enc, &mp.g, w_gate, FF, D_, 32, 256, S64); make_map2(enc, &mp.u, w_up, FF, D_, 32, 256, S64);
    for (int p = 0; p < 2; p++) {
        const cuuint64_t dims[5] = {D_, 2, 4, 4, 16}, strides[4] = {D_ * 2, 8 * D_ * 2, 2 * D_ * 2, 64 * D_ * 2};
        const cuuint32_t box[5] = {64, 2, 4, 4, 2};
        make_map(enc, &mp.wo[p], wo + (size_t)p * 32 * D_, 5, dims, strides, box, S128);
    }
    {
        const cuuint64_t dims[3] = {64, FF, 16}, strides[2] = {D_ * 2, 128};
        const cuuint32_t box[3] = {64, 32, 4};
        make_map(enc, &mp.d, w_down, 3, dims, strides, box, S128);
    }
    cudaFuncSetAttribute(k_all, cudaFuncAttributeMaxDynamicSharedMemorySize, K_SMEM);
    k_all<<<128, 384, K_SMEM, cudaStreamPerThread>>>(mp, x0, wo, w_down, w_r, (bf16*)d_out, desc_plain(A_RING, 2048, 128), desc_plain(A_RING + 8192, 128, 2048), 0x64A264A2u, 0u, 16u);
}
```

```cpp
#include <cuda_runtime.h>
#include <cuda_bf16.h>
#include <cuda_fp16.h>
#include <cuda.h>
#include <cudaTypedefs.h>
#include <stdint.h>

namespace {

typedef __nv_bfloat16 bf16;

constexpr int S_ = 2048, D_ = 1024, NH = 32, FF = 3584, NFC = FF / 32;
constexpr float LN_EPS = 1e-5f;
constexpr float QSCALE = 0.17677669529663687f * 1.4426950408889634f;
constexpr uint32_t EMPTY = 0xFFFFFFFFu;

constexpr int KV_TILE = 16384;
__device__ __align__(1024) char g_kv[NH * 16 * KV_TILE];
__device__ __align__(1024) bf16 g_o[S_ * D_];
__device__ __align__(1024) bf16 g_x1[S_ * D_];
__device__ __align__(16) float2 g_cs[8][3 * D_];
__device__ __align__(16) float2 g_rs0[S_];
__device__ uint4 g_qsave[128][24][256];
struct Xchg {
    uint4 part[2][16][8][128];
    float ypart[2][128][NFC][8];
    uint32_t cand[2][16][D_ / 2];
    uint4 hdr[2][128][16];
    float2 rs1[S_];
    float fix[3 * D_];
    uint32_t x2row[D_ / 2];
    uint8_t kv[2][NH][128];
    int o[2][16][2][32];
    uint8_t x[2][8][128];
};
constexpr int FILL = (sizeof(Xchg) / 128 + 127) / 128 * 8;
union XchgFill { Xchg x; uint4 fill[128][FILL]; };
static_assert(FILL > 768 && FILL <= 1024, "exchange area");
__device__ __align__(128) XchgFill g_u;
#define g_x g_u.x
__device__ int g_pctr;

constexpr uint32_t SMEM_BASE = 1024;

__device__ __forceinline__ int tid_now() { int v; asm volatile("mov.u32 %0, %%tid.x;" : "=r"(v)); return v; }
__device__ __forceinline__ int cta_now() { int v; asm volatile("mov.u32 %0, %%ctaid.x;" : "=r"(v)); return v; }
__device__ __forceinline__ uint64_t opaque(uint64_t v) { uint64_t r; asm volatile("mov.b64 %0, %1;" : "=l"(r) : "l"(v)); return r; }
__device__ __forceinline__ uint32_t base32(uint32_t v) { uint32_t r; asm("mov.b32 %0, %1;" : "=r"(r) : "r"(v)); return r; }
__device__ __forceinline__ uint32_t smem_u32(const void* p) { return (uint32_t)__cvta_generic_to_shared(p); }
__device__ __forceinline__ void mbar_init(uint32_t bar, int cnt) { asm volatile("mbarrier.init.shared::cta.b64 [%0], %1;" :: "r"(bar), "r"(cnt) : "memory"); }
__device__ __forceinline__ void mbar_expect_tx(uint32_t bar, uint32_t bytes) { asm volatile("mbarrier.arrive.expect_tx.shared::cta.b64 _, [%0], %1;" :: "r"(bar), "r"(bytes) : "memory"); }
__device__ __forceinline__ void mbar_arrive(uint32_t bar) { asm volatile("mbarrier.arrive.shared::cta.b64 _, [%0];" :: "r"(bar) : "memory"); }
__device__ __forceinline__ void mbar_sleep(uint32_t bar, uint32_t parity) {
    asm volatile("{\n.reg .pred p;\n.reg .u32 n;\nmov.u32 n, 0;\n"
                 "LAB_WAIT:\nmbarrier.try_wait.parity.shared::cta.b64 p, [%0], %1, 0x10000;\n@p bra LAB_DONE;\n"
                 "add.u32 n, n, 1;\nsetp.lt.u32 p, n, 0x10000;\n@p bra LAB_WAIT;\ntrap;\nLAB_DONE:\n}" :: "r"(bar), "r"(parity) : "memory");
}
__device__ __forceinline__ void mbar_nap(uint32_t bar, uint32_t parity) {
    asm volatile("{\n.reg .pred p;\nLAB_WAIT:\nmbarrier.try_wait.parity.shared::cta.b64 p, [%0], %1, 0x10000;\n@!p bra LAB_WAIT;\n}" :: "r"(bar), "r"(parity) : "memory");
}
__device__ __forceinline__ void mbar_spin(uint32_t bar, uint32_t parity) {
    asm volatile("{\n.reg .pred p;\nLAB_WAIT:\nmbarrier.try_wait.parity.shared::cta.b64 p, [%0], %1;\n@!p bra LAB_WAIT;\n}" :: "r"(bar), "r"(parity) : "memory");
}
__device__ __forceinline__ uint32_t mbar_test(uint32_t bar, uint32_t parity) {
    uint32_t ok;
    asm volatile("{\n.reg .pred p;\nmbarrier.test_wait.parity.shared::cta.b64 p, [%1], %2;\nselp.u32 %0, 1, 0, p;\n}" : "=r"(ok) : "r"(bar), "r"(parity) : "memory");
    return ok;
}
__device__ __forceinline__ void mbar_spin_unless(uint32_t ok, uint32_t bar, uint32_t parity) {
    asm volatile("{\n.reg .pred p;\nsetp.ne.u32 p, %2, 0;\n@p bra LAB_DONE;\nLAB_WAIT:\nmbarrier.try_wait.parity.shared::cta.b64 p, [%0], %1;\n@!p bra LAB_WAIT;\nLAB_DONE:\n}"
                 :: "r"(bar), "r"(parity), "r"(ok) : "memory");
}
__device__ __forceinline__ bool elect_one() {
    uint32_t r;
    asm volatile("{\n.reg .pred p;\nelect.sync _|p, 0xffffffff;\nselp.u32 %0, 1, 0, p;\n}" : "=r"(r));
    return r != 0;
}
__device__ __forceinline__ void mbar_arrive_elect(uint32_t bar) {
    asm volatile("{\n.reg .pred p;\nelect.sync _|p, 0xffffffff;\n@p mbarrier.arrive.shared::cta.b64 _, [%0];\n}" :: "r"(bar) : "memory");
}
__device__ __forceinline__ void mbar_arrive_elect_p(uint32_t bar, uint32_t on) {
    asm volatile("{\n.reg .pred p, q;\nelect.sync _|p, 0xffffffff;\nsetp.ne.and.u32 q, %1, 0, p;\n@q mbarrier.arrive.shared::cta.b64 _, [%0];\n}" :: "r"(bar), "r"(on) : "memory");
}
__device__ __forceinline__ int warp_uniform(int v) { return __shfl_sync(0xffffffffu, v, 0); }
__device__ __forceinline__ void fence_mbar_init() { asm volatile("fence.mbarrier_init.release.cluster;" ::: "memory"); }
__device__ __forceinline__ void fence_async_smem() { asm volatile("fence.proxy.async.shared::cta;" ::: "memory"); }
__device__ __forceinline__ void fence_async_global() { asm volatile("fence.proxy.async.global;" ::: "memory"); }
__device__ __forceinline__ void named_sync(int id, int n) { asm volatile("bar.sync %0, %1;" :: "r"(id), "r"(n) : "memory"); }
__device__ __forceinline__ void named_arrive(int id, int n) { asm volatile("bar.arrive %0, %1;" :: "r"(id), "r"(n) : "memory"); }
__device__ __forceinline__ void bulk_load(uint32_t dst, const void* src, uint32_t bytes, uint32_t bar) {
    asm volatile("cp.async.bulk.shared::cluster.global.mbarrier::complete_tx::bytes [%0], [%1], %2, [%3];" :: "r"(dst), "l"(src), "r"(bytes), "r"(bar) : "memory");
}
__device__ __forceinline__ void bulk_store(void* dst, uint32_t src, uint32_t bytes) {
    asm volatile("cp.async.bulk.global.shared::cta.bulk_group [%0], [%1], %2;" :: "l"(dst), "r"(src), "r"(bytes) : "memory");
}
__device__ __forceinline__ void bulk_commit() { asm volatile("cp.async.bulk.commit_group;" ::: "memory"); }
__device__ __forceinline__ void bulk_wait() { asm volatile("cp.async.bulk.wait_group 0;" ::: "memory"); }
__device__ __forceinline__ void l2_prefetch(const void* src, uint32_t bytes) {
    asm volatile("cp.async.bulk.prefetch.L2.global [%0], %1;" :: "l"(src), "r"(bytes) : "memory");
}
__device__ __forceinline__ void tma_load(uint32_t dst, const CUtensorMap* tm, int c0, int c1, uint32_t bar) {
    asm volatile("cp.async.bulk.tensor.2d.shared::cluster.global.mbarrier::complete_tx::bytes [%0], [%1, {%3, %4}], [%2];"
                 :: "r"(dst), "l"(tm), "r"(bar), "r"(c0), "r"(c1) : "memory");
}
__device__ __forceinline__ void tma_load3(uint32_t dst, const CUtensorMap* tm, int c0, int c1, int c2, uint32_t bar) {
    asm volatile("cp.async.bulk.tensor.3d.shared::cluster.global.mbarrier::complete_tx::bytes [%0], [%1, {%3, %4, %5}], [%2];"
                 :: "r"(dst), "l"(tm), "r"(bar), "r"(c0), "r"(c1), "r"(c2) : "memory");
}
__device__ __forceinline__ void tma_load5(uint32_t dst, const CUtensorMap* tm, int c0, int c4, uint32_t bar) {
    asm volatile("cp.async.bulk.tensor.5d.shared::cluster.global.mbarrier::complete_tx::bytes [%0], [%1, {%3, %5, %5, %5, %4}], [%2];"
                 :: "r"(dst), "l"(tm), "r"(bar), "r"(c0), "r"(c4), "r"(0) : "memory");
}
__device__ __forceinline__ uint64_t policy_evict_first() { uint64_t p; asm volatile("createpolicy.fractional.L2::evict_first.b64 %0, 1.0;" : "=l"(p)); return p; }
__device__ __forceinline__ void tma_load_s(uint32_t dst, const CUtensorMap* tm, int c0, int c1, uint32_t bar, uint64_t pol) {
    asm volatile("cp.async.bulk.tensor.2d.shared::cluster.global.mbarrier::complete_tx::bytes.L2::cache_hint [%0], [%1, {%3, %4}], [%2], %5;"
                 :: "r"(dst), "l"(tm), "r"(bar), "r"(c0), "r"(c1), "l"(pol) : "memory");
}
__device__ __forceinline__ void tma_load3_s(uint32_t dst, const CUtensorMap* tm, int c0, int c1, int c2, uint32_t bar, uint64_t pol) {
    asm volatile("cp.async.bulk.tensor.3d.shared::cluster.global.mbarrier::complete_tx::bytes.L2::cache_hint [%0], [%1, {%3, %4, %5}], [%2], %6;"
                 :: "r"(dst), "l"(tm), "r"(bar), "r"(c0), "r"(c1), "r"(c2), "l"(pol) : "memory");
}
__device__ __forceinline__ void tma_store(const CUtensorMap* tm, uint32_t src, int c0, int c1) {
    asm volatile("cp.async.bulk.tensor.2d.global.shared::cta.bulk_group [%0, {%2, %3}], [%1];" :: "l"(tm), "r"(src), "r"(c0), "r"(c1) : "memory");
}
__device__ __forceinline__ void tma_prefetch(const CUtensorMap* tm, int c0, int c1) {
    asm volatile("cp.async.bulk.prefetch.tensor.2d.L2.global [%0, {%1, %2}];" :: "l"(tm), "r"(c0), "r"(c1) : "memory");
}
__device__ __forceinline__ void tm_prefetch(const CUtensorMap* tm) { asm volatile("prefetch.tensormap [%0];" :: "l"(tm) : "memory"); }
__device__ __forceinline__ void wg_fence() { asm volatile("wgmma.fence.sync.aligned;" ::: "memory"); }
__device__ __forceinline__ void wg_commit() { asm volatile("wgmma.commit_group.sync.aligned;" ::: "memory"); }
template <int N> __device__ __forceinline__ void wg_wait() { asm volatile("wgmma.wait_group.sync.aligned %0;" :: "n"(N) : "memory"); }
template <int N> __device__ __forceinline__ void pin(uint32_t (&r)[N]) {
    #pragma unroll
    for (int i = 0; i < N; i++) asm volatile("" : "+r"(r[i]) :: "memory");
}
template <int N> __device__ __forceinline__ void pin(float (&r)[N]) {
    #pragma unroll
    for (int i = 0; i < N; i++) asm volatile("" : "+f"(r[i]) :: "memory");
}
template <int N> __device__ __forceinline__ void reg_inc() { asm volatile("setmaxnreg.inc.sync.aligned.u32 %0;" :: "n"(N)); }
template <int N> __device__ __forceinline__ void reg_dec() { asm volatile("setmaxnreg.dec.sync.aligned.u32 %0;" :: "n"(N)); }
__host__ __device__ constexpr uint64_t desc_plain(uint32_t addr, uint32_t lbo, uint32_t sbo) {
    return (uint64_t)((addr & 0x3FFFF) >> 4) | ((uint64_t)(lbo >> 4) << 16) | ((uint64_t)(sbo >> 4) << 32);
}
__host__ __device__ constexpr uint64_t desc_sw128(uint32_t addr, uint32_t lbo, uint32_t sbo) { return desc_plain(addr, lbo, sbo) | (1ull << 62); }
__host__ __device__ constexpr uint64_t desc_sw64(uint32_t addr, uint32_t lbo, uint32_t sbo) { return desc_plain(addr, lbo, sbo) | (2ull << 62); }

__device__ __forceinline__ uint32_t lds32(uint32_t a) { uint32_t v; asm volatile("ld.shared.b32 %0, [%1];" : "=r"(v) : "r"(a) : "memory"); return v; }
__device__ __forceinline__ uint32_t lds16(uint32_t a) { uint32_t v; asm volatile("ld.shared.u16 %0, [%1];" : "=r"(v) : "r"(a) : "memory"); return v; }
__device__ __forceinline__ float ldsf(uint32_t a) { return __uint_as_float(lds32(a)); }
__device__ __forceinline__ float2 lds64f(uint32_t a) { float2 v; asm volatile("ld.shared.v2.f32 {%0, %1}, [%2];" : "=f"(v.x), "=f"(v.y) : "r"(a) : "memory"); return v; }
__device__ __forceinline__ uint4 lds128(uint32_t a) { uint4 v; asm volatile("ld.shared.v4.b32 {%0, %1, %2, %3}, [%4];" : "=r"(v.x), "=r"(v.y), "=r"(v.z), "=r"(v.w) : "r"(a) : "memory"); return v; }
__device__ __forceinline__ void sts16(uint32_t a, uint32_t v) { asm volatile("st.shared.b16 [%0], %1;" :: "r"(a), "h"((uint16_t)v) : "memory"); }
__device__ __forceinline__ void sts32(uint32_t a, uint32_t v) { asm volatile("st.shared.b32 [%0], %1;" :: "r"(a), "r"(v) : "memory"); }
__device__ __forceinline__ void stsf(uint32_t a, float v) { sts32(a, __float_as_uint(v)); }
__device__ __forceinline__ void sts64(uint32_t a, uint32_t x, uint32_t y) { asm volatile("st.shared.v2.b32 [%0], {%1, %2};" :: "r"(a), "r"(x), "r"(y) : "memory"); }
__device__ __forceinline__ void sts128(uint32_t a, uint32_t x, uint32_t y, uint32_t z, uint32_t w) { asm volatile("st.shared.v4.b32 [%0], {%1, %2, %3, %4};" :: "r"(a), "r"(x), "r"(y), "r"(z), "r"(w) : "memory"); }
__device__ __forceinline__ void stsm4(uint32_t a, uint32_t x, uint32_t y, uint32_t z, uint32_t w) {
    asm volatile("stmatrix.sync.aligned.m8n8.x4.shared.b16 [%0], {%1, %2, %3, %4};" :: "r"(a), "r"(x), "r"(y), "r"(z), "r"(w) : "memory");
}
__device__ __forceinline__ void ldsm4(uint32_t& a0, uint32_t& a1, uint32_t& a2, uint32_t& a3, uint32_t addr) {
    asm volatile("ldmatrix.sync.aligned.m8n8.x4.shared.b16 {%0,%1,%2,%3}, [%4];" : "=r"(a0), "=r"(a1), "=r"(a2), "=r"(a3) : "r"(addr) : "memory");
}
__device__ __forceinline__ void ldsm4t(uint32_t& a0, uint32_t& a1, uint32_t& a2, uint32_t& a3, uint32_t addr) {
    asm volatile("ldmatrix.sync.aligned.m8n8.x4.trans.shared.b16 {%0,%1,%2,%3}, [%4];" : "=r"(a0), "=r"(a1), "=r"(a2), "=r"(a3) : "r"(addr) : "memory");
}
__device__ __forceinline__ void mma_bf16(float (&d)[4], uint32_t a0, uint32_t a1, uint32_t a2, uint32_t a3, uint32_t b0, uint32_t b1) {
    asm("mma.sync.aligned.m16n8k16.row.col.f32.bf16.bf16.f32 {%0,%1,%2,%3}, {%4,%5,%6,%7}, {%8,%9}, {%0,%1,%2,%3};"
        : "+f"(d[0]), "+f"(d[1]), "+f"(d[2]), "+f"(d[3]) : "r"(a0), "r"(a1), "r"(a2), "r"(a3), "r"(b0), "r"(b1));
}
__device__ __forceinline__ void mma_bf16_k8(float (&d)[4], uint32_t a0, uint32_t a1, uint32_t b0) {
    asm("mma.sync.aligned.m16n8k8.row.col.f32.bf16.bf16.f32 {%0,%1,%2,%3}, {%4,%5}, {%6}, {%0,%1,%2,%3};"
        : "+f"(d[0]), "+f"(d[1]), "+f"(d[2]), "+f"(d[3]) : "r"(a0), "r"(a1), "r"(b0));
}
__device__ __forceinline__ void mma_f16(float (&d)[4], uint32_t a0, uint32_t a1, uint32_t a2, uint32_t a3, uint32_t b0, uint32_t b1) {
    asm("mma.sync.aligned.m16n8k16.row.col.f32.f16.f16.f32 {%0,%1,%2,%3}, {%4,%5,%6,%7}, {%8,%9}, {%0,%1,%2,%3};"
        : "+f"(d[0]), "+f"(d[1]), "+f"(d[2]), "+f"(d[3]) : "r"(a0), "r"(a1), "r"(a2), "r"(a3), "r"(b0), "r"(b1));
}
__device__ __forceinline__ void stg128_pred(void* p, const uint4& v, bool on) {
    asm volatile("{\n.reg .pred q;\nsetp.ne.u32 q, %5, 0;\n@q st.global.v4.b32 [%0], {%1, %2, %3, %4};\n}"
                 :: "l"(p), "r"(v.x), "r"(v.y), "r"(v.z), "r"(v.w), "r"((uint32_t)on) : "memory");
}
__device__ __forceinline__ void st_x32(void* p, uint32_t v) { asm volatile("st.relaxed.gpu.global.u32 [%0], %1;" :: "l"(p), "r"(v) : "memory"); }
__device__ __forceinline__ void st_x64(void* p, uint32_t x, uint32_t y) {
    asm volatile("{\n.reg .b64 v;\nmov.b64 v, {%1, %2};\nst.relaxed.gpu.global.b64 [%0], v;\n}" :: "l"(p), "r"(x), "r"(y) : "memory");
}
__device__ __forceinline__ void st_x128(void* p, uint32_t x, uint32_t y, uint32_t z, uint32_t w) {
    asm volatile("{\n.reg .b64 a, b;\n.reg .b128 v;\nmov.b64 a, {%1, %2};\nmov.b64 b, {%3, %4};\nmov.b128 v, {a, b};\nst.relaxed.gpu.global.b128 [%0], v;\n}"
                 :: "l"(p), "r"(x), "r"(y), "r"(z), "r"(w) : "memory");
}
__device__ __forceinline__ uint32_t ld_x32(const void* p) { uint32_t v; asm volatile("ld.relaxed.gpu.global.u32 %0, [%1];" : "=r"(v) : "l"(p) : "memory"); return v; }
__device__ __forceinline__ uint2 ld_x64(const void* p) {
    uint2 v; asm volatile("{\n.reg .b64 a;\nld.relaxed.gpu.global.b64 a, [%2];\nmov.b64 {%0, %1}, a;\n}" : "=r"(v.x), "=r"(v.y) : "l"(p) : "memory"); return v;
}
__device__ __forceinline__ uint4 ld_x128(const void* p) {
    uint4 v;
    asm volatile("{\n.reg .b64 a, b;\n.reg .b128 v;\nld.relaxed.gpu.global.b128 v, [%4];\nmov.b128 {a, b}, v;\nmov.b64 {%0, %1}, a;\nmov.b64 {%2, %3}, b;\n}"
                 : "=r"(v.x), "=r"(v.y), "=r"(v.z), "=r"(v.w) : "l"(p) : "memory");
    return v;
}
__device__ __forceinline__ void poll_tick(uint32_t& n) { asm volatile("{\n.reg .pred p;\nadd.u32 %0, %0, 1;\nsetp.ge.u32 p, %0, 0x800000;\n@p st.global.u32 [%1], %0;\n}" : "+r"(n) : "l"(0ull)); }
__device__ __forceinline__ void ctr_arrive(int* c) { asm volatile("red.release.gpu.global.add.s32 [%0], 1;" :: "l"(c) : "memory"); }
__device__ __forceinline__ void ctr_wait(const int* c, int target) {
    int v;
    uint32_t n = 0;
    #pragma unroll 1
    do {
        asm volatile("ld.acquire.gpu.global.s32 %0, [%1];" : "=r"(v) : "l"(c) : "memory");
        poll_tick(n);
    } while (v < target);
}
__device__ __forceinline__ void flag_wait(const uint8_t* f) {
    uint32_t n = 0, v;
    #pragma unroll 1
    do { asm volatile("ld.acquire.gpu.global.u8 %0, [%1];" : "=r"(v) : "l"(f) : "memory"); poll_tick(n); } while (v);
}
__device__ __forceinline__ void flags16_wait(const uint8_t* f) {
    uint32_t n = 0;
    uint64_t v;
    #pragma unroll 1
    do {
        asm volatile("{\n.reg .b64 a, b;\n.reg .b128 v;\nld.acquire.gpu.global.b128 v, [%1];\nmov.b128 {a, b}, v;\nor.b64 %0, a, b;\n}" : "=l"(v) : "l"(f) : "memory");
        poll_tick(n);
    } while (v != 0);
}
__device__ __forceinline__ bool any_empty(const uint4& v) { return v.x == EMPTY || v.y == EMPTY || v.z == EMPTY || v.w == EMPTY; }
__device__ __forceinline__ bool warp_any(bool p) { return __any_sync(0xffffffffu, p); }

__device__ __forceinline__ float ex2(float x) { float y; asm("ex2.approx.ftz.f32 %0, %1;" : "=f"(y) : "f"(x)); return y; }
__device__ __forceinline__ float rsq(float x) { float y; asm("rsqrt.approx.ftz.f32 %0, %1;" : "=f"(y) : "f"(x)); return y; }
__device__ __forceinline__ float rcp(float x) { float y; asm("rcp.approx.ftz.f32 %0, %1;" : "=f"(y) : "f"(x)); return y; }
__device__ __forceinline__ uint32_t pack_bf16(float lo, float hi) { uint32_t r; asm("cvt.rn.bf16x2.f32 %0, %1, %2;" : "=r"(r) : "f"(hi), "f"(lo)); return r; }
__device__ __forceinline__ uint32_t pack_f16(float lo, float hi) { uint32_t r; asm("cvt.rn.f16x2.f32 %0, %1, %2;" : "=r"(r) : "f"(hi), "f"(lo)); return r; }
__device__ __forceinline__ float bf_lo(uint32_t v) { return __uint_as_float(v << 16); }
__device__ __forceinline__ float bf_hi(uint32_t v) { return __uint_as_float(v & 0xFFFF0000u); }
__device__ __forceinline__ float bf_round(float x) { return __uint_as_float(pack_bf16(0.f, x)); }
__device__ __forceinline__ void h2_unpack(uint32_t v, float& lo, float& hi) {
    asm("{.reg .f16 l, h; mov.b32 {l, h}, %2; cvt.f32.f16 %0, l; cvt.f32.f16 %1, h;}" : "=f"(lo), "=f"(hi) : "r"(v));
}
__device__ __forceinline__ uint32_t hadd2(uint32_t a, uint32_t b) { uint32_t r; asm("add.rn.f16x2 %0, %1, %2;" : "=r"(r) : "r"(a), "r"(b)); return r; }
__device__ __forceinline__ uint32_t hmax2(uint32_t a, uint32_t b) { uint32_t r; asm("max.f16x2 %0, %1, %2;" : "=r"(r) : "r"(a), "r"(b)); return r; }
__device__ __forceinline__ uint32_t badd2(uint32_t a, uint32_t b) { uint32_t r; asm("add.rn.bf16x2 %0, %1, %2;" : "=r"(r) : "r"(a), "r"(b)); return r; }
__device__ __forceinline__ uint32_t bmul2(uint32_t a, uint32_t b) { uint32_t r; asm("mul.rn.bf16x2 %0, %1, %2;" : "=r"(r) : "r"(a), "r"(b)); return r; }
__device__ __forceinline__ float warp_sum(float v) {
    #pragma unroll
    for (int o = 16; o > 0; o >>= 1) v += __shfl_xor_sync(0xffffffffu, v, o);
    return v;
}
__device__ __forceinline__ float quad_sum(float v) { v += __shfl_xor_sync(0xffffffffu, v, 1); return v + __shfl_xor_sync(0xffffffffu, v, 2); }
__device__ __forceinline__ float quad_max(float v) { v = fmaxf(v, __shfl_xor_sync(0xffffffffu, v, 1)); return fmaxf(v, __shfl_xor_sync(0xffffffffu, v, 2)); }
__device__ __forceinline__ uint32_t redux_max(uint32_t v) { uint32_t r; asm volatile("redux.sync.max.u32 %0, %1, 0xffffffff;" : "=r"(r) : "r"(v)); return r; }
__device__ __forceinline__ uint32_t redux_min(uint32_t v) { uint32_t r; asm volatile("redux.sync.min.u32 %0, %1, 0xffffffff;" : "=r"(r) : "r"(v)); return r; }
__device__ __forceinline__ uint32_t order_bits(float r) { const uint32_t u = __float_as_uint(r); return (u & 0x80000000u) ? ~u : (u | 0x80000000u); }
struct Ln2 { uint32_t nm, rh, rl, c; };
__device__ __forceinline__ Ln2 ln2_coef(float mean, float rstd) {
    const uint32_t a = pack_bf16(-mean, rstd), b = pack_bf16((-mean - bf_lo(a)) * rstd, rstd - bf_hi(a));
    return {__byte_perm(a, 0, 0x1010), __byte_perm(a, 0, 0x3232), __byte_perm(b, 0, 0x3232), __byte_perm(b, 0, 0x1010)};
}
__device__ __forceinline__ uint32_t bfma2(uint32_t a, uint32_t b, uint32_t c) { uint32_t r; asm("fma.rn.bf16x2 %0, %1, %2, %3;" : "=r"(r) : "r"(a), "r"(b), "r"(c)); return r; }
__device__ __forceinline__ uint32_t ln2(uint32_t v, const Ln2& k) { const uint32_t d = badd2(v, k.nm); return bfma2(d, k.rh, bfma2(d, k.rl, k.c)); }
__device__ __forceinline__ uint32_t add_ln2(uint32_t v, const Ln2& k) { return badd2(v, ln2(v, k)); }

#define TL(TID, i)
#define CK(TID, i)

__device__ __forceinline__ void wg_gemm_n128(float (&d)[64], uint64_t desca, uint64_t desc) {
    asm volatile("{\n.reg .pred p;\nsetp.ne.b32 p, 1, 0;\n"
        "wgmma.mma_async.sync.aligned.m64n128k16.f32.bf16.bf16 "
        "{%0,%1,%2,%3,%4,%5,%6,%7,%8,%9,%10,%11,%12,%13,%14,%15,%16,%17,%18,%19,%20,%21,%22,%23,%24,%25,%26,%27,%28,%29,%30,%31,%32,%33,%34,%35,%36,%37,%38,%39,%40,%41,%42,%43,%44,%45,%46,%47,%48,%49,%50,%51,%52,%53,%54,%55,%56,%57,%58,%59,%60,%61,%62,%63}, "
        "%64, %65, p, 1, 1, 0, 1;\n}\n"
        : "+f"(d[0]), "+f"(d[1]), "+f"(d[2]), "+f"(d[3]), "+f"(d[4]), "+f"(d[5]), "+f"(d[6]), "+f"(d[7]), "+f"(d[8]), "+f"(d[9]), "+f"(d[10]), "+f"(d[11]),
          "+f"(d[12]), "+f"(d[13]), "+f"(d[14]), "+f"(d[15]), "+f"(d[16]), "+f"(d[17]), "+f"(d[18]), "+f"(d[19]), "+f"(d[20]), "+f"(d[21]), "+f"(d[22]), "+f"(d[23]),
          "+f"(d[24]), "+f"(d[25]), "+f"(d[26]), "+f"(d[27]), "+f"(d[28]), "+f"(d[29]), "+f"(d[30]), "+f"(d[31]), "+f"(d[32]), "+f"(d[33]), "+f"(d[34]), "+f"(d[35]),
          "+f"(d[36]), "+f"(d[37]), "+f"(d[38]), "+f"(d[39]), "+f"(d[40]), "+f"(d[41]), "+f"(d[42]), "+f"(d[43]), "+f"(d[44]), "+f"(d[45]), "+f"(d[46]), "+f"(d[47]),
          "+f"(d[48]), "+f"(d[49]), "+f"(d[50]), "+f"(d[51]), "+f"(d[52]), "+f"(d[53]), "+f"(d[54]), "+f"(d[55]), "+f"(d[56]), "+f"(d[57]), "+f"(d[58]), "+f"(d[59]),
          "+f"(d[60]), "+f"(d[61]), "+f"(d[62]), "+f"(d[63])
        : "l"(desca), "l"(desc));
}
__device__ __forceinline__ void wg_gemm_n192(float (&d)[96], uint64_t desca, uint64_t desc) {
    asm volatile("{\n.reg .pred p;\nsetp.ne.b32 p, 1, 0;\n"
        "wgmma.mma_async.sync.aligned.m64n192k16.f32.bf16.bf16 "
        "{%0,%1,%2,%3,%4,%5,%6,%7,%8,%9,%10,%11,%12,%13,%14,%15,%16,%17,%18,%19,%20,%21,%22,%23,%24,%25,%26,%27,%28,%29,%30,%31,%32,%33,%34,%35,%36,%37,%38,%39,%40,%41,%42,%43,%44,%45,%46,%47,%48,%49,%50,%51,%52,%53,%54,%55,%56,%57,%58,%59,%60,%61,%62,%63,%64,%65,%66,%67,%68,%69,%70,%71,%72,%73,%74,%75,%76,%77,%78,%79,%80,%81,%82,%83,%84,%85,%86,%87,%88,%89,%90,%91,%92,%93,%94,%95}, "
        "%96, %97, p, 1, 1, 0, 1;\n}\n"
        : "+f"(d[0]), "+f"(d[1]), "+f"(d[2]), "+f"(d[3]), "+f"(d[4]), "+f"(d[5]), "+f"(d[6]), "+f"(d[7]), "+f"(d[8]), "+f"(d[9]), "+f"(d[10]), "+f"(d[11]),
          "+f"(d[12]), "+f"(d[13]), "+f"(d[14]), "+f"(d[15]), "+f"(d[16]), "+f"(d[17]), "+f"(d[18]), "+f"(d[19]), "+f"(d[20]), "+f"(d[21]), "+f"(d[22]), "+f"(d[23]),
          "+f"(d[24]), "+f"(d[25]), "+f"(d[26]), "+f"(d[27]), "+f"(d[28]), "+f"(d[29]), "+f"(d[30]), "+f"(d[31]), "+f"(d[32]), "+f"(d[33]), "+f"(d[34]), "+f"(d[35]),
          "+f"(d[36]), "+f"(d[37]), "+f"(d[38]), "+f"(d[39]), "+f"(d[40]), "+f"(d[41]), "+f"(d[42]), "+f"(d[43]), "+f"(d[44]), "+f"(d[45]), "+f"(d[46]), "+f"(d[47]),
          "+f"(d[48]), "+f"(d[49]), "+f"(d[50]), "+f"(d[51]), "+f"(d[52]), "+f"(d[53]), "+f"(d[54]), "+f"(d[55]), "+f"(d[56]), "+f"(d[57]), "+f"(d[58]), "+f"(d[59]),
          "+f"(d[60]), "+f"(d[61]), "+f"(d[62]), "+f"(d[63]), "+f"(d[64]), "+f"(d[65]), "+f"(d[66]), "+f"(d[67]), "+f"(d[68]), "+f"(d[69]), "+f"(d[70]), "+f"(d[71]),
          "+f"(d[72]), "+f"(d[73]), "+f"(d[74]), "+f"(d[75]), "+f"(d[76]), "+f"(d[77]), "+f"(d[78]), "+f"(d[79]), "+f"(d[80]), "+f"(d[81]), "+f"(d[82]), "+f"(d[83]),
          "+f"(d[84]), "+f"(d[85]), "+f"(d[86]), "+f"(d[87]), "+f"(d[88]), "+f"(d[89]), "+f"(d[90]), "+f"(d[91]), "+f"(d[92]), "+f"(d[93]), "+f"(d[94]), "+f"(d[95])
        : "l"(desca), "l"(desc));
}
__device__ __forceinline__ void wg_gemm_n192_init(float (&d)[96], uint64_t desca, uint64_t desc) {
    asm volatile("{\n.reg .pred p;\nsetp.ne.b32 p, 0, 0;\n"
        "wgmma.mma_async.sync.aligned.m64n192k16.f32.bf16.bf16 "
        "{%0,%1,%2,%3,%4,%5,%6,%7,%8,%9,%10,%11,%12,%13,%14,%15,%16,%17,%18,%19,%20,%21,%22,%23,%24,%25,%26,%27,%28,%29,%30,%31,%32,%33,%34,%35,%36,%37,%38,%39,%40,%41,%42,%43,%44,%45,%46,%47,%48,%49,%50,%51,%52,%53,%54,%55,%56,%57,%58,%59,%60,%61,%62,%63,%64,%65,%66,%67,%68,%69,%70,%71,%72,%73,%74,%75,%76,%77,%78,%79,%80,%81,%82,%83,%84,%85,%86,%87,%88,%89,%90,%91,%92,%93,%94,%95}, "
        "%96, %97, p, 1, 1, 0, 1;\n}\n"
        : "=f"(d[0]), "=f"(d[1]), "=f"(d[2]), "=f"(d[3]), "=f"(d[4]), "=f"(d[5]), "=f"(d[6]), "=f"(d[7]), "=f"(d[8]), "=f"(d[9]), "=f"(d[10]), "=f"(d[11]),
          "=f"(d[12]), "=f"(d[13]), "=f"(d[14]), "=f"(d[15]), "=f"(d[16]), "=f"(d[17]), "=f"(d[18]), "=f"(d[19]), "=f"(d[20]), "=f"(d[21]), "=f"(d[22]), "=f"(d[23]),
          "=f"(d[24]), "=f"(d[25]), "=f"(d[26]), "=f"(d[27]), "=f"(d[28]), "=f"(d[29]), "=f"(d[30]), "=f"(d[31]), "=f"(d[32]), "=f"(d[33]), "=f"(d[34]), "=f"(d[35]),
          "=f"(d[36]), "=f"(d[37]), "=f"(d[38]), "=f"(d[39]), "=f"(d[40]), "=f"(d[41]), "=f"(d[42]), "=f"(d[43]), "=f"(d[44]), "=f"(d[45]), "=f"(d[46]), "=f"(d[47]),
          "=f"(d[48]), "=f"(d[49]), "=f"(d[50]), "=f"(d[51]), "=f"(d[52]), "=f"(d[53]), "=f"(d[54]), "=f"(d[55]), "=f"(d[56]), "=f"(d[57]), "=f"(d[58]), "=f"(d[59]),
          "=f"(d[60]), "=f"(d[61]), "=f"(d[62]), "=f"(d[63]), "=f"(d[64]), "=f"(d[65]), "=f"(d[66]), "=f"(d[67]), "=f"(d[68]), "=f"(d[69]), "=f"(d[70]), "=f"(d[71]),
          "=f"(d[72]), "=f"(d[73]), "=f"(d[74]), "=f"(d[75]), "=f"(d[76]), "=f"(d[77]), "=f"(d[78]), "=f"(d[79]), "=f"(d[80]), "=f"(d[81]), "=f"(d[82]), "=f"(d[83]),
          "=f"(d[84]), "=f"(d[85]), "=f"(d[86]), "=f"(d[87]), "=f"(d[88]), "=f"(d[89]), "=f"(d[90]), "=f"(d[91]), "=f"(d[92]), "=f"(d[93]), "=f"(d[94]), "=f"(d[95])
        : "l"(desca), "l"(desc));
}
__device__ __forceinline__ void wg_qk_init(uint32_t (&d)[32], uint32_t a0, uint32_t a1, uint32_t a2, uint32_t a3, uint64_t desc) {
    asm volatile("{\n.reg .pred p;\nsetp.ne.b32 p, 0, 0;\n"
        "wgmma.mma_async.sync.aligned.m64n128k16.f16.f16.f16 "
        "{%0,%1,%2,%3,%4,%5,%6,%7,%8,%9,%10,%11,%12,%13,%14,%15,%16,%17,%18,%19,%20,%21,%22,%23,%24,%25,%26,%27,%28,%29,%30,%31}, "
        "{%32,%33,%34,%35}, %36, p, 1, 1, 0;\n}\n"
        : "=r"(d[0]), "=r"(d[1]), "=r"(d[2]), "=r"(d[3]), "=r"(d[4]), "=r"(d[5]), "=r"(d[6]), "=r"(d[7]), "=r"(d[8]), "=r"(d[9]), "=r"(d[10]), "=r"(d[11]),
          "=r"(d[12]), "=r"(d[13]), "=r"(d[14]), "=r"(d[15]), "=r"(d[16]), "=r"(d[17]), "=r"(d[18]), "=r"(d[19]), "=r"(d[20]), "=r"(d[21]), "=r"(d[22]), "=r"(d[23]),
          "=r"(d[24]), "=r"(d[25]), "=r"(d[26]), "=r"(d[27]), "=r"(d[28]), "=r"(d[29]), "=r"(d[30]), "=r"(d[31])
        : "r"(a0), "r"(a1), "r"(a2), "r"(a3), "l"(desc));
}
__device__ __forceinline__ void wg_qk_acc(uint32_t (&d)[32], uint32_t a0, uint32_t a1, uint32_t a2, uint32_t a3, uint64_t desc) {
    asm volatile("{\n.reg .pred p;\nsetp.ne.b32 p, 1, 0;\n"
        "wgmma.mma_async.sync.aligned.m64n128k16.f16.f16.f16 "
        "{%0,%1,%2,%3,%4,%5,%6,%7,%8,%9,%10,%11,%12,%13,%14,%15,%16,%17,%18,%19,%20,%21,%22,%23,%24,%25,%26,%27,%28,%29,%30,%31}, "
        "{%32,%33,%34,%35}, %36, p, 1, 1, 0;\n}\n"
        : "+r"(d[0]), "+r"(d[1]), "+r"(d[2]), "+r"(d[3]), "+r"(d[4]), "+r"(d[5]), "+r"(d[6]), "+r"(d[7]), "+r"(d[8]), "+r"(d[9]), "+r"(d[10]), "+r"(d[11]),
          "+r"(d[12]), "+r"(d[13]), "+r"(d[14]), "+r"(d[15]), "+r"(d[16]), "+r"(d[17]), "+r"(d[18]), "+r"(d[19]), "+r"(d[20]), "+r"(d[21]), "+r"(d[22]), "+r"(d[23]),
          "+r"(d[24]), "+r"(d[25]), "+r"(d[26]), "+r"(d[27]), "+r"(d[28]), "+r"(d[29]), "+r"(d[30]), "+r"(d[31])
        : "r"(a0), "r"(a1), "r"(a2), "r"(a3), "l"(desc));
}
__device__ __forceinline__ void wg_pv_init(uint32_t (&d)[10], uint32_t a0, uint32_t a1, uint32_t a2, uint32_t a3, uint64_t desc) {
    asm volatile("{\n.reg .pred p;\nsetp.ne.b32 p, 0, 0;\n"
        "wgmma.mma_async.sync.aligned.m64n40k16.f16.f16.f16 "
        "{%0,%1,%2,%3,%4,%5,%6,%7,%8,%9}, "
        "{%10,%11,%12,%13}, %14, p, 1, 1, 1;\n}\n"
        : "=r"(d[0]), "=r"(d[1]), "=r"(d[2]), "=r"(d[3]), "=r"(d[4]), "=r"(d[5]), "=r"(d[6]), "=r"(d[7]), "=r"(d[8]), "=r"(d[9])
        : "r"(a0), "r"(a1), "r"(a2), "r"(a3), "l"(desc));
}
__device__ __forceinline__ void wg_pv_acc(uint32_t (&d)[10], uint32_t a0, uint32_t a1, uint32_t a2, uint32_t a3, uint64_t desc) {
    asm volatile("{\n.reg .pred p;\nsetp.ne.b32 p, 1, 0;\n"
        "wgmma.mma_async.sync.aligned.m64n40k16.f16.f16.f16 "
        "{%0,%1,%2,%3,%4,%5,%6,%7,%8,%9}, "
        "{%10,%11,%12,%13}, %14, p, 1, 1, 1;\n}\n"
        : "+r"(d[0]), "+r"(d[1]), "+r"(d[2]), "+r"(d[3]), "+r"(d[4]), "+r"(d[5]), "+r"(d[6]), "+r"(d[7]), "+r"(d[8]), "+r"(d[9])
        : "r"(a0), "r"(a1), "r"(a2), "r"(a3), "l"(desc));
}

constexpr uint32_t SB = SMEM_BASE;
constexpr uint32_t R_SLOT = 18432, A_RING = SB, A_KP = SB + 73728, A_QX = SB + 81920, A_STB = SB + 98304;
constexpr uint32_t F_GU0 = SB + 98304, F_GU1 = SB + 163840, F_WD = F_GU0;
__host__ __device__ constexpr uint32_t o_a(uint32_t s) { return s == 0 ? SB : s == 1 ? A_QX : F_GU0 + (s - 2) * 32768; }
__host__ __device__ constexpr uint32_t o_b(uint32_t s) { return s < 2 ? SB + 16384 + s * 16384 : F_GU0 + 16384 + (s - 2) * 32768; }
constexpr uint32_t XT0 = SB + 49152, XT1 = XT0 + 16384;
constexpr uint32_t Q_ABYTES = 256 * 64 * 2, Q_STB = Q_ABYTES + 192 * 64 * 2;
constexpr uint32_t Q_CS = SB + 3 * Q_STB, Q_VS = Q_CS + 768, Q_RC = Q_VS + 256, Q_FIX = Q_RC + 2048;
constexpr uint32_t SD_VEC = SB + 176128, SD_W = SB + 180224;
static_assert(Q_FIX + 768 <= SD_VEC, "smem");
constexpr uint32_t M_RED = SB + 229376, M_BAR = M_RED + 2048, BAR_SET = 320, M_IVS = M_BAR + 2 * BAR_SET, M_SM = M_IVS + 128;
constexpr uint32_t M_F2 = M_SM;
constexpr uint32_t M_WS = M_SM + 16;
constexpr uint32_t M_SS = M_SM + 24;
constexpr uint32_t M_RT = M_SM + 32;
constexpr uint32_t M_SR = M_SM + 128;
constexpr int K_SMEM = M_SR + 128 - SB;
static_assert(K_SMEM == 232448, "smem");
constexpr uint32_t B_QF = 0, B_AF = 24, B_OF = 56, B_RES = 88, B_GU = 96, B_WD = 104, B_SW = 120, B_ONE = 128, B_QE = 136, B_OE = 160, B_PX = 192,
                   B_AE = 216, B_OD = 248, B_FG = 280, B_FD = 288, B_XS = 296, B_KS = 304, B_END = 320;
constexpr int NB_ML = 1, NB_CONS = 2, NB_SIDE = 3, NB_EPI = 4;

struct Maps { CUtensorMap x[3], wqkv, o, wo[2], r, g, u, d; };

template <int N>
__device__ __forceinline__ void halve(float (&v)[8], int lane, int bit) {
    const bool up = lane & bit;
    #pragma unroll
    for (int i = 0; i < N; i++) v[i] = (up ? v[N + i] : v[i]) + __shfl_xor_sync(0xffffffffu, up ? v[i] : v[N + i], bit);
}

__device__ __forceinline__ void reset_exchange(int c, int t) {
    #pragma unroll 1
    for (int i = t; i < FILL; i += 96) g_u.fill[c][i] = make_uint4(EMPTY, EMPTY, EMPTY, EMPTY);
}
__device__ __forceinline__ void prep_work(const bf16* __restrict__ x0, const bf16* __restrict__ w_r, uint32_t lb) {
    const int t = tid_now() - 288, c = cta_now(), lane = t & 31, warp = warp_uniform(t >> 5);
    const uint32_t wb = SD_W + warp * 8192;
    mbar_nap(lb + B_SW, 0);
    {
        float cs[8], cq[8];
        #pragma unroll
        for (int i = 0; i < 8; i++) { cs[i] = 0.f; cq[i] = 0.f; }
        #pragma unroll 1
        for (int h = 0; h < 2; h++) {
            #pragma unroll 2
            for (int r = 0; r < 16; r++) {
                const uint4 u = lds128(wb + h * 24576 + (lane >> 3) * 128 + r * 512 + (((lane & 7) ^ ((r * 4 + (lane >> 3)) & 7)) << 4));
                const uint32_t w[4] = {u.x, u.y, u.z, u.w};
                #pragma unroll
                for (int e = 0; e < 4; e++) {
                    const float a = bf_lo(w[e]), b = bf_hi(w[e]);
                    cs[2*e] += a; cs[2*e+1] += b; cq[2*e] = fmaf(a, a, cq[2*e]); cq[2*e+1] = fmaf(b, b, cq[2*e+1]);
                }
            }
            fence_async_smem();
            __syncwarp();
            if (elect_one()) {
                const uint32_t bytes = h == 0 ? 8192 : warp < 2 ? 4096 : 2048;
                mbar_expect_tx(lb + B_PX + warp * 8, bytes);
                bulk_load(wb + h * 24576, h && warp == 2 ? w_r : x0 + (size_t)(c * 16 + (h ? 12 + warp * 2 : warp * 4)) * D_, bytes, lb + B_PX + warp * 8);
            }
            __syncwarp();
        }
        halve<4>(cs, lane, 16); halve<2>(cs, lane, 8);
        halve<4>(cq, lane, 16); halve<2>(cq, lane, 8);
        *reinterpret_cast<float4*>(&g_cs[c >> 4][warp * D_ + (c & 15) * 64 + (lane & 7) * 8 + (lane >> 3) * 2]) = make_float4(cs[0], cq[0], cs[1], cq[1]);
    }
    TL(288, 22);
    reset_exchange(c, t);
    mbar_nap(lb + B_PX + warp * 8, 0);
    #pragma unroll 1
    for (int i = 0; i < (warp < 2 ? 6 : 5); i++) {
        const int r = i < 4 ? warp * 4 + i : 8 + warp * 2 + i;
        float s0 = 0.f, s1 = 0.f, q0 = 0.f, q1 = 0.f;
        #pragma unroll 2
        for (int j = 0; j < 4; j++) {
            const uint4 u = lds128(wb + (i >> 2) * 16384 + i * 2048 + j * 512 + lane * 16);
            const uint32_t w[4] = {u.x, u.y, u.z, u.w};
            #pragma unroll
            for (int e = 0; e < 4; e++) { const float a = bf_lo(w[e]), b = bf_hi(w[e]); s0 += a; s1 += b; q0 = fmaf(a, a, q0); q1 = fmaf(b, b, q1); }
        }
        s0 += s1; q0 += q1;
        float v = (lane & 16 ? q0 : s0) + __shfl_xor_sync(0xffffffffu, lane & 16 ? s0 : q0, 16);
        #pragma unroll
        for (int o = 8; o > 0; o >>= 1) v += __shfl_xor_sync(0xffffffffu, v, o);
        const float mean = v * (1.f / D_), sq = __shfl_xor_sync(0xffffffffu, mean, 16);
        if (lane == 0) {
            if (r < 16) g_rs0[c * 16 + r] = make_float2(fmaxf(sq - mean * mean, 0.f), mean);
            else stsf(M_WS, v);
        }
    }
    named_sync(NB_SIDE, 96);
    if (t == 0) { TL(288, 23); ctr_arrive(&g_pctr); ctr_wait(&g_pctr, 128); TL(288, 24); }
    named_sync(NB_SIDE, 96);
}

__device__ __forceinline__ void head_scales(float fq, float fk, float& sq, float& sk, float& ss) {
    const bool ok = fq <= 16384.f && fk <= 16384.f && fq * fk <= 50000.f;
    const int a = min(max((((int)(__float_as_uint(fq) >> 23) - 125) >> 1) - 8, -60), 60), b = min(max((((int)(__float_as_uint(fk) >> 23) - 125) >> 1) - 8, -60), 60);
    sq = QSCALE * __uint_as_float((uint32_t)(ok ? 127 : 127 - a) << 23);
    sk = __uint_as_float((uint32_t)(ok ? 127 : 127 - b) << 23);
    ss = ok ? 0.f : __uint_as_float((uint32_t)(127 + a + b) << 23);
}

__device__ __forceinline__ void epi_inputs(int L, const bf16* __restrict__ w_r) {
    const int t = tid_now() - 288, c = cta_now(), mt = c >> 4, nt = c & 15, lane = t & 31;
    const uint32_t wr = t < 64 ? __ldg(reinterpret_cast<const uint32_t*>(w_r) + (c & 7) * 64 + t) : 0x3F803F80u;
    #pragma unroll 1
    for (int k = 0; k < 3; k++) {
        const int i = t + 96 * k, col = (i >> 6) * D_ + nt * 64 + (i & 63);
        const float2* rsp = (L ? g_x.rs1 : g_rs0) + mt * 256 + (i & 255);
        uint2 sv = ld_x64(rsp);
        if (k < 2) {
            float2 p[8];
            #pragma unroll
            for (int j = 0; j < 8; j++) p[j] = __ldcg(&g_cs[j][col]);
            stsf(Q_CS + i * 4, ((p[0].x + p[1].x) + (p[2].x + p[3].x)) + ((p[4].x + p[5].x) + (p[6].x + p[7].x)));
            const float zz = ((p[0].y + p[1].y) + (p[2].y + p[3].y)) + ((p[4].y + p[5].y) + (p[6].y + p[7].y));
            const float zs = warp_sum(zz);
            if (i < 128) { if (lane == 0) stsf(M_SR + (i >> 5) * 4, zs); }
            else {
                const int e = (int)(__float_as_uint(zz) >> 23) - 127;
                const int sh = min(max(((e + 2) >> 1) + 3, -60), 60);
                sts32(Q_VS + (i - 128) * 4, (uint32_t)(127 - sh) << 23);
                sts16(M_IVS + ((i & 32) + (i & 6) * 4 + ((i >> 2) & 6) + (i & 1)) * 2, (uint32_t)(127 + sh - 4) << 7);
            }
        }
        else {
            named_sync(NB_SIDE, 96);
            if (t < 2) {
                float sq, sk, ss;
                head_scales(ldsf(M_SR + t * 4), ldsf(M_SR + 8 + t * 4), sq, sk, ss);
                stsf(M_F2 + t * 4, sq); stsf(M_F2 + 8 + t * 4, sk); stsf(M_SS + t * 4, ss);
            }
            __syncwarp();
        }
        uint32_t n = 0;
        #pragma unroll 1
        while (warp_any(sv.x == EMPTY)) { sv = ld_x64(rsp); poll_tick(n); }
        const float var = __uint_as_float(sv.x), a = L ? 1.f + rsq(var + LN_EPS) : 1.f;
        sts64(Q_RC + (i & 255) * 8, __float_as_uint(a * rsq(a * a * var + LN_EPS)), sv.y ^ 0x80000000u);
    }
    if (t < 68) sts32(M_RED + t * 4, wr);
}

__device__ __forceinline__ void ffn_finish(int L, bf16* __restrict__ out) {
    const int t = tid_now() - 288, c = cta_now(), lane = t & 31, warp = warp_uniform(t >> 5);
    TL(288, L * 32 + 29);
    const uint4 rv = lds128(M_RT + 16 * L);
    const int idx = (int)rv.w;
    const uint32_t* xsrc = &g_x.cand[L][idx >> 7][(c >> 2) * 16 + (t & 3) * 4 + (c & 3)];
    const uint8_t* fsrc = &g_x.x[L][idx >> 8][((idx >> 7) & 1) * 8 + (c >> 4)];
    uint32_t xw, busy;
    float a[4] = {0.f, 0.f, 0.f, 0.f};
    {
        const float* src = &g_x.ypart[L][c][0][t * 4];
        uint4 v[3];
        uint32_t n = 0;
        __nanosleep(500);
        #pragma unroll 1
        do {
            v[0] = ld_x128(src); v[1] = ld_x128(src + 384);
            v[2] = make_uint4(0u, 0u, 0u, 0u);
            xw = 0u; busy = 0u;
            if (warp == 0) {
                v[2] = ld_x128(src + 768); xw = ld_x32(xsrc);
                asm volatile("ld.relaxed.gpu.global.u8 %0, [%1];" : "=r"(busy) : "l"(fsrc) : "memory");
            }
            poll_tick(n);
        } while (warp_any(any_empty(v[0]) || any_empty(v[1]) || any_empty(v[2]) || xw == EMPTY || busy != 0));
        TL(288, L * 32 + 30); TL(352, L * 32 + 31);
        #pragma unroll
        for (int i = 0; i < 3; i++) { a[0] += __uint_as_float(v[i].x); a[1] += __uint_as_float(v[i].y); a[2] += __uint_as_float(v[i].z); a[3] += __uint_as_float(v[i].w); }
    }
    #pragma unroll
    for (int o = 2; o < 32; o <<= 1) {
        #pragma unroll
        for (int i = 0; i < 4; i++) a[i] += __shfl_xor_sync(0xffffffffu, a[i], o);
    }
    if (lane < 2) sts128(M_SR + warp * 32 + lane * 16, __float_as_uint(a[0]), __float_as_uint(a[1]), __float_as_uint(a[2]), __float_as_uint(a[3]));
    named_sync(NB_SIDE, 96);
    if (t < 4) {
        const float2 y0 = lds64f(M_SR + t * 8), y1 = lds64f(M_SR + 32 + t * 8), y2 = lds64f(M_SR + 64 + t * 8);
        const uint32_t y = pack_bf16(y0.x + y1.x + y2.x, y0.y + y1.y + y2.y);
        const float rsel = bf_round(rcp(1.f + __expf(-bf_round(__uint_as_float(rv.x)))));
        const uint32_t xn = ln2(xw, ln2_coef(__uint_as_float(rv.y), __uint_as_float(rv.z)));
        const uint32_t res = badd2(xw, badd2(xn, pack_bf16(bf_lo(y) * rsel, bf_hi(y) * rsel)));
        if (L == 0) st_x32(&g_x.x2row[c * 4 + t], res);
        reinterpret_cast<uint32_t*>(L ? out : g_x1)[idx * (D_ / 2) + c * 4 + t] = res;
    }
}

__device__ __forceinline__ void fix_row(uint32_t lb) {
    const int t = tid_now() - 288, c = cta_now(), lane = t & 31, warp = warp_uniform(t >> 5);
    uint4 v[2];
    {
        uint32_t n = 0;
        #pragma unroll 1
        do {
            v[0] = ld_x128(g_x.x2row + t * 4);
            v[1] = make_uint4(0u, 0u, 0u, 0u);
            if (warp == 0) v[1] = ld_x128(g_x.x2row + (96 + t) * 4);
            poll_tick(n);
        } while (warp_any(any_empty(v[0]) || any_empty(v[1])));
    }
    const uint32_t w[8] = {v[0].x, v[0].y, v[0].z, v[0].w, v[1].x, v[1].y, v[1].z, v[1].w};
    float su = 0.f, sq = 0.f;
    #pragma unroll
    for (int i = 0; i < 8; i++) { const float a = bf_lo(w[i]), b = bf_hi(w[i]); su += a + b; sq = fmaf(a, a, fmaf(b, b, sq)); }
    su = warp_sum(su); sq = warp_sum(sq);
    if (lane == 0) sts64(M_SR + 96 + warp * 8, __float_as_uint(su), __float_as_uint(sq));
    named_sync(NB_SIDE, 96);
    const float2 s0 = lds64f(M_SR + 96), s1 = lds64f(M_SR + 104), s2 = lds64f(M_SR + 112);
    const float mean = (s0.x + s1.x + s2.x) * (1.f / D_);
    const float rstd = rsq(fmaxf((s0.y + s1.y + s2.y) * (1.f / D_) - mean * mean, 0.f) + LN_EPS);
    const Ln2 k = ln2_coef(mean, rstd);
    #pragma unroll
    for (int i = 0; i < 2; i++)
        if (i == 0 || warp == 0) sts128(SD_VEC + (t + 96 * i) * 16, ln2(w[4*i], k), ln2(w[4*i+1], k), ln2(w[4*i+2], k), ln2(w[4*i+3], k));
    named_sync(NB_SIDE, 96);
    TL(288, 32 + 22);
    mbar_nap(lb + B_SW, 0);
    float a[8];
    #pragma unroll
    for (int i = 0; i < 8; i++) a[i] = 0.f;
    const uint32_t xa = base32(SD_VEC + lane * 2), wa = base32(SD_W + lane * 48 + warp * 16);
    #pragma unroll 2
    for (int b = 0; b < 32; b++) {
        const float x = bf_lo(lds16(xa + b * 64));
        const uint4 u = lds128(wa + b * 1536);
        a[0] = fmaf(x, bf_lo(u.x), a[0]); a[1] = fmaf(x, bf_hi(u.x), a[1]); a[2] = fmaf(x, bf_lo(u.y), a[2]); a[3] = fmaf(x, bf_hi(u.y), a[3]);
        a[4] = fmaf(x, bf_lo(u.z), a[4]); a[5] = fmaf(x, bf_hi(u.z), a[5]); a[6] = fmaf(x, bf_lo(u.w), a[6]); a[7] = fmaf(x, bf_hi(u.w), a[7]);
    }
    halve<4>(a, lane, 16); halve<2>(a, lane, 8); halve<1>(a, lane, 4);
    a[0] = quad_sum(a[0]);
    if ((lane & 3) == 0) st_x32(&g_x.fix[c * 24 + warp * 8 + (lane >> 2)], __float_as_uint(a[0]));
    TL(288, 32 + 23);
    if (((int)lds32(M_RT + 12) >> 8) == (c >> 4)) {
        const float* src = &g_x.fix[(t >> 5) * D_ + (c & 15) * 64 + (t & 31) * 2];
        uint2 f;
        uint32_t n = 0;
        #pragma unroll 1
        do { f = ld_x64(src); poll_tick(n); } while (warp_any(f.x == EMPTY || f.y == EMPTY));
        sts64(Q_FIX + t * 8, f.x, f.y);
    }
}

#define PFXNS 1000
#define GAPNS 900
__device__ __forceinline__ void publish(uint8_t* f) {
    bulk_commit();
    bulk_wait();
    fence_async_global();
    asm volatile("st.release.gpu.global.u8 [%0], 0;" :: "l"(f) : "memory");
}
__device__ __forceinline__ void side_role(const Maps& mp, const bf16* __restrict__ x0, const bf16* __restrict__ wo, const bf16* __restrict__ w_down, const bf16* __restrict__ w_r, bf16* __restrict__ out) {
    #pragma unroll 1
    for (int L = 0; L < 2; L++) {
        const uint32_t lb = M_BAR + L * BAR_SET;
        if (L == 0) prep_work(x0, w_r, lb);
        else fix_row(lb);
        epi_inputs(L, w_r);
        const int t = tid_now() - 288, c = cta_now(), mt = c >> 4, nt = c & 15, warp = warp_uniform(t >> 5);
        TL(288, L * 32 + 4);
        named_arrive(NB_EPI, 224);
        named_arrive(NB_EPI + 1, 224);
        if (warp == 0) {
            named_sync(NB_ML, 288);
            #pragma unroll
            for (int i = 0; i < 16; i++) sts128(base32(A_RING + 16384 + t * 16) + (i >> 2) * R_SLOT + (i & 3) * 512, 0x2C002C00u, 0x2C002C00u, 0x2C002C00u, 0x2C002C00u);
            fence_async_smem();
            __syncwarp();
            mbar_arrive_elect(lb + B_ONE);
        }
        if (elect_one()) {
            #pragma unroll 1
            for (int n = warp - 1; n >= 0 && n < 3 * warp - 2; n++) {
                char* dst = g_kv + (size_t)(nt * 2 + (n >> 1)) * 16 * KV_TILE;
                const int tile = 2 * mt + (n & 1);
                if (n < 3) mbar_nap(lb + (n == 2 ? B_AE + 16 : B_KS + 8 * n), 0);
                bulk_store(dst + ((tile - 1) & 15) * KV_TILE, n == 0 ? A_KP : n == 1 ? A_RING : A_STB + (n - 2) * 8192, 8192);
                bulk_store(dst + tile * KV_TILE + 8192, n < 2 ? A_RING + 8192 + n * R_SLOT : A_STB + n * 8192, 8192);
                publish(&g_x.kv[L][nt * 2 + (n >> 1)][tile]);
                if (n == 1) TL(352, L * 32 + 6);
                if (n == 0) TL(320, L * 32 + 27);
            }
            if (warp == 2) {
                const bool ffn = c < NFC;
                const uint64_t pol = policy_evict_first();
                mbar_expect_tx(lb + B_GU, ffn ? 131072 : 0);
                mbar_expect_tx(lb + B_WD, ffn ? 65536 : 0);
                l2_prefetch(reinterpret_cast<const char*>(wo) + (size_t)c * 16384, 16384);
                if (ffn) {
                    #pragma unroll 1
                    for (int i = 0; i < 12; i++) {
                        if (i < 8) tma_load_s(F_GU0 + i * 16384, (i & 1) ? &mp.u : &mp.g, c * 32, (i >> 1) * 256, lb + B_GU, pol);
                        else l2_prefetch(reinterpret_cast<const char*>(w_down) + (size_t)c * 65536 + (i - 8) * 16384, 16384);
                        __nanosleep(GAPNS);
                    }
                }
                mbar_nap(lb + B_OD, 0);
                __nanosleep(PFXNS);
                l2_prefetch(g_u.fill[c], sizeof(g_u.fill[0]));
                mbar_nap(lb + B_XS, 0);
                tma_store(&mp.x[L + 1], XT0, (c & 7) * 128, (c >> 3) * 128);
                tma_store(&mp.x[L + 1], XT1, (c & 7) * 128 + 64, (c >> 3) * 128);
                publish(&g_x.x[L][mt][nt]);
                TL(352, L * 32 + 18);
            } else {
                #pragma unroll 1
                for (int p = 0; p < 2; p++) { mbar_sleep(lb + B_OD + (p * 2 + warp) * 8, 0); ctr_arrive(g_x.o[L][mt * 2 + warp][p]); TL(288, L * 32 + 19); }
            }
        }
        __syncwarp();
        mbar_sleep(lb + B_FD, 0);
        if (c == 0 && t == 0 && L == 0) g_pctr = 0;
        ffn_finish(L, out);
        TL(288, L * 32 + 20);
    }
}

struct Cols { float2 c[4], v[4]; };
template <int HH>
__device__ __forceinline__ void load_cols(Cols& k, uint32_t cs) {
    #pragma unroll
    for (int jj = 0; jj < 4; jj++) {
        k.c[jj] = lds64f(cs + (HH * 32 + jj * 8) * 4);
        if (HH >= 4) k.v[jj] = lds64f(cs + (Q_VS - Q_CS) + ((HH & 1) * 32 + jj * 8) * 4);
    }
}
template <int HH>
__device__ __forceinline__ void qkv_epi_head(const float (&acc0)[96], const float (&acc1)[96], const float (&cf)[4], const float (&nm)[4], const Cols& k, float hs, uint32_t (&pk)[4][4]) {
    #pragma unroll
    for (int jj = 0; jj < 4; jj++) {
        #pragma unroll
        for (int i = 0; i < 4; i++) {
            const float* a = (i >> 1) ? acc1 : acc0;
            const float sc = HH < 4 ? cf[i] * hs : cf[i];
            float x = fmaf(nm[i], k.c[jj].x, a[4 * (4 * HH + jj) + 2 * (i & 1)]) * sc;
            float y = fmaf(nm[i], k.c[jj].y, a[4 * (4 * HH + jj) + 2 * (i & 1) + 1]) * sc;
            if (HH >= 4) { x *= k.v[jj].x; y *= k.v[jj].y; }
            pk[i][jj] = pack_f16(x, y);
        }
    }
}
__device__ __forceinline__ void stage_kv(uint32_t dst, const uint32_t (&pk)[4][4]) {
    #pragma unroll
    for (int i = 0; i < 4; i++) stsm4(dst + (i >> 1) * 1024 + (i & 1) * 128, pk[i][0], pk[i][1], pk[i][2], pk[i][3]);
}
template <int OFF>
__device__ __forceinline__ void patch_row(float (&acc)[96], uint32_t fx) {
    #pragma unroll
    for (int j = 0; j < 24; j++) { const float2 f = lds64f(fx + j * 32); acc[4 * j + OFF] = f.x; acc[4 * j + OFF + 1] = f.y; }
}
#define QLEAD 2
template <bool INIT>
__device__ __forceinline__ void qkv_step(float (&acc0)[96], float (&acc1)[96], uint64_t da, uint64_t db) {
    wg_fence();
    #pragma unroll
    for (int kk = 0; kk < 4; kk++) {
        if (INIT && kk == 0) { wg_gemm_n192_init(acc0, da, db); wg_gemm_n192_init(acc1, da + (8192 >> 4), db); }
        else { wg_gemm_n192(acc0, da + kk * 2, db + kk * 128); wg_gemm_n192(acc1, da + (8192 >> 4) + kk * 2, db + kk * 128); }
    }
    wg_commit();
}
__device__ __forceinline__ void qkv_phase(int L, uint32_t lb, int wg, uint32_t (&qa)[8], uint32_t (&qb)[8], uint32_t (&SA)[32], uint32_t (&SB_)[32]) {
    float acc0[96], acc1[96];
    {
        const bool leader = (tid_now() & 127) == 0;
        const uint64_t da0 = opaque(desc_sw128(SB + wg * 16384, 16, 1024)), db0 = opaque(desc_sw128(SB + Q_ABYTES, 8192, 1024));
        mbar_spin(lb + B_QF, 0);
        TL(0, L * 32 + 1); CK(0, L * 32 + 10);
        qkv_step<true>(acc0, acc1, da0, db0);
        uint32_t st = 1, ph = 0;
        #pragma unroll 1
        for (int k = 1; k < 16; k++) {
            mbar_spin(lb + B_QF + 8 * st, ph);
            if (k == 16 - QLEAD && wg) named_sync(NB_CONS, 256);
            qkv_step<false>(acc0, acc1, da0 + st * (Q_STB >> 4), db0 + st * (Q_STB >> 4));
            if (k == 15 && !wg) named_arrive(NB_CONS, 256);
            wg_wait<1>();
            if (leader) mbar_arrive(lb + B_QE + 8 * (st == 0 ? 2 : st - 1));
            if (++st == 3) { st = 0; ph ^= 1; }
        }
    }
    named_sync(NB_EPI + wg, 224);
    const int tid = tid_now(), lane = tid & 31, w = (tid >> 5) & 3, g = lane >> 2, t = lane & 3;
    const int lr0 = wg * 128 + w * 16 + g;
    float cf[4], nm[4];
    #pragma unroll
    for (int i = 0; i < 4; i++) { const float2 r = lds64f(base32(Q_RC + lr0 * 8) + ((i >> 1) * 64 + (i & 1) * 8) * 8); cf[i] = r.x; nm[i] = r.y; }
    const uint32_t cs = base32(Q_CS + t * 8);
    const int d = L ? (int)lds32(M_RT + 12) - ((cta_now() >> 4) * 256 + lr0) : -1;
    const uint4 hs = lds128(M_F2);
    const uint32_t ko = base32((lane >> 3) * 2048 + (w * 16 + (lane & 7)) * 16);
    Cols k0, k1;
    load_cols<2>(k0, cs);
    wg_wait<0>();
    pin(acc0); pin(acc1);
    TL(128, L * 32 + 2); CK(128, L * 32 + 11);
    named_arrive(NB_ML, 288);
    if ((tid & 127) == 0) mbar_arrive(lb + B_QE);
    if (__builtin_expect((d & ~72) == 0, 0)) {
        if (d == 0) { patch_row<0>(acc0, cs + (Q_FIX - Q_CS)); cf[0] = 1.f; nm[0] = 0.f; }
        else if (d == 8) { patch_row<2>(acc0, cs + (Q_FIX - Q_CS)); cf[1] = 1.f; nm[1] = 0.f; }
        else if (d == 64) { patch_row<0>(acc1, cs + (Q_FIX - Q_CS)); cf[2] = 1.f; nm[2] = 0.f; }
        else { patch_row<2>(acc1, cs + (Q_FIX - Q_CS)); cf[3] = 1.f; nm[3] = 0.f; }
    }
    __syncwarp();
    uint32_t pk[4][4];
    qkv_epi_head<2>(acc0, acc1, cf, nm, k0, __uint_as_float(hs.z), pk);
    load_cols<4>(k1, cs);
    mbar_spin(lb + B_QE + 8 - 8 * wg, wg);
    stage_kv((wg ? A_RING : A_KP) + ko, pk);
    qkv_epi_head<4>(acc0, acc1, cf, nm, k1, 1.f, pk);
    load_cols<3>(k0, cs);
    stage_kv(A_RING + wg * R_SLOT + 8192 + ko, pk);
    fence_async_smem();
    __syncwarp();
    mbar_arrive_elect(lb + B_KS + 8 * wg);
    qkv_epi_head<3>(acc0, acc1, cf, nm, k0, __uint_as_float(hs.w), pk);
    load_cols<0>(k1, cs);
    load_cols<5>(k0, cs);
    stage_kv(A_STB + wg * 8192 + ko, pk);
    qkv_epi_head<0>(acc0, acc1, cf, nm, k1, __uint_as_float(hs.x), pk);
    #pragma unroll
    for (int s = 0; s < 2; s++) {
        qa[4*s] = pk[0][2*s]; qa[4*s+1] = pk[1][2*s]; qa[4*s+2] = pk[0][2*s+1]; qa[4*s+3] = pk[1][2*s+1];
        qb[4*s] = pk[2][2*s]; qb[4*s+1] = pk[3][2*s]; qb[4*s+2] = pk[2][2*s+1]; qb[4*s+3] = pk[3][2*s+1];
    }
    mbar_spin(lb + B_KS, 0);
    {
        constexpr uint64_t dk = desc_plain(A_KP, 2048, 128);
        wg_fence();
        wg_qk_init(SA, qa[0], qa[1], qa[2], qa[3], dk);
        wg_qk_acc(SA, qa[4], qa[5], qa[6], qa[7], dk + 256);
        wg_qk_init(SB_, qb[0], qb[1], qb[2], qb[3], dk);
        wg_commit();
    }
    qkv_epi_head<5>(acc0, acc1, cf, nm, k0, 1.f, pk);
    load_cols<1>(k1, cs);
    stage_kv(A_STB + 16384 + wg * 8192 + ko, pk);
    qkv_epi_head<1>(acc0, acc1, cf, nm, k1, __uint_as_float(hs.y), pk);
    #pragma unroll
    for (int u = 0; u < 2; u++)
        #pragma unroll
        for (int s = 0; s < 2; s++) sts128(A_QX + (u * 2 + s) * 4096 + tid * 16, pk[2*u][2*s], pk[2*u+1][2*s], pk[2*u][2*s+1], pk[2*u+1][2*s+1]);
    fence_async_smem();
    wg_wait<0>();
    pin(SA); pin(SB_);
    TL(128, L * 32 + 5); CK(128, L * 32 + 12);
}

#define PMASK 0x0000AAAAu
#define IMASK 0x10101010u
__host__ __device__ constexpr bool is_poly(int j) { return !((PMASK >> j) & 1); }
struct Shift { uint32_t f0, f1, n0, n1, bad; };

__device__ __forceinline__ uint32_t exp2_mufu(uint32_t s, uint32_t nm) {
    uint32_t r;
    asm("ex2.approx.f16x2 %0, %1;" : "=r"(r) : "r"(hadd2(s, nm)));
    return r;
}
__device__ __forceinline__ uint32_t exp2_fix(uint32_t s, uint32_t fm, uint32_t ca, uint32_t& U, bool mul, uint32_t sixteen) {
    uint32_t G, D;
    asm("fma.rn.relu.f16x2 %0, %1, %2, %3;" : "=r"(U) : "r"(s), "r"(0x00400040u), "r"(fm));
    asm("fma.rn.f16x2 %0, %1, %2, %3;" : "=r"(G) : "r"(U & 0x003F003Fu), "r"(ca), "r"(0x98B898B8u));
    asm("{.reg .b32 n; neg.f16x2 n, %1; fma.rn.relu.f16x2 %0, %1, n, %2;}" : "=r"(D) : "r"(G), "r"(0x00570057u));
    if (mul) return U * sixteen - D;
    return (U << 4) - D;
}
__device__ __forceinline__ uint32_t or3(uint32_t a, uint32_t b, uint32_t c) { uint32_t r; asm("lop3.b32 %0, %1, %2, %3, 0xFE;" : "=r"(r) : "r"(a), "r"(b), "r"(c)); return r; }
__device__ __forceinline__ void exp_tile(const uint32_t (&S)[32], uint32_t (&P)[32], Shift& h, uint32_t ca, uint32_t sixteen) {
    uint32_t U[33];
    int n = 0;
    #pragma unroll
    for (int i = 0; i < 32; i++) {
        if (is_poly(i)) P[i] = exp2_fix(S[i], (i & 1) ? h.f1 : h.f0, ca, U[n++], (IMASK >> i) & 1, sixteen);
        else P[i] = exp2_mufu(S[i], (i & 1) ? h.n1 : h.n0);
    }
    U[n] = 0u;
    #pragma unroll
    for (int i = 0; i < 32; i += 6) {
        if (i + 5 <= n) h.bad = or3(h.bad, or3(U[i], U[i + 1], U[i + 2]), or3(U[i + 3], U[i + 4], U[i + 5]));
        else
        {
            #pragma unroll
            for (int j = i; j < i + 6; j += 2) if (j < n) h.bad = or3(h.bad, U[j], U[j + 1]);
        }
    }
    pin(P);
}
__device__ __forceinline__ uint32_t hfma2(uint32_t a, uint32_t b, uint32_t c) { uint32_t r; asm("fma.rn.f16x2 %0, %1, %2, %3;" : "=r"(r) : "r"(a), "r"(b), "r"(c)); return r; }
__device__ __forceinline__ void unit_start(const uint32_t (&S)[32], Shift& h, uint32_t (&o2)[10]) {
    uint32_t m[4] = {S[0], S[1], S[2], S[3]};
    #pragma unroll
    for (int i = 1; i < 8; i++)
        #pragma unroll
        for (int e = 0; e < 4; e++) m[e] = hmax2(m[e], S[4 * i + e]);
    const uint32_t a = hadd2(m[0], m[2]), c = hadd2(m[1], m[3]);
    uint32_t x = hadd2(__byte_perm(a, c, 0x5410), __byte_perm(a, c, 0x7632));
    x = hadd2(x, __shfl_xor_sync(0xffffffffu, x, 1));
    x = hadd2(x, __shfl_xor_sync(0xffffffffu, x, 2));
    const uint32_t T = hfma2(x, 0xAC00AC00u, 0x5DEB5DEBu);
    const uint32_t n = hadd2(T, 0xDE00DE00u), f = hfma2(n, 0x00400040u, 0x03C003C0u);
    h.n0 = __byte_perm(n, 0, 0x1010); h.n1 = __byte_perm(n, 0, 0x3232);
    h.f0 = __byte_perm(f, 0, 0x1010); h.f1 = __byte_perm(f, 0, 0x3232);
    h.bad = T ^ 0x58005800u;
    #pragma unroll
    for (int i = 0; i < 10; i++) o2[i] = 0u;
}
__device__ __forceinline__ uint32_t o_offset() {
    const int c = cta_now(), tid = tid_now();
    return ((c >> 4) * 256 + (tid & 128) + ((tid >> 1) & 48) + ((tid >> 2) & 7)) * (D_ * 2) + (c & 15) * 64 + (tid & 3) * 16;
}
template <int PASS, int UNIT>
__device__ __forceinline__ void unit_end(const uint32_t (&o)[10], uint32_t bad, uint32_t lb, uint32_t oo, uint32_t& fail) {
    float v[20];
    #pragma unroll
    for (int i = 0; i < 10; i++) h2_unpack(o[i], v[2 * i], v[2 * i + 1]);
    const float i0 = rcp(v[16]), i1 = rcp(v[18]);
    const uint4 iv = lds128(M_IVS + PASS * 64 + (oo & 48));
    uint32_t r[8], z = 0;
    #pragma unroll
    for (int j = 0; j < 4; j++) {
        r[j] = pack_bf16(v[4*j] * i0, v[4*j+1] * i0); r[4 + j] = pack_bf16(v[4*j+2] * i1, v[4*j+3] * i1);
        z = bfma2(r[j], r[4 + j], z);
    }
    const bool good = o[8] - 0x34003400u < 0x48000000u && o[9] - 0x34003400u < 0x48000000u &&
                      ((bad & 0xF800F800u) | (bmul2(z, 0u) & 0x7FFF7FFFu) | (fail & (1u << (2 * PASS + UNIT)))) == 0;
    const bool all = __all_sync(0xffffffffu, good);
    char* dst = reinterpret_cast<char*>(g_o) + oo + (UNIT * 64 * D_ + PASS * 512) * 2;
    stg128_pred(dst, make_uint4(bmul2(r[0], iv.x), bmul2(r[1], iv.y), bmul2(r[2], iv.z), bmul2(r[3], iv.w)), all);
    stg128_pred(dst + 16 * D_, make_uint4(bmul2(r[4], iv.x), bmul2(r[5], iv.y), bmul2(r[6], iv.z), bmul2(r[7], iv.w)), all);
    if (__builtin_expect(!all, 0)) {
        fail |= 1u << (2 * PASS + UNIT);
        if (PASS == 0) {
            #pragma unroll
            for (int s = 0; s < 2; s++) g_qsave[cta_now()][UNIT * 2 + s][tid_now()] = lds128(A_KP + (UNIT * 2 + s) * 4096 + tid_now() * 16);
        }
    }
    __syncwarp();
    mbar_arrive_elect_p(lb + PASS * 16, all);
}
__device__ __forceinline__ void swap_q(uint32_t (&q)[8], uint32_t a) {
    asm volatile("{\n.reg .pred p;\nsetp.ne.u32 p, %8, 0;\n"
                 "@p st.shared.v4.b32 [%8 + -8192], {%0, %1, %2, %3};\n@p st.shared.v4.b32 [%8 + -4096], {%4, %5, %6, %7};\n"
                 "@p ld.shared.v4.b32 {%0, %1, %2, %3}, [%8];\n@p ld.shared.v4.b32 {%4, %5, %6, %7}, [%8 + 4096];\n}"
                 : "+r"(q[0]), "+r"(q[1]), "+r"(q[2]), "+r"(q[3]), "+r"(q[4]), "+r"(q[5]), "+r"(q[6]), "+r"(q[7]) : "r"(a) : "memory");
}
static_assert(A_QX == A_KP + 8192, "parking places");
template <bool INIT>
__device__ __forceinline__ void issue_pv(uint32_t (&o)[10], const uint32_t (&P)[32], uint64_t dv) {
    if (INIT) wg_pv_init(o, P[0], P[1], P[2], P[3], dv); else wg_pv_acc(o, P[0], P[1], P[2], P[3], dv);
    #pragma unroll
    for (int k = 1; k < 8; k++) wg_pv_acc(o, P[4*k], P[4*k+1], P[4*k+2], P[4*k+3], dv + k * 16);
}

__device__ __forceinline__ uint4 quad_transpose(uint32_t x0, uint32_t x1, uint32_t x2, uint32_t x3, int t) {
    const bool b0 = t & 1, b1 = t & 2;
    uint32_t s0 = b0 ? x0 : x1, s1 = b0 ? x2 : x3;
    s0 = __shfl_xor_sync(0xffffffffu, s0, 1); s1 = __shfl_xor_sync(0xffffffffu, s1, 1);
    const uint32_t y0 = b0 ? s0 : x0, y1 = b0 ? x1 : s0, y2 = b0 ? s1 : x2, y3 = b0 ? x3 : s1;
    uint32_t u0 = b1 ? y0 : y2, u1 = b1 ? y1 : y3;
    u0 = __shfl_xor_sync(0xffffffffu, u0, 2); u1 = __shfl_xor_sync(0xffffffffu, u1, 2);
    return b1 ? make_uint4(u0, u1, y2, y3) : make_uint4(y0, y1, u0, u1);
}
__device__ __forceinline__ uint32_t movm(uint32_t v) { uint32_t r; asm volatile("movmatrix.sync.aligned.m8n8.trans.b16 %0, %1;" : "=r"(r) : "r"(v)); return r; }
__device__ __forceinline__ void attn_repair(const uint4 qx, const uint4 qy, uint32_t lb, int pass, int unit) {
    const int tid = tid_now(), g = (tid & 31) >> 2, t = tid & 3;
    float ss = ldsf(M_SS + pass * 4);
    if (ss == 0.f) ss = 1.f;
    const uint4 q0 = quad_transpose(qx.x, qx.z, qy.x, qy.z, t), q1 = quad_transpose(qx.y, qx.w, qy.y, qy.w, t);
    const char* kv = g_kv + (size_t)((cta_now() & 15) * 2 + pass) * 16 * KV_TILE + t * 2048 + g * 16;
    float o[4][4], m0 = -INFINITY, m1 = -INFINITY, l0 = 0.f, l1 = 0.f;
    #pragma unroll
    for (int j = 0; j < 4; j++) { o[j][0] = 0.f; o[j][1] = 0.f; o[j][2] = 0.f; o[j][3] = 0.f; }
    uint4 kf[8];
    #pragma unroll
    for (int i = 0; i < 8; i++) kf[i] = __ldcg(reinterpret_cast<const uint4*>(kv + 15 * KV_TILE + i * 128));
    #pragma unroll 1
    for (int b = 0; b < 32; b++) {
        uint4 vf[8];
        #pragma unroll
        for (int i = 0; i < 8; i++) vf[i] = __ldcg(reinterpret_cast<const uint4*>(kv + (b >> 1) * KV_TILE + (b & 1) * 1024 + 8192 + i * 128));
        float s[8][4];
        #pragma unroll
        for (int i = 0; i < 8; i++) {
            s[i][0] = 0.f; s[i][1] = 0.f; s[i][2] = 0.f; s[i][3] = 0.f;
            mma_f16(s[i], q0.x, q1.x, q0.y, q1.y, kf[i].x, kf[i].y); mma_f16(s[i], q0.z, q1.z, q0.w, q1.w, kf[i].z, kf[i].w);
        }
        #pragma unroll
        for (int i = 0; i < 8; i++) kf[i] = __ldcg(reinterpret_cast<const uint4*>(kv + (((b - 1) >> 1) & 15) * KV_TILE + (~b & 1) * 1024 + i * 128));
        float t0 = m0, t1 = m1;
        #pragma unroll
        for (int i = 0; i < 8; i++) { t0 = fmaxf(t0, fmaxf(s[i][0], s[i][1])); t1 = fmaxf(t1, fmaxf(s[i][2], s[i][3])); }
        t0 = quad_max(t0); t1 = quad_max(t1);
        const float a0 = ex2((m0 - t0) * ss), a1 = ex2((m1 - t1) * ss);
        m0 = t0; m1 = t1;
        l0 *= a0; l1 *= a1;
        #pragma unroll
        for (int j = 0; j < 4; j++) { o[j][0] *= a0; o[j][1] *= a0; o[j][2] *= a1; o[j][3] *= a1; }
        #pragma unroll
        for (int k = 0; k < 4; k++) {
            uint32_t pf[4];
            #pragma unroll
            for (int e = 0; e < 2; e++) {
                const float p0 = ex2((s[2*k+e][0] - m0) * ss), p1 = ex2((s[2*k+e][1] - m0) * ss), p2 = ex2((s[2*k+e][2] - m1) * ss), p3 = ex2((s[2*k+e][3] - m1) * ss);
                l0 += p0 + p1; l1 += p2 + p3;
                pf[2*e] = pack_f16(p0, p1); pf[2*e+1] = pack_f16(p2, p3);
            }
            mma_f16(o[0], pf[0], pf[1], pf[2], pf[3], movm(vf[2*k].x), movm(vf[2*k+1].x));
            mma_f16(o[1], pf[0], pf[1], pf[2], pf[3], movm(vf[2*k].y), movm(vf[2*k+1].y));
            mma_f16(o[2], pf[0], pf[1], pf[2], pf[3], movm(vf[2*k].z), movm(vf[2*k+1].z));
            mma_f16(o[3], pf[0], pf[1], pf[2], pf[3], movm(vf[2*k].w), movm(vf[2*k+1].w));
        }
    }
    const float i0 = 16.f * rcp(quad_sum(l0)), i1 = 16.f * rcp(quad_sum(l1));
    uint32_t* dst = reinterpret_cast<uint32_t*>(reinterpret_cast<char*>(g_o) + (o_offset() & ~48u) + (unit * 64 * D_ + pass * 512) * 2) + t;
    #pragma unroll
    for (int j = 0; j < 4; j++) {
        const uint32_t iv = lds32(M_IVS + pass * 64 + j * 16 + t * 4);
        dst[j * 4] = pack_bf16(o[j][0] * i0 * bf_lo(iv), o[j][1] * i0 * bf_hi(iv));
        dst[j * 4 + 4 * D_] = pack_bf16(o[j][2] * i1 * bf_lo(iv), o[j][3] * i1 * bf_hi(iv));
    }
    __syncwarp();
    mbar_arrive_elect(lb + B_OD + (pass * 2 + (tid >> 7)) * 8);
}

__device__ __forceinline__ void load_gu(uint32_t (&f)[64], uint32_t src, int warp, int lane) {
    const uint32_t row = (warp & 3) * 64 + (lane >> 4) * 8 + (lane & 7), ch = (lane >> 3) & 1, sw = (lane >> 1) & 3;
    const uint32_t a0 = base32(src + (warp >> 2) * 32768 + row * 64 + ((ch ^ sw) << 4)), a1 = base32(a0 ^ 32);
    #pragma unroll
    for (int i = 0; i < 16; i++) ldsm4t(f[4*i], f[4*i+1], f[4*i+2], f[4*i+3], ((i & 1) ? a1 : a0) + ((i >> 1) & 1) * 16384 + (i >> 2) * 1024);
}

__device__ __forceinline__ void arrive_loaded(uint32_t bar, const uint32_t (&f)[64], uint32_t zero) {
    uint32_t x = 0;
    #pragma unroll
    for (int i = 0; i < 16; i++) x |= f[4 * i];
    mbar_arrive_elect(bar + (x & zero));
}
__device__ __forceinline__ void flush(uint32_t (&o2)[10], const uint32_t (&o)[10]) {
    #pragma unroll
    for (int i = 0; i < 10; i++) o2[i] = hadd2(o2[i], o[i]);
}
__device__ __forceinline__ void attention_phase(int L, uint32_t lb, int wg, uint32_t (&qa)[8], uint32_t (&qb)[8], uint32_t (&SA)[32], uint32_t (&SB_)[32], uint64_t dk0, uint64_t dv0, uint32_t ca, uint32_t (&wa)[64], uint32_t zero, uint32_t sixteen) {
    uint32_t PA[32], PB[32], oa[10], ob[10], oa2[10], ob2[10];
    Shift ha, hb;
    uint32_t fail = (lds32(M_SS) ? 3u : 0u) | (lds32(M_SS + 4) ? 12u : 0u);
    ca += base32(fail) >> 4;
    const uint32_t oo = o_offset(), odb = lb + B_OD + wg * 8;
    constexpr uint64_t SL = R_SLOT >> 4, KH = 4096 >> 4;
    uint64_t dkd = dk0 + ((A_KP - A_RING) >> 4);
    unit_start(SA, ha, oa2);
    exp_tile(SA, PA, ha, ca, sixteen);
    #pragma unroll
    for (int i = 0; i < 10; i++) { ob[i] = 0u; ob2[i] = 0u; }
    hb = ha;
    mbar_spin(lb + B_KS + 8, 0);
    mbar_spin(lb + B_ONE, 0);
    #pragma unroll 1
    for (int it = 0; ; it++) {
        const uint32_t ph = it & 1;
        uint32_t qsw = 0;
        #pragma unroll
        for (int u = 0; u < 4; u++) {
            const uint64_t dk = opaque(dk0) + u * SL, dv = opaque(dv0) + u * SL;
            wg_fence();
            if (u == 0) { wg_qk_acc(SB_, qb[4], qb[5], qb[6], qb[7], dkd + KH); wg_commit(); }
            if (u == 0) issue_pv<true>(oa, PA, dv); else issue_pv<false>(oa, PA, dv);
            wg_qk_init(SA, qa[0], qa[1], qa[2], qa[3], dk);
            wg_qk_acc(SA, qa[4], qa[5], qa[6], qa[7], dk + KH);
            wg_commit();
            wg_wait<1>();
            pin(SB_); pin(ob);
            if (u == 0) {
                mbar_arrive_elect_p(lb + B_AE + 24, it);
                flush(ob2, ob);
                if (__builtin_expect((it & 3) == 0, 0)) {
                    if (it) unit_end<0, 1>(ob2, hb.bad, odb, oo, fail);
                    unit_start(SB_, hb, ob2);
                }
            } else mbar_arrive_elect(lb + B_AE + 8 * (u - 1));
            if (u == 3) swap_q(qb, qsw ? qsw + 8192 : 0u);
            uint32_t ready = 0;
            if (u < 3) ready = mbar_test(lb + B_AF + 8 * (u + 1), ph);
            exp_tile(SB_, PB, hb, ca, sixteen);
            wg_fence();
            if (u == 0) issue_pv<true>(ob, PB, dv); else issue_pv<false>(ob, PB, dv);
            wg_qk_init(SB_, qb[0], qb[1], qb[2], qb[3], dk);
            if (u < 3) wg_qk_acc(SB_, qb[4], qb[5], qb[6], qb[7], dk + KH);
            wg_commit();
            if (u < 3) mbar_spin_unless(ready, lb + B_AF + 8 * (u + 1), ph);
            wg_wait<1>();
            pin(SA); pin(oa);
            if (u == 2) { qsw = it == 3 ? A_QX + tid_now() * 16 : 0u; swap_q(qa, qsw); }
            if (u == 3) {
                flush(oa2, oa);
                if (__builtin_expect((it & 3) == 3, 0)) {
                    TL(0, L * 32 + 7 + (it >> 2)); CK(0, L * 32 + 1 + (it >> 2));
                    if (it == 7) goto done;
                    unit_end<0, 0>(oa2, ha.bad, odb, oo, fail);
                    unit_start(SA, ha, oa2);
                }
            }
            exp_tile(SA, PA, ha, ca, sixteen);
        }
        mbar_spin(lb + B_AF, ph ^ 1);
        wg_wait<0>();
        dkd = dk0 + 3 * SL;
    }
done:
    mbar_spin(lb + B_GU, 0);
    load_gu(wa, F_GU0, tid_now() >> 5, tid_now() & 31);
    unit_end<1, 0>(oa2, ha.bad, odb, oo, fail);
    arrive_loaded(lb + B_FG, wa, zero);
    wg_wait<0>();
    pin(ob);
    mbar_arrive_elect(lb + B_AE + 24);
    flush(ob2, ob);
    unit_end<1, 1>(ob2, hb.bad, odb, oo, fail);
    if (__builtin_expect(fail != 0, 0)) {
        uint4* const qs = &g_qsave[cta_now()][0][tid_now()];
        qs[4 * 256] = make_uint4(qa[0], qa[1], qa[2], qa[3]); qs[5 * 256] = make_uint4(qa[4], qa[5], qa[6], qa[7]);
        qs[6 * 256] = make_uint4(qb[0], qb[1], qb[2], qb[3]); qs[7 * 256] = make_uint4(qb[4], qb[5], qb[6], qb[7]);
        #pragma unroll
        for (int i = 0; i < 16; i++) qs[(8 + i) * 256] = make_uint4(wa[4*i], wa[4*i+1], wa[4*i+2], wa[4*i+3]);
        #pragma unroll 1
        for (int r = 0; r < 4; r++)
            if ((fail >> r) & 1) attn_repair(__ldcg(qs + r * 512), __ldcg(qs + r * 512 + 256), lb, r >> 1, r & 1);
        #pragma unroll
        for (int i = 0; i < 16; i++) { const uint4 v = __ldcg(qs + (8 + i) * 256); wa[4*i] = v.x; wa[4*i+1] = v.y; wa[4*i+2] = v.z; wa[4*i+3] = v.w; }
    }
    TL(0, L * 32 + 9); CK(0, L * 32 + 8);
}

#define OSPLIT 8
__device__ __forceinline__ void oproj_steps(float (&acc)[64], uint32_t lb, int wg, int k0, int k1) {
    const bool leader = (tid_now() & 127) == 0;
    #pragma unroll 1
    for (int k = k0; k < k1; k++) {
        const uint32_t st = k & 3;
        mbar_spin(lb + B_OF + 8 * st, (k >> 2) & 1);
        const uint64_t da = desc_sw128(o_a(st) + wg * 8192, 16, 1024);
        const uint64_t db = desc_sw128(o_b(st), 8192, 1024);
        wg_fence();
        #pragma unroll
        for (int kk = 0; kk < 4; kk++) wg_gemm_n128(acc, da + kk * 2, db + kk * 128);
        wg_commit();
        wg_wait<1>();
        if (leader && k > 0) mbar_arrive(lb + B_OE + 8 * ((k - 1) & 3));
    }
}

__device__ __forceinline__ uint4 best_of(const uint4& e, int sh, int mask) {
    const uint32_t m = redux_max(e.x), row = redux_min(e.x == m ? e.w : 0x7FFFFFFFu), src = (row >> sh) & mask;
    return make_uint4(m, __shfl_sync(0xffffffffu, e.y, src), __shfl_sync(0xffffffffu, e.z, src), row);
}
__device__ __forceinline__ void load_wd(uint32_t (&wd)[64], uint32_t lb, int warp, int lane) {
    mbar_spin(lb + B_WD, 0);
    const uint32_t a0 = F_WD + warp * 8192 + ((lane >> 4) * 8 + (lane & 7)) * 128, ch = ((lane >> 3) & 1) ^ (lane & 7);
    #pragma unroll
    for (int i = 0; i < 16; i++) ldsm4t(wd[4*i], wd[4*i+1], wd[4*i+2], wd[4*i+3], base32(a0 + ((ch ^ (i & 6)) << 4)) + (i >> 3) * 4096 + (i & 1) * 2048);
}
__device__ __forceinline__ void stage_tile(const uint32_t (&xa)[4], const uint32_t (&xv)[32], uint32_t lb) {
    #pragma unroll
    for (int m = 0; m < 8; m++) stsm4(xa[m & 3] + (m < 4 ? 0 : XT1 - XT0), xv[4*m], xv[4*m+1], xv[4*m+2], xv[4*m+3]);
    fence_async_smem();
    __syncwarp();
    mbar_arrive_elect(lb + B_XS);
}

__device__ __forceinline__ void tail_phase(int L, uint32_t lb, int wg, const uint32_t (&wa)[64]) {
    const int c = cta_now(), blk = c >> 3, cb = c & 7, tid = tid_now();
    const int lane = tid & 31, w = (tid >> 5) & 3, g = lane >> 2, t = lane & 3;
    const int lr0 = wg * 64 + w * 16 + g;
    uint32_t xa[4];
    #pragma unroll
    for (int m = 0; m < 4; m++) xa[m] = base32(XT0 + (wg * 64 + w * 16 + (lane & 15)) * 128 + (((lane >> 4) ^ (lane & 7) ^ (2 * m)) << 4));
    uint32_t xv[32];
    const bool ffn = c < NFC;
    uint32_t wb[64], wd[64];
    float own[6];
    {
        float acc[64];
        #pragma unroll
        for (int i = 0; i < 64; i++) acc[i] = 0.f;
        pin(acc);
        float2 rs0 = make_float2(0.f, 0.f), rs1 = rs0;
        if (L) { rs0 = __ldcg(&g_x.rs1[blk * 128 + lr0]); rs1 = __ldcg(&g_x.rs1[blk * 128 + lr0 + 8]); }
        oproj_steps(acc, lb, wg, 0, OSPLIT);
        mbar_spin(lb + B_RES, 0);
        #pragma unroll
        for (int m = 0; m < 8; m++) ldsm4(xv[4*m], xv[4*m+1], xv[4*m+2], xv[4*m+3], xa[m & 3] + (m < 4 ? 0 : XT1 - XT0));
        if (L) {
            const int d = (int)lds32(M_RT + 12) - (blk * 128 + lr0);
            const Ln2 k0 = ln2_coef(rs0.y, d == 0 ? 0.f : rsq(rs0.x + LN_EPS)), k1 = ln2_coef(rs1.y, d == 8 ? 0.f : rsq(rs1.x + LN_EPS));
            #pragma unroll
            for (int j = 0; j < 16; j++) { xv[2*j] = add_ln2(xv[2*j], k0); xv[2*j+1] = add_ln2(xv[2*j+1], k1); }
        }
        pin(xv);
        oproj_steps(acc, lb, wg, OSPLIT, 16);
        uint32_t wv[16];
        #pragma unroll
        for (int i = 0; i < 4; i++) ldsm4(wv[4*i], wv[4*i+1], wv[4*i+2], wv[4*i+3], (lane & 1) ? M_RED + (lane >> 3) * 16 + i * 64 : M_RED + 256);
        wg_wait<0>();
        pin(acc);
        if ((tid & 127) == 0) mbar_arrive(lb + B_OE + 24);
        TL(0, L * 32 + 11); CK(0, L * 32 + 13);
        float sa[4] = {0.f, 0.f, 0.f, 0.f}, sb[4] = {0.f, 0.f, 0.f, 0.f}, sc[4] = {0.f, 0.f, 0.f, 0.f};
        float sd[4] = {0.f, 0.f, 0.f, 0.f}, se[4] = {0.f, 0.f, 0.f, 0.f};
        #pragma unroll
        for (int m = 0; m < 8; m++) {
            #pragma unroll
            for (int i = 0; i < 4; i++) xv[4*m+i] = badd2(xv[4*m+i], pack_bf16(acc[8*m + 2*i], acc[8*m + 2*i + 1]));
            mma_bf16(sa, xv[4*m], xv[4*m+1], xv[4*m+2], xv[4*m+3], wv[2*m], wv[2*m+1]);
            mma_bf16_k8(sb, xv[4*m], xv[4*m+1], xv[4*m]); mma_bf16_k8(sc, xv[4*m], xv[4*m+1], xv[4*m+1]);
            mma_bf16_k8(sd, xv[4*m+2], xv[4*m+3], xv[4*m+2]); mma_bf16_k8(se, xv[4*m+2], xv[4*m+3], xv[4*m+3]);
        }
        const float q0 = (g & 1) ? sb[1] + sd[1] : sb[0] + sd[0], q1 = (g & 1) ? sc[3] + se[3] : sc[2] + se[2];
        if (t == (g >> 1)) {
            st_x128(&g_x.part[L][blk][cb][lr0], __float_as_uint(sa[0]), __float_as_uint(q0), __float_as_uint(sa[1]), 0u);
            st_x128(&g_x.part[L][blk][cb][lr0 + 8], __float_as_uint(sa[2]), __float_as_uint(q1), __float_as_uint(sa[3]), 0u);
        }
        __syncwarp();
        own[0] = sa[0]; own[1] = __shfl_sync(0xffffffffu, q0, (lane & 28) + (g >> 1)); own[2] = sa[1];
        own[3] = sa[2]; own[4] = __shfl_sync(0xffffffffu, q1, (lane & 28) + (g >> 1)); own[5] = sa[3];
    }
    TL(0, L * 32 + 12);
    load_gu(wb, F_GU1, tid >> 5, lane);
    if (L == 0) stage_tile(xa, xv, lb);
    float mean[2], rstd[2], score[2];
    {
        const bool o0 = cb == 2 * t, o1 = cb == 2 * t + 1;
        const uint4* const psrc = &g_x.part[L][blk][2 * t][lr0];
        uint4 p[4];
        uint32_t n = 0;
        #pragma unroll 1
        do {
            p[0] = ld_x128(psrc); p[1] = ld_x128(psrc + 128); p[2] = ld_x128(psrc + 8); p[3] = ld_x128(psrc + 136);
            poll_tick(n);
        } while (warp_any((!o0 && (p[0].w | p[2].w) != 0) || (!o1 && (p[1].w | p[3].w) != 0)));
        const float ws = ldsf(M_WS);
        #pragma unroll
        for (int h = 0; h < 2; h++) {
            const float su = quad_sum((o0 ? own[3*h] : __uint_as_float(p[2*h].x)) + (o1 ? own[3*h] : __uint_as_float(p[2*h+1].x)));
            const float sq = quad_sum((o0 ? own[3*h+1] : __uint_as_float(p[2*h].y)) + (o1 ? own[3*h+1] : __uint_as_float(p[2*h+1].y)));
            const float sd = quad_sum((o0 ? own[3*h+2] : __uint_as_float(p[2*h].z)) + (o1 ? own[3*h+2] : __uint_as_float(p[2*h+1].z)));
            mean[h] = su * (1.f / D_);
            const float var = fmaxf(sq * (1.f / D_) - mean[h] * mean[h], 0.f);
            rstd[h] = rsq(var + LN_EPS);
            score[h] = rstd[h] * (sd - mean[h] * ws);
            if (L == 0 && cb == 0 && t == h) st_x64(&g_x.rs1[blk * 128 + lr0 + 8 * h], __float_as_uint(var), __float_as_uint(mean[h]));
        }
    }
    TL(0, L * 32 + 13);
    uint4 f;
    {
        const uint32_t k0 = order_bits(score[0]), k1 = order_bits(score[1]);
        const bool up = k1 > k0;
        const uint32_t kb = max(k0, k1), row = blk * 128 + lr0 + (up ? 8 : 0), m = redux_max(kb);
        if (redux_min(kb == m ? row : 0x7FFFFFFFu) == row && t == 0) sts128(M_SR + (tid >> 5) * 16, kb, __float_as_uint(up ? mean[1] : mean[0]), __float_as_uint(up ? rstd[1] : rstd[0]), row);
        named_sync(NB_CONS, 256);
        f = best_of(lds128(M_SR + (lane & 7) * 16), 4, 7);
        if (tid < 16) st_x128(&g_x.hdr[L][tid * 8 + cb][blk], f.x, f.y, f.z, f.w);
        const int d = (int)f.w - (blk * 128 + lr0);
        if ((d & ~8) == 0) {
            #pragma unroll
            for (int b = 0; b < 4; b++)
                st_x128(&g_x.cand[L][blk][cb * 64 + b * 16 + t * 4], d ? xv[8*b+1] : xv[8*b], d ? xv[8*b+3] : xv[8*b+2], d ? xv[8*b+5] : xv[8*b+4], d ? xv[8*b+7] : xv[8*b+6]);
        }
        __syncwarp();
    }
    TL(0, L * 32 + 28);
    if (L) {
        const Ln2 k0 = ln2_coef(mean[0], rstd[0]), k1 = ln2_coef(mean[1], rstd[1]);
        #pragma unroll
        for (int j = 0; j < 16; j++) { xv[2*j] = add_ln2(xv[2*j], k0); xv[2*j+1] = add_ln2(xv[2*j+1], k1); }
        stage_tile(xa, xv, lb);
    }
    load_wd(wd, lb, tid >> 5, lane);
    TL(0, L * 32 + 25);
    uint4 e;
    {
        uint32_t n = 0;
        #pragma unroll 1
        do { e = ld_x128(&g_x.hdr[L][c][lane & 15]); poll_tick(n); } while (warp_any(e.w == EMPTY && (lane & 15) != blk));
        if ((lane & 15) == blk) e = f;
        e = best_of(e, 7, 15);
    }
    TL(0, L * 32 + 14);
    if (tid == 0) sts128(M_RT + 16 * L, (e.x & 0x80000000u) ? e.x ^ 0x80000000u : ~e.x, e.y, e.z, e.w);
    if (ffn) {
        const uint32_t* src = &g_x.cand[L][e.w >> 7][(tid >> 5) * 32 + t * 4];
        const Ln2 kx = ln2_coef(__uint_as_float(e.y), __uint_as_float(e.z));
        uint4 x[4];
        uint32_t n = 0;
        #pragma unroll 1
        do {
            x[0] = ld_x128(src); x[1] = ld_x128(src + 16); x[2] = ld_x128(src + 256); x[3] = ld_x128(src + 272);
            poll_tick(n);
        } while (warp_any(x[0].x == EMPTY || x[1].x == EMPTY || x[2].x == EMPTY || x[3].x == EMPTY));
        TL(0, L * 32 + 15);
        float d[4][4];
        #pragma unroll
        for (int i = 0; i < 4; i++) { d[i][0] = 0.f; d[i][1] = 0.f; d[i][2] = 0.f; d[i][3] = 0.f; }
        #pragma unroll
        for (int k = 0; k < 8; k++) {
            const uint32_t b0 = ln2((k & 1) ? x[k >> 1].z : x[k >> 1].x, kx), b1 = ln2((k & 1) ? x[k >> 1].w : x[k >> 1].y, kx);
            const uint32_t* f = (k < 4 ? wa : wb) + (k & 3) * 16;
            #pragma unroll
            for (int i = 0; i < 4; i++) mma_bf16(d[i], f[4*i], f[4*i+1], f[4*i+2], f[4*i+3], b0, b1);
        }
        #pragma unroll
        for (int h = 0; h < 2; h++) {
            const float a = (t & 1) ? d[1][2*h] : d[0][2*h], b = (t & 1) ? d[3][2*h] : d[2][2*h];
            stsf(M_RED + ((tid >> 5) * 64 + t * 16 + h * 8 + g) * 4, (t & 2) ? b : a);
        }
        named_sync(NB_CONS, 256);
        TL(0, L * 32 + 16);
        float s0 = 0.f, s1 = 0.f;
        #pragma unroll
        for (int i = 0; i < 8; i++) { const float2 v = lds64f(base32(M_RED + lane * 8) + i * 256); s0 += v.x; s1 += v.y; }
        const uint32_t mine = pack_bf16(s0, s1), other = __shfl_xor_sync(0xffffffffu, mine, 16);
        const uint32_t gv = lane < 16 ? mine : other, uv = lane < 16 ? other : mine;
        const float g0 = bf_lo(gv), g1 = bf_hi(gv);
        const uint32_t hv = bmul2(pack_bf16(g0 * rcp(1.f + __expf(-g0)), g1 * rcp(1.f + __expf(-g1))), uv);
        uint32_t hb[4];
        #pragma unroll
        for (int i = 0; i < 4; i++) hb[i] = __shfl_sync(0xffffffffu, hv, 4 * i + t);
        float y[8][4];
        #pragma unroll
        for (int i = 0; i < 8; i++) {
            y[i][0] = 0.f; y[i][1] = 0.f; y[i][2] = 0.f; y[i][3] = 0.f;
            mma_bf16(y[i], wd[8*i], wd[8*i+1], wd[8*i+2], wd[8*i+3], hb[0], hb[1]);
            mma_bf16(y[i], wd[8*i+4], wd[8*i+5], wd[8*i+6], wd[8*i+7], hb[2], hb[3]);
        }
        float* dst = &g_x.ypart[L][(tid >> 5) * 16 + t * 4][c][g];
        #pragma unroll
        for (int i = 0; i < 2; i++)
            #pragma unroll
            for (int h = 0; h < 2; h++) {
                const float a = (t & 1) ? y[2 + i][2*h] : y[i][2*h], b = (t & 1) ? y[6 + i][2*h] : y[4 + i][2*h];
                st_x32(dst + (i * 2 + h) * (NFC * 8), __float_as_uint((t & 2) ? b : a));
            }
    }
    __syncwarp();
    mbar_arrive_elect(lb + B_FD);
    TL(0, L * 32 + 17);
}

__device__ __forceinline__ void qkv_load_w(const Maps& mp, uint32_t dst, int k, uint32_t fb) { tma_load3(dst, &mp.wqkv, (blockIdx.x & 15) * 64, k * 64, 0, fb); }
__device__ __forceinline__ void qkv_load_x(const CUtensorMap* tx, uint32_t sa, int k, uint32_t fb) {
    #pragma unroll
    for (int a = 0; a < 2; a++) tma_load(sa + a * 16384, tx, k * 64, (blockIdx.x >> 4) * 256 + a * 128, fb);
}
#define RESIT 0
__device__ __forceinline__ void producer_role(const Maps& mp) {
    const int c = blockIdx.x, mt = c >> 4, nt = c & 15, blk = c >> 3, cb = c & 7;
    const uint64_t pol = policy_evict_first();
    #pragma unroll 1
    for (int L = 0; L < 2; L++) {
        const uint32_t lb = M_BAR + L * BAR_SET;
        const CUtensorMap* tx = &mp.x[L];
        mbar_expect_tx(lb + B_SW, 49152);
        if (L == 0) {
            mbar_nap(lb + B_QF, 0);
            qkv_load_w(mp, SD_W, mt * 2, lb + B_SW);
            qkv_load_w(mp, SD_W + 24576, mt * 2 + 1, lb + B_SW);
        } else {
            mbar_nap(M_BAR + B_XS, 0);
            flags16_wait(g_x.x[0][mt]);
            fence_async_global();
            TL(256, 32);
        }
        {
            uint32_t st = 0, ph = L;
            #pragma unroll 1
            for (int k = L ? 0 : 3; k < 16; k++) {
                mbar_sleep(k == 1 ? M_BAR + B_FD : lb + B_QE + 8 * st, k == 1 ? 0 : ph);
                const uint32_t fb = lb + B_QF + 8 * st, sa = SB + st * Q_STB;
                mbar_expect_tx(fb, Q_STB);
                qkv_load_x(tx, sa, k, fb);
                qkv_load_w(mp, sa + Q_ABYTES, k, fb);
                if (L && k >= 3 && k < 7) tma_load(SD_W + (k - 3) * 12288, &mp.r, c * 24, (k - 3) * 256, lb + B_SW);
                if (++st == 3) { st = 0; ph ^= 1; }
            }
        }
        mbar_sleep(lb + B_QE, 1);
        TL(256, L * 32 + 26);
        mbar_arrive(lb + B_AF);
        {
            const char* kv = g_kv + (size_t)nt * 32 * KV_TILE;
            const uint8_t* fl = g_x.kv[L][nt * 2];
            #pragma unroll 1
            for (int j = 1; j < 4; j++) {
                flag_wait(fl + ((2 * mt + j + 1) & 15));
                fence_async_global();
                const uint32_t bytes = j == 1 ? 8192 : 16384;
                mbar_expect_tx(lb + B_AF + 8 * j, bytes);
                bulk_load(A_RING + j * R_SLOT, kv + ((2 * mt + j) & 15) * KV_TILE, bytes, lb + B_AF + 8 * j);
                if (j == 1) TL(256, L * 32 + 21);
            }
            flags16_wait(fl);
            fence_async_global();
            #pragma unroll 1
            for (int it = 1; it < 8; it++) {
                #pragma unroll
                for (int u = 0; u < 4; u++) {
                    const char* src = kv + ((2 * mt + 4 * it + u) & 15) * KV_TILE;
                    const uint32_t fb = lb + B_AF + 8 * u, dst = A_RING + u * R_SLOT;
                    mbar_nap(lb + B_AE + 8 * u, (it - 1) & 1);
                    mbar_expect_tx(fb, 16384);
                    if (u < 3) bulk_load(dst, src, 16384, fb);
                    else {
                        bulk_load(dst + 8192, src + 8192, 8192, fb);
                        if (it == 3) {
                            flags16_wait(fl + 128);
                            fence_async_global();
                            kv += 16 * KV_TILE; src += 16 * KV_TILE;
                        }
                        bulk_load(dst, src, 8192, fb);
                    }
                }
            }
        }
        #pragma unroll 1
        for (int it = 0; it < 4; it++) {
            #pragma unroll
            for (int s = 0; s < 4; s++) {
                mbar_spin(lb + (it ? B_OE + 8 * s : s < 2 ? B_AE + 8 + 8 * s : B_FG), it ? (it - 1) & 1 : s < 2);
                const uint32_t fb = lb + B_OF + 8 * s;
                mbar_expect_tx(fb, 32768);
                #pragma unroll
                for (int b = 0; b < 2; b++)
                    tma_load5(o_b(s) + b * 8192, &mp.wo[it >> 1], cb * 128 + b * 64, (it & 1) * 8 + s * 2, fb);
                if (s == 0 && !(it & 1)) {
                    ctr_wait(g_x.o[L][blk][it >> 1], 15);
                    fence_async_global();
                    TL(256, L * 32 + 10);
                }
                tma_load(o_a(s), &mp.o, it * 256 + s * 64, blk * 128, fb);
            }
            if (it == RESIT) {
                mbar_spin(lb + B_AE + 24, 1);
                mbar_expect_tx(lb + B_RES, 32768);
                tma_load_s(XT0, tx, cb * 128, blk * 128, lb + B_RES, pol);
                tma_load_s(XT1, tx, cb * 128 + 64, blk * 128, lb + B_RES, pol);
            }
        }
        if (c < NFC) {
            #pragma unroll 1
            for (int i = 0; i < 4; i++) {
                mbar_spin(lb + B_OE + 16 + 8 * (i >> 1), 1);
                tma_load3_s(F_WD + i * 16384, &mp.d, 0, c * 32, i * 4, lb + B_WD, pol);
            }
        }
    }
}

__global__ void __launch_bounds__(384, 1) k_all(const __grid_constant__ Maps mp, const bf16* __restrict__ x0, const bf16* __restrict__ wo, const bf16* __restrict__ w_down,
                                                const bf16* __restrict__ w_r, bf16* __restrict__ out, const uint64_t dk0, const uint64_t dv0, const uint32_t ca, const uint32_t zero, const uint32_t sixteen) {
    extern __shared__ __align__(1024) char smem[];
    if (smem_u32(smem) != SB) __trap();
    const int warp = warp_uniform(threadIdx.x >> 5), wg = warp >> 2;
    TL(0, 0);
    if (warp == 8) {
      if (elect_one()) {
        tm_prefetch(&mp.x[0]); tm_prefetch(&mp.wqkv);
        #pragma unroll
        for (int s = 0; s < 3; s++) { mbar_init(M_BAR + B_QF + 8 * s, 1); mbar_init(M_BAR + BAR_SET + B_QF + 8 * s, 1); }
        fence_mbar_init();
        #pragma unroll 1
        for (int s = 0; s < 3; s++) {
            const uint32_t sa = SB + s * Q_STB, fb = M_BAR + B_QF + 8 * s;
            mbar_expect_tx(fb, Q_STB);
            qkv_load_x(&mp.x[0], sa, s, fb);
            qkv_load_w(mp, sa + Q_ABYTES, s, fb);
        }
      }
      __syncwarp();
    } else if (warp > 8) {
        if (elect_one()) {
            const uint32_t o0 = warp == 9 ? B_AF : warp == 10 ? B_QE : B_AE, o1 = warp == 9 ? B_QE : warp == 10 ? B_AE : B_END, cnt = warp == 9 ? 1 : warp == 10 ? 2 : 8;
            #pragma unroll 1
            for (uint32_t o = o0; o < o1; o += 8) { const uint32_t n = o >= B_KS ? 4 : cnt; mbar_init(M_BAR + o, n); mbar_init(M_BAR + BAR_SET + o, n); }
            fence_mbar_init();
        }
        __syncwarp();
    }
    __syncthreads();
    if (wg == 2) {
        reg_dec<40>();
        if (warp > 8) side_role(mp, x0, wo, w_down, w_r, out);
        else if (elect_one()) producer_role(mp);
    } else {
        reg_inc<232>();
        #pragma unroll 1
        for (int L = 0; L < 2; L++)
        {
            const uint32_t lb = M_BAR + L * BAR_SET;
            uint32_t qa[8], qb[8], sa[32], sb[32], wa[64];
            qkv_phase(L, lb, wg, qa, qb, sa, sb);
            attention_phase(L, lb, wg, qa, qb, sa, sb, dk0, dv0, ca, wa, zero, sixteen);
            tail_phase(L, lb, wg, wa);
        }
    }
}

typedef CUresult (*EncodeFn)(CUtensorMap*, CUtensorMapDataType, cuuint32_t, void*, const cuuint64_t*, const cuuint64_t*, const cuuint32_t*,
                             const cuuint32_t*, CUtensorMapInterleave, CUtensorMapSwizzle, CUtensorMapL2promotion, CUtensorMapFloatOOBfill);

void make_map(EncodeFn enc, CUtensorMap* tm, const void* ptr, int rank, const cuuint64_t* dims, const cuuint64_t* strides, const cuuint32_t* box, CUtensorMapSwizzle sw) {
    const cuuint32_t es[5] = {1, 1, 1, 1, 1};
    enc(tm, CU_TENSOR_MAP_DATA_TYPE_BFLOAT16, rank, const_cast<void*>(ptr), dims, strides, box, es, CU_TENSOR_MAP_INTERLEAVE_NONE, sw,
        box[0] == 64 ? CU_TENSOR_MAP_L2_PROMOTION_L2_128B : CU_TENSOR_MAP_L2_PROMOTION_NONE, CU_TENSOR_MAP_FLOAT_OOB_FILL_NONE);
}
void make_map2(EncodeFn enc, CUtensorMap* tm, const void* ptr, uint64_t cols, uint64_t rows, uint32_t bc, uint32_t br, CUtensorMapSwizzle sw) {
    const cuuint64_t dims[2] = {cols, rows}, strides[1] = {cols * 2};
    const cuuint32_t box[2] = {bc, br};
    make_map(enc, tm, ptr, 2, dims, strides, box, sw);
}

}

extern "C" void kernel_launch(void* const* d_in, const int* in_sizes, int n_in, void* d_out, int out_size) {
    const bf16* x0 = (const bf16*)d_in[0];
    const bf16* wqkv = (const bf16*)d_in[1];
    const bf16* wo = (const bf16*)d_in[2];
    const bf16* w_r = (const bf16*)d_in[4];
    const bf16* w_gate = (const bf16*)d_in[5];
    const bf16* w_up = (const bf16*)d_in[6];
    const bf16* w_down = (const bf16*)d_in[7];

    EncodeFn enc = nullptr;
    cudaDriverEntryPointQueryResult qr;
    cudaGetDriverEntryPoint("cuTensorMapEncodeTiled", (void**)&enc, cudaEnableDefault, &qr);
    void *p_o, *p_x1;
    cudaGetSymbolAddress(&p_o, g_o); cudaGetSymbolAddress(&p_x1, g_x1);
    const CUtensorMapSwizzle S128 = CU_TENSOR_MAP_SWIZZLE_128B, S64 = CU_TENSOR_MAP_SWIZZLE_64B, S0 = CU_TENSOR_MAP_SWIZZLE_NONE;
    Maps mp;
    make_map2(enc, &mp.x[0], x0, D_, S_, 64, 128, S128); make_map2(enc, &mp.x[1], p_x1, D_, S_, 64, 128, S128);
    make_map2(enc, &mp.x[2], d_out, D_, S_, 64, 128, S128);
    make_map2(enc, &mp.o, p_o, D_, S_, 64, 128, S128);
    {
        const cuuint64_t dims[3] = {D_, D_, 3}, strides[2] = {3 * D_ * 2, D_ * 2};
        const cuuint32_t box[3] = {64, 64, 3};
        make_map(enc, &mp.wqkv, wqkv, 3, dims, strides, box, S128);
    }
    make_map2(enc, &mp.r, wqkv, 3 * D_, D_, 24, 256, S0);
    make_map2(enc, &mp.g, w_gate, FF, D_, 32, 256, S64); make_map2(enc, &mp.u, w_up, FF, D_, 32, 256, S64);
    for (int p = 0; p < 2; p++) {
        const cuuint64_t dims[5] = {D_, 2, 4, 4, 16}, strides[4] = {D_ * 2, 8 * D_ * 2, 2 * D_ * 2, 64 * D_ * 2};
        const cuuint32_t box[5] = {64, 2, 4, 4, 2};
        make_map(enc, &mp.wo[p], wo + (size_t)p * 32 * D_, 5, dims, strides, box, S128);
    }
    {
        const cuuint64_t dims[3] = {64, FF, 16}, strides[2] = {D_ * 2, 128};
        const cuuint32_t box[3] = {64, 32, 4};
        make_map(enc, &mp.d, w_down, 3, dims, strides, box, S128);
    }
    cudaFuncSetAttribute(k_all, cudaFuncAttributeMaxDynamicSharedMemorySize, K_SMEM);
    k_all<<<128, 384, K_SMEM, cudaStreamPerThread>>>(mp, x0, wo, w_down, w_r, (bf16*)d_out, desc_plain(A_RING, 2048, 128), desc_plain(A_RING + 8192, 128, 2048), 0x64A264A2u, 0u, 16u);
}
```

```cpp
#include <cuda_runtime.h>
#include <cuda_bf16.h>
#include <cuda_fp16.h>
#include <cuda.h>
#include <cudaTypedefs.h>
#include <stdint.h>

namespace {

typedef __nv_bfloat16 bf16;

constexpr int S_ = 2048, D_ = 1024, NH = 32, FF = 3584, NFC = FF / 32;
constexpr float LN_EPS = 1e-5f;
constexpr float QSCALE = 0.17677669529663687f * 1.4426950408889634f;
constexpr uint32_t EMPTY = 0xFFFFFFFFu;

constexpr int KV_TILE = 16384;
__device__ __align__(1024) char g_kv[NH * 16 * KV_TILE];
__device__ __align__(1024) bf16 g_o[S_ * D_];
__device__ __align__(1024) bf16 g_x1[S_ * D_];
__device__ __align__(16) float2 g_cs[8][3 * D_];
__device__ __align__(16) float2 g_rs0[S_];
__device__ uint4 g_qsave[128][24][256];
struct Xchg {
    uint4 part[2][16][8][128];
    float ypart[2][128][NFC][8];
    uint32_t cand[2][16][D_ / 2];
    uint4 hdr[2][128][16];
    float2 rs1[S_];
    float fix[3 * D_];
    uint32_t x2row[D_ / 2];
    uint8_t kv[2][NH][128];
    int o[2][16][2][32];
    uint8_t x[8][128];
};
constexpr int FILL = (sizeof(Xchg) / 128 + 127) / 128 * 8;
union XchgFill { Xchg x; uint4 fill[128][FILL]; };
static_assert(FILL > 768 && FILL <= 1024, "exchange area");
__device__ __align__(128) XchgFill g_u;
#define g_x g_u.x
__device__ int g_pctr;

constexpr uint32_t SMEM_BASE = 1024;

__device__ __forceinline__ int tid_now() { int v; asm volatile("mov.u32 %0, %%tid.x;" : "=r"(v)); return v; }
__device__ __forceinline__ int cta_now() { int v; asm volatile("mov.u32 %0, %%ctaid.x;" : "=r"(v)); return v; }
__device__ __forceinline__ uint64_t opaque(uint64_t v) { uint64_t r; asm volatile("mov.b64 %0, %1;" : "=l"(r) : "l"(v)); return r; }
__device__ __forceinline__ uint32_t base32(uint32_t v) { uint32_t r; asm("mov.b32 %0, %1;" : "=r"(r) : "r"(v)); return r; }
__device__ __forceinline__ uint32_t smem_u32(const void* p) { return (uint32_t)__cvta_generic_to_shared(p); }
__device__ __forceinline__ void mbar_init(uint32_t bar, int cnt) { asm volatile("mbarrier.init.shared::cta.b64 [%0], %1;" :: "r"(bar), "r"(cnt) : "memory"); }
__device__ __forceinline__ void mbar_expect_tx(uint32_t bar, uint32_t bytes) { asm volatile("mbarrier.arrive.expect_tx.shared::cta.b64 _, [%0], %1;" :: "r"(bar), "r"(bytes) : "memory"); }
__device__ __forceinline__ void mbar_arrive(uint32_t bar) { asm volatile("mbarrier.arrive.shared::cta.b64 _, [%0];" :: "r"(bar) : "memory"); }
__device__ __forceinline__ void mbar_sleep(uint32_t bar, uint32_t parity) {
    asm volatile("{\n.reg .pred p;\n.reg .u32 n;\nmov.u32 n, 0;\n"
                 "LAB_WAIT:\nmbarrier.try_wait.parity.shared::cta.b64 p, [%0], %1, 0x10000;\n@p bra LAB_DONE;\n"
                 "add.u32 n, n, 1;\nsetp.lt.u32 p, n, 0x10000;\n@p bra LAB_WAIT;\ntrap;\nLAB_DONE:\n}" :: "r"(bar), "r"(parity) : "memory");
}
__device__ __forceinline__ void mbar_nap(uint32_t bar, uint32_t parity) {
    asm volatile("{\n.reg .pred p;\nLAB_WAIT:\nmbarrier.try_wait.parity.shared::cta.b64 p, [%0], %1, 0x10000;\n@!p bra LAB_WAIT;\n}" :: "r"(bar), "r"(parity) : "memory");
}
__device__ __forceinline__ void mbar_spin(uint32_t bar, uint32_t parity) {
    asm volatile("{\n.reg .pred p;\nLAB_WAIT:\nmbarrier.try_wait.parity.shared::cta.b64 p, [%0], %1;\n@!p bra LAB_WAIT;\n}" :: "r"(bar), "r"(parity) : "memory");
}
__device__ __forceinline__ uint32_t mbar_test(uint32_t bar, uint32_t parity) {
    uint32_t ok;
    asm volatile("{\n.reg .pred p;\nmbarrier.test_wait.parity.shared::cta.b64 p, [%1], %2;\nselp.u32 %0, 1, 0, p;\n}" : "=r"(ok) : "r"(bar), "r"(parity) : "memory");
    return ok;
}
__device__ __forceinline__ void mbar_spin_unless(uint32_t ok, uint32_t bar, uint32_t parity) {
    asm volatile("{\n.reg .pred p;\nsetp.ne.u32 p, %2, 0;\n@p bra LAB_DONE;\nLAB_WAIT:\nmbarrier.try_wait.parity.shared::cta.b64 p, [%0], %1;\n@!p bra LAB_WAIT;\nLAB_DONE:\n}"
                 :: "r"(bar), "r"(parity), "r"(ok) : "memory");
}
__device__ __forceinline__ bool elect_one() {
    uint32_t r;
    asm volatile("{\n.reg .pred p;\nelect.sync _|p, 0xffffffff;\nselp.u32 %0, 1, 0, p;\n}" : "=r"(r));
    return r != 0;
}
__device__ __forceinline__ void mbar_arrive_elect(uint32_t bar) {
    asm volatile("{\n.reg .pred p;\nelect.sync _|p, 0xffffffff;\n@p mbarrier.arrive.shared::cta.b64 _, [%0];\n}" :: "r"(bar) : "memory");
}
__device__ __forceinline__ void mbar_arrive_elect_p(uint32_t bar, uint32_t on) {
    asm volatile("{\n.reg .pred p, q;\nelect.sync _|p, 0xffffffff;\nsetp.ne.and.u32 q, %1, 0, p;\n@q mbarrier.arrive.shared::cta.b64 _, [%0];\n}" :: "r"(bar), "r"(on) : "memory");
}
__device__ __forceinline__ int warp_uniform(int v) { return __shfl_sync(0xffffffffu, v, 0); }
__device__ __forceinline__ void fence_mbar_init() { asm volatile("fence.mbarrier_init.release.cluster;" ::: "memory"); }
__device__ __forceinline__ void fence_async_smem() { asm volatile("fence.proxy.async.shared::cta;" ::: "memory"); }
__device__ __forceinline__ void fence_async_global() { asm volatile("fence.proxy.async.global;" ::: "memory"); }
__device__ __forceinline__ void named_sync(int id, int n) { asm volatile("bar.sync %0, %1;" :: "r"(id), "r"(n) : "memory"); }
__device__ __forceinline__ void named_arrive(int id, int n) { asm volatile("bar.arrive %0, %1;" :: "r"(id), "r"(n) : "memory"); }
__device__ __forceinline__ void bulk_load(uint32_t dst, const void* src, uint32_t bytes, uint32_t bar) {
    asm volatile("cp.async.bulk.shared::cluster.global.mbarrier::complete_tx::bytes [%0], [%1], %2, [%3];" :: "r"(dst), "l"(src), "r"(bytes), "r"(bar) : "memory");
}
__device__ __forceinline__ void bulk_store(void* dst, uint32_t src, uint32_t bytes) {
    asm volatile("cp.async.bulk.global.shared::cta.bulk_group [%0], [%1], %2;" :: "l"(dst), "r"(src), "r"(bytes) : "memory");
}
__device__ __forceinline__ void bulk_commit() { asm volatile("cp.async.bulk.commit_group;" ::: "memory"); }
__device__ __forceinline__ void bulk_wait() { asm volatile("cp.async.bulk.wait_group 0;" ::: "memory"); }
__device__ __forceinline__ void l2_prefetch(const void* src, uint32_t bytes) {
    asm volatile("cp.async.bulk.prefetch.L2.global [%0], %1;" :: "l"(src), "r"(bytes) : "memory");
}
__device__ __forceinline__ void tma_load(uint32_t dst, const CUtensorMap* tm, int c0, int c1, uint32_t bar) {
    asm volatile("cp.async.bulk.tensor.2d.shared::cluster.global.mbarrier::complete_tx::bytes [%0], [%1, {%3, %4}], [%2];"
                 :: "r"(dst), "l"(tm), "r"(bar), "r"(c0), "r"(c1) : "memory");
}
__device__ __forceinline__ void tma_load3(uint32_t dst, const CUtensorMap* tm, int c0, int c1, int c2, uint32_t bar) {
    asm volatile("cp.async.bulk.tensor.3d.shared::cluster.global.mbarrier::complete_tx::bytes [%0], [%1, {%3, %4, %5}], [%2];"
                 :: "r"(dst), "l"(tm), "r"(bar), "r"(c0), "r"(c1), "r"(c2) : "memory");
}
__device__ __forceinline__ void tma_load5(uint32_t dst, const CUtensorMap* tm, int c0, int c4, uint32_t bar) {
    asm volatile("cp.async.bulk.tensor.5d.shared::cluster.global.mbarrier::complete_tx::bytes [%0], [%1, {%3, %5, %5, %5, %4}], [%2];"
                 :: "r"(dst), "l"(tm), "r"(bar), "r"(c0), "r"(c4), "r"(0) : "memory");
}
__device__ __forceinline__ uint64_t policy_evict_first() { uint64_t p; asm volatile("createpolicy.fractional.L2::evict_first.b64 %0, 1.0;" : "=l"(p)); return p; }
__device__ __forceinline__ void tma_load_s(uint32_t dst, const CUtensorMap* tm, int c0, int c1, uint32_t bar, uint64_t pol) {
    asm volatile("cp.async.bulk.tensor.2d.shared::cluster.global.mbarrier::complete_tx::bytes.L2::cache_hint [%0], [%1, {%3, %4}], [%2], %5;"
                 :: "r"(dst), "l"(tm), "r"(bar), "r"(c0), "r"(c1), "l"(pol) : "memory");
}
__device__ __forceinline__ void tma_load3_s(uint32_t dst, const CUtensorMap* tm, int c0, int c1, int c2, uint32_t bar, uint64_t pol) {
    asm volatile("cp.async.bulk.tensor.3d.shared::cluster.global.mbarrier::complete_tx::bytes.L2::cache_hint [%0], [%1, {%3, %4, %5}], [%2], %6;"
                 :: "r"(dst), "l"(tm), "r"(bar), "r"(c0), "r"(c1), "r"(c2), "l"(pol) : "memory");
}
__device__ __forceinline__ void tma_store(const CUtensorMap* tm, uint32_t src, int c0, int c1) {
    asm volatile("cp.async.bulk.tensor.2d.global.shared::cta.bulk_group [%0, {%2, %3}], [%1];" :: "l"(tm), "r"(src), "r"(c0), "r"(c1) : "memory");
}
__device__ __forceinline__ void tma_prefetch(const CUtensorMap* tm, int c0, int c1) {
    asm volatile("cp.async.bulk.prefetch.tensor.2d.L2.global [%0, {%1, %2}];" :: "l"(tm), "r"(c0), "r"(c1) : "memory");
}
__device__ __forceinline__ void tm_prefetch(const CUtensorMap* tm) { asm volatile("prefetch.tensormap [%0];" :: "l"(tm) : "memory"); }
__device__ __forceinline__ void wg_fence() { asm volatile("wgmma.fence.sync.aligned;" ::: "memory"); }
__device__ __forceinline__ void wg_commit() { asm volatile("wgmma.commit_group.sync.aligned;" ::: "memory"); }
template <int N> __device__ __forceinline__ void wg_wait() { asm volatile("wgmma.wait_group.sync.aligned %0;" :: "n"(N) : "memory"); }
template <int N> __device__ __forceinline__ void pin(uint32_t (&r)[N]) {
    #pragma unroll
    for (int i = 0; i < N; i++) asm volatile("" : "+r"(r[i]) :: "memory");
}
template <int N> __device__ __forceinline__ void pin(float (&r)[N]) {
    #pragma unroll
    for (int i = 0; i < N; i++) asm volatile("" : "+f"(r[i]) :: "memory");
}
template <int N> __device__ __forceinline__ void reg_inc() { asm volatile("setmaxnreg.inc.sync.aligned.u32 %0;" :: "n"(N)); }
template <int N> __device__ __forceinline__ void reg_dec() { asm volatile("setmaxnreg.dec.sync.aligned.u32 %0;" :: "n"(N)); }
__host__ __device__ constexpr uint64_t desc_plain(uint32_t addr, uint32_t lbo, uint32_t sbo) {
    return (uint64_t)((addr & 0x3FFFF) >> 4) | ((uint64_t)(lbo >> 4) << 16) | ((uint64_t)(sbo >> 4) << 32);
}
__host__ __device__ constexpr uint64_t desc_sw128(uint32_t addr, uint32_t lbo, uint32_t sbo) { return desc_plain(addr, lbo, sbo) | (1ull << 62); }
__host__ __device__ constexpr uint64_t desc_sw64(uint32_t addr, uint32_t lbo, uint32_t sbo) { return desc_plain(addr, lbo, sbo) | (2ull << 62); }

__device__ __forceinline__ uint32_t lds32(uint32_t a) { uint32_t v; asm volatile("ld.shared.b32 %0, [%1];" : "=r"(v) : "r"(a) : "memory"); return v; }
__device__ __forceinline__ uint32_t lds16(uint32_t a) { uint32_t v; asm volatile("ld.shared.u16 %0, [%1];" : "=r"(v) : "r"(a) : "memory"); return v; }
__device__ __forceinline__ float ldsf(uint32_t a) { return __uint_as_float(lds32(a)); }
__device__ __forceinline__ float2 lds64f(uint32_t a) { float2 v; asm volatile("ld.shared.v2.f32 {%0, %1}, [%2];" : "=f"(v.x), "=f"(v.y) : "r"(a) : "memory"); return v; }
__device__ __forceinline__ uint4 lds128(uint32_t a) { uint4 v; asm volatile("ld.shared.v4.b32 {%0, %1, %2, %3}, [%4];" : "=r"(v.x), "=r"(v.y), "=r"(v.z), "=r"(v.w) : "r"(a) : "memory"); return v; }
__device__ __forceinline__ void sts16(uint32_t a, uint32_t v) { asm volatile("st.shared.b16 [%0], %1;" :: "r"(a), "h"((uint16_t)v) : "memory"); }
__device__ __forceinline__ void sts32(uint32_t a, uint32_t v) { asm volatile("st.shared.b32 [%0], %1;" :: "r"(a), "r"(v) : "memory"); }
__device__ __forceinline__ void stsf(uint32_t a, float v) { sts32(a, __float_as_uint(v)); }
__device__ __forceinline__ void sts64(uint32_t a, uint32_t x, uint32_t y) { asm volatile("st.shared.v2.b32 [%0], {%1, %2};" :: "r"(a), "r"(x), "r"(y) : "memory"); }
__device__ __forceinline__ void sts128(uint32_t a, uint32_t x, uint32_t y, uint32_t z, uint32_t w) { asm volatile("st.shared.v4.b32 [%0], {%1, %2, %3, %4};" :: "r"(a), "r"(x), "r"(y), "r"(z), "r"(w) : "memory"); }
__device__ __forceinline__ void stsm4(uint32_t a, uint32_t x, uint32_t y, uint32_t z, uint32_t w) {
    asm volatile("stmatrix.sync.aligned.m8n8.x4.shared.b16 [%0], {%1, %2, %3, %4};" :: "r"(a), "r"(x), "r"(y), "r"(z), "r"(w) : "memory");
}
__device__ __forceinline__ void ldsm4(uint32_t& a0, uint32_t& a1, uint32_t& a2, uint32_t& a3, uint32_t addr) {
    asm volatile("ldmatrix.sync.aligned.m8n8.x4.shared.b16 {%0,%1,%2,%3}, [%4];" : "=r"(a0), "=r"(a1), "=r"(a2), "=r"(a3) : "r"(addr) : "memory");
}
__device__ __forceinline__ void ldsm4t(uint32_t& a0, uint32_t& a1, uint32_t& a2, uint32_t& a3, uint32_t addr) {
    asm volatile("ldmatrix.sync.aligned.m8n8.x4.trans.shared.b16 {%0,%1,%2,%3}, [%4];" : "=r"(a0), "=r"(a1), "=r"(a2), "=r"(a3) : "r"(addr) : "memory");
}
__device__ __forceinline__ void mma_bf16(float (&d)[4], uint32_t a0, uint32_t a1, uint32_t a2, uint32_t a3, uint32_t b0, uint32_t b1) {
    asm("mma.sync.aligned.m16n8k16.row.col.f32.bf16.bf16.f32 {%0,%1,%2,%3}, {%4,%5,%6,%7}, {%8,%9}, {%0,%1,%2,%3};"
        : "+f"(d[0]), "+f"(d[1]), "+f"(d[2]), "+f"(d[3]) : "r"(a0), "r"(a1), "r"(a2), "r"(a3), "r"(b0), "r"(b1));
}
__device__ __forceinline__ void mma_bf16_k8(float (&d)[4], uint32_t a0, uint32_t a1, uint32_t b0) {
    asm("mma.sync.aligned.m16n8k8.row.col.f32.bf16.bf16.f32 {%0,%1,%2,%3}, {%4,%5}, {%6}, {%0,%1,%2,%3};"
        : "+f"(d[0]), "+f"(d[1]), "+f"(d[2]), "+f"(d[3]) : "r"(a0), "r"(a1), "r"(b0));
}
__device__ __forceinline__ void mma_f16(float (&d)[4], uint32_t a0, uint32_t a1, uint32_t a2, uint32_t a3, uint32_t b0, uint32_t b1) {
    asm("mma.sync.aligned.m16n8k16.row.col.f32.f16.f16.f32 {%0,%1,%2,%3}, {%4,%5,%6,%7}, {%8,%9}, {%0,%1,%2,%3};"
        : "+f"(d[0]), "+f"(d[1]), "+f"(d[2]), "+f"(d[3]) : "r"(a0), "r"(a1), "r"(a2), "r"(a3), "r"(b0), "r"(b1));
}
__device__ __forceinline__ void stg128_pred(void* p, const uint4& v, bool on) {
    asm volatile("{\n.reg .pred q;\nsetp.ne.u32 q, %5, 0;\n@q st.global.v4.b32 [%0], {%1, %2, %3, %4};\n}"
                 :: "l"(p), "r"(v.x), "r"(v.y), "r"(v.z), "r"(v.w), "r"((uint32_t)on) : "memory");
}
__device__ __forceinline__ void st_x32(void* p, uint32_t v) { asm volatile("st.relaxed.gpu.global.u32 [%0], %1;" :: "l"(p), "r"(v) : "memory"); }
__device__ __forceinline__ void st_x64(void* p, uint32_t x, uint32_t y) {
    asm volatile("{\n.reg .b64 v;\nmov.b64 v, {%1, %2};\nst.relaxed.gpu.global.b64 [%0], v;\n}" :: "l"(p), "r"(x), "r"(y) : "memory");
}
__device__ __forceinline__ void st_x128(void* p, uint32_t x, uint32_t y, uint32_t z, uint32_t w) {
    asm volatile("{\n.reg .b64 a, b;\n.reg .b128 v;\nmov.b64 a, {%1, %2};\nmov.b64 b, {%3, %4};\nmov.b128 v, {a, b};\nst.relaxed.gpu.global.b128 [%0], v;\n}"
                 :: "l"(p), "r"(x), "r"(y), "r"(z), "r"(w) : "memory");
}
__device__ __forceinline__ uint32_t ld_x32(const void* p) { uint32_t v; asm volatile("ld.relaxed.gpu.global.u32 %0, [%1];" : "=r"(v) : "l"(p) : "memory"); return v; }
__device__ __forceinline__ uint2 ld_x64(const void* p) {
    uint2 v; asm volatile("{\n.reg .b64 a;\nld.relaxed.gpu.global.b64 a, [%2];\nmov.b64 {%0, %1}, a;\n}" : "=r"(v.x), "=r"(v.y) : "l"(p) : "memory"); return v;
}
__device__ __forceinline__ uint4 ld_x128(const void* p) {
    uint4 v;
    asm volatile("{\n.reg .b64 a, b;\n.reg .b128 v;\nld.relaxed.gpu.global.b128 v, [%4];\nmov.b128 {a, b}, v;\nmov.b64 {%0, %1}, a;\nmov.b64 {%2, %3}, b;\n}"
                 : "=r"(v.x), "=r"(v.y), "=r"(v.z), "=r"(v.w) : "l"(p) : "memory");
    return v;
}
__device__ __forceinline__ void poll_tick(uint32_t& n) { asm volatile("{\n.reg .pred p;\nadd.u32 %0, %0, 1;\nsetp.ge.u32 p, %0, 0x800000;\n@p st.global.u32 [%1], %0;\n}" : "+r"(n) : "l"(0ull)); }
__device__ __forceinline__ void ctr_arrive(int* c) { asm volatile("red.release.gpu.global.add.s32 [%0], 1;" :: "l"(c) : "memory"); }
__device__ __forceinline__ void ctr_wait(const int* c, int target) {
    int v;
    uint32_t n = 0;
    #pragma unroll 1
    do {
        asm volatile("ld.acquire.gpu.global.s32 %0, [%1];" : "=r"(v) : "l"(c) : "memory");
        poll_tick(n);
    } while (v < target);
}
__device__ __forceinline__ void flag_wait(const uint8_t* f) {
    uint32_t n = 0, v;
    #pragma unroll 1
    do { asm volatile("ld.acquire.gpu.global.u8 %0, [%1];" : "=r"(v) : "l"(f) : "memory"); poll_tick(n); } while (v);
}
__device__ __forceinline__ void flags16_wait(const uint8_t* f) {
    uint32_t n = 0;
    uint64_t v;
    #pragma unroll 1
    do {
        asm volatile("{\n.reg .b64 a, b;\n.reg .b128 v;\nld.acquire.gpu.global.b128 v, [%1];\nmov.b128 {a, b}, v;\nor.b64 %0, a, b;\n}" : "=l"(v) : "l"(f) : "memory");
        poll_tick(n);
    } while (v != 0);
}
__device__ __forceinline__ bool any_empty(const uint4& v) { return v.x == EMPTY || v.y == EMPTY || v.z == EMPTY || v.w == EMPTY; }
__device__ __forceinline__ bool warp_any(bool p) { return __any_sync(0xffffffffu, p); }

__device__ __forceinline__ float ex2(float x) { float y; asm("ex2.approx.ftz.f32 %0, %1;" : "=f"(y) : "f"(x)); return y; }
__device__ __forceinline__ float rsq(float x) { float y; asm("rsqrt.approx.ftz.f32 %0, %1;" : "=f"(y) : "f"(x)); return y; }
__device__ __forceinline__ float rcp(float x) { float y; asm("rcp.approx.ftz.f32 %0, %1;" : "=f"(y) : "f"(x)); return y; }
__device__ __forceinline__ uint32_t pack_bf16(float lo, float hi) { uint32_t r; asm("cvt.rn.bf16x2.f32 %0, %1, %2;" : "=r"(r) : "f"(hi), "f"(lo)); return r; }
__device__ __forceinline__ uint32_t pack_f16(float lo, float hi) { uint32_t r; asm("cvt.rn.f16x2.f32 %0, %1, %2;" : "=r"(r) : "f"(hi), "f"(lo)); return r; }
__device__ __forceinline__ float bf_lo(uint32_t v) { return __uint_as_float(v << 16); }
__device__ __forceinline__ float bf_hi(uint32_t v) { return __uint_as_float(v & 0xFFFF0000u); }
__device__ __forceinline__ float bf_round(float x) { return __uint_as_float(pack_bf16(0.f, x)); }
__device__ __forceinline__ void h2_unpack(uint32_t v, float& lo, float& hi) {
    asm("{.reg .f16 l, h; mov.b32 {l, h}, %2; cvt.f32.f16 %0, l; cvt.f32.f16 %1, h;}" : "=f"(lo), "=f"(hi) : "r"(v));
}
__device__ __forceinline__ uint32_t hadd2(uint32_t a, uint32_t b) { uint32_t r; asm("add.rn.f16x2 %0, %1, %2;" : "=r"(r) : "r"(a), "r"(b)); return r; }
__device__ __forceinline__ uint32_t hmax2(uint32_t a, uint32_t b) { uint32_t r; asm("max.f16x2 %0, %1, %2;" : "=r"(r) : "r"(a), "r"(b)); return r; }
__device__ __forceinline__ uint32_t badd2(uint32_t a, uint32_t b) { uint32_t r; asm("add.rn.bf16x2 %0, %1, %2;" : "=r"(r) : "r"(a), "r"(b)); return r; }
__device__ __forceinline__ uint32_t bmul2(uint32_t a, uint32_t b) { uint32_t r; asm("mul.rn.bf16x2 %0, %1, %2;" : "=r"(r) : "r"(a), "r"(b)); return r; }
__device__ __forceinline__ float warp_sum(float v) {
    #pragma unroll
    for (int o = 16; o > 0; o >>= 1) v += __shfl_xor_sync(0xffffffffu, v, o);
    return v;
}
__device__ __forceinline__ float quad_sum(float v) { v += __shfl_xor_sync(0xffffffffu, v, 1); return v + __shfl_xor_sync(0xffffffffu, v, 2); }
__device__ __forceinline__ float quad_max(float v) { v = fmaxf(v, __shfl_xor_sync(0xffffffffu, v, 1)); return fmaxf(v, __shfl_xor_sync(0xffffffffu, v, 2)); }
__device__ __forceinline__ uint32_t redux_max(uint32_t v) { uint32_t r; asm volatile("redux.sync.max.u32 %0, %1, 0xffffffff;" : "=r"(r) : "r"(v)); return r; }
__device__ __forceinline__ uint32_t redux_min(uint32_t v) { uint32_t r; asm volatile("redux.sync.min.u32 %0, %1, 0xffffffff;" : "=r"(r) : "r"(v)); return r; }
__device__ __forceinline__ uint32_t order_bits(float r) { const uint32_t u = __float_as_uint(r); return (u & 0x80000000u) ? ~u : (u | 0x80000000u); }
struct Ln2 { uint32_t nm, rh, rl, c; };
__device__ __forceinline__ Ln2 ln2_coef(float mean, float rstd) {
    const uint32_t a = pack_bf16(-mean, rstd), b = pack_bf16((-mean - bf_lo(a)) * rstd, rstd - bf_hi(a));
    return {__byte_perm(a, 0, 0x1010), __byte_perm(a, 0, 0x3232), __byte_perm(b, 0, 0x3232), __byte_perm(b, 0, 0x1010)};
}
__device__ __forceinline__ uint32_t bfma2(uint32_t a, uint32_t b, uint32_t c) { uint32_t r; asm("fma.rn.bf16x2 %0, %1, %2, %3;" : "=r"(r) : "r"(a), "r"(b), "r"(c)); return r; }
__device__ __forceinline__ uint32_t ln2(uint32_t v, const Ln2& k) { const uint32_t d = badd2(v, k.nm); return bfma2(d, k.rh, bfma2(d, k.rl, k.c)); }
__device__ __forceinline__ uint32_t add_ln2(uint32_t v, const Ln2& k) { return badd2(v, ln2(v, k)); }

#define TL(TID, i)
#define CK(TID, i)

__device__ __forceinline__ void wg_gemm_n128(float (&d)[64], uint64_t desca, uint64_t desc) {
    asm volatile("{\n.reg .pred p;\nsetp.ne.b32 p, 1, 0;\n"
        "wgmma.mma_async.sync.aligned.m64n128k16.f32.bf16.bf16 "
        "{%0,%1,%2,%3,%4,%5,%6,%7,%8,%9,%10,%11,%12,%13,%14,%15,%16,%17,%18,%19,%20,%21,%22,%23,%24,%25,%26,%27,%28,%29,%30,%31,%32,%33,%34,%35,%36,%37,%38,%39,%40,%41,%42,%43,%44,%45,%46,%47,%48,%49,%50,%51,%52,%53,%54,%55,%56,%57,%58,%59,%60,%61,%62,%63}, "
        "%64, %65, p, 1, 1, 0, 1;\n}\n"
        : "+f"(d[0]), "+f"(d[1]), "+f"(d[2]), "+f"(d[3]), "+f"(d[4]), "+f"(d[5]), "+f"(d[6]), "+f"(d[7]), "+f"(d[8]), "+f"(d[9]), "+f"(d[10]), "+f"(d[11]),
          "+f"(d[12]), "+f"(d[13]), "+f"(d[14]), "+f"(d[15]), "+f"(d[16]), "+f"(d[17]), "+f"(d[18]), "+f"(d[19]), "+f"(d[20]), "+f"(d[21]), "+f"(d[22]), "+f"(d[23]),
          "+f"(d[24]), "+f"(d[25]), "+f"(d[26]), "+f"(d[27]), "+f"(d[28]), "+f"(d[29]), "+f"(d[30]), "+f"(d[31]), "+f"(d[32]), "+f"(d[33]), "+f"(d[34]), "+f"(d[35]),
          "+f"(d[36]), "+f"(d[37]), "+f"(d[38]), "+f"(d[39]), "+f"(d[40]), "+f"(d[41]), "+f"(d[42]), "+f"(d[43]), "+f"(d[44]), "+f"(d[45]), "+f"(d[46]), "+f"(d[47]),
          "+f"(d[48]), "+f"(d[49]), "+f"(d[50]), "+f"(d[51]), "+f"(d[52]), "+f"(d[53]), "+f"(d[54]), "+f"(d[55]), "+f"(d[56]), "+f"(d[57]), "+f"(d[58]), "+f"(d[59]),
          "+f"(d[60]), "+f"(d[61]), "+f"(d[62]), "+f"(d[63])
        : "l"(desca), "l"(desc));
}
__device__ __forceinline__ void wg_gemm_n192(float (&d)[96], uint64_t desca, uint64_t desc) {
    asm volatile("{\n.reg .pred p;\nsetp.ne.b32 p, 1, 0;\n"
        "wgmma.mma_async.sync.aligned.m64n192k16.f32.bf16.bf16 "
        "{%0,%1,%2,%3,%4,%5,%6,%7,%8,%9,%10,%11,%12,%13,%14,%15,%16,%17,%18,%19,%20,%21,%22,%23,%24,%25,%26,%27,%28,%29,%30,%31,%32,%33,%34,%35,%36,%37,%38,%39,%40,%41,%42,%43,%44,%45,%46,%47,%48,%49,%50,%51,%52,%53,%54,%55,%56,%57,%58,%59,%60,%61,%62,%63,%64,%65,%66,%67,%68,%69,%70,%71,%72,%73,%74,%75,%76,%77,%78,%79,%80,%81,%82,%83,%84,%85,%86,%87,%88,%89,%90,%91,%92,%93,%94,%95}, "
        "%96, %97, p, 1, 1, 0, 1;\n}\n"
        : "+f"(d[0]), "+f"(d[1]), "+f"(d[2]), "+f"(d[3]), "+f"(d[4]), "+f"(d[5]), "+f"(d[6]), "+f"(d[7]), "+f"(d[8]), "+f"(d[9]), "+f"(d[10]), "+f"(d[11]),
          "+f"(d[12]), "+f"(d[13]), "+f"(d[14]), "+f"(d[15]), "+f"(d[16]), "+f"(d[17]), "+f"(d[18]), "+f"(d[19]), "+f"(d[20]), "+f"(d[21]), "+f"(d[22]), "+f"(d[23]),
          "+f"(d[24]), "+f"(d[25]), "+f"(d[26]), "+f"(d[27]), "+f"(d[28]), "+f"(d[29]), "+f"(d[30]), "+f"(d[31]), "+f"(d[32]), "+f"(d[33]), "+f"(d[34]), "+f"(d[35]),
          "+f"(d[36]), "+f"(d[37]), "+f"(d[38]), "+f"(d[39]), "+f"(d[40]), "+f"(d[41]), "+f"(d[42]), "+f"(d[43]), "+f"(d[44]), "+f"(d[45]), "+f"(d[46]), "+f"(d[47]),
          "+f"(d[48]), "+f"(d[49]), "+f"(d[50]), "+f"(d[51]), "+f"(d[52]), "+f"(d[53]), "+f"(d[54]), "+f"(d[55]), "+f"(d[56]), "+f"(d[57]), "+f"(d[58]), "+f"(d[59]),
          "+f"(d[60]), "+f"(d[61]), "+f"(d[62]), "+f"(d[63]), "+f"(d[64]), "+f"(d[65]), "+f"(d[66]), "+f"(d[67]), "+f"(d[68]), "+f"(d[69]), "+f"(d[70]), "+f"(d[71]),
          "+f"(d[72]), "+f"(d[73]), "+f"(d[74]), "+f"(d[75]), "+f"(d[76]), "+f"(d[77]), "+f"(d[78]), "+f"(d[79]), "+f"(d[80]), "+f"(d[81]), "+f"(d[82]), "+f"(d[83]),
          "+f"(d[84]), "+f"(d[85]), "+f"(d[86]), "+f"(d[87]), "+f"(d[88]), "+f"(d[89]), "+f"(d[90]), "+f"(d[91]), "+f"(d[92]), "+f"(d[93]), "+f"(d[94]), "+f"(d[95])
        : "l"(desca), "l"(desc));
}
__device__ __forceinline__ void wg_gemm_n192_init(float (&d)[96], uint64_t desca, uint64_t desc) {
    asm volatile("{\n.reg .pred p;\nsetp.ne.b32 p, 0, 0;\n"
        "wgmma.mma_async.sync.aligned.m64n192k16.f32.bf16.bf16 "
        "{%0,%1,%2,%3,%4,%5,%6,%7,%8,%9,%10,%11,%12,%13,%14,%15,%16,%17,%18,%19,%20,%21,%22,%23,%24,%25,%26,%27,%28,%29,%30,%31,%32,%33,%34,%35,%36,%37,%38,%39,%40,%41,%42,%43,%44,%45,%46,%47,%48,%49,%50,%51,%52,%53,%54,%55,%56,%57,%58,%59,%60,%61,%62,%63,%64,%65,%66,%67,%68,%69,%70,%71,%72,%73,%74,%75,%76,%77,%78,%79,%80,%81,%82,%83,%84,%85,%86,%87,%88,%89,%90,%91,%92,%93,%94,%95}, "
        "%96, %97, p, 1, 1, 0, 1;\n}\n"
        : "=f"(d[0]), "=f"(d[1]), "=f"(d[2]), "=f"(d[3]), "=f"(d[4]), "=f"(d[5]), "=f"(d[6]), "=f"(d[7]), "=f"(d[8]), "=f"(d[9]), "=f"(d[10]), "=f"(d[11]),
          "=f"(d[12]), "=f"(d[13]), "=f"(d[14]), "=f"(d[15]), "=f"(d[16]), "=f"(d[17]), "=f"(d[18]), "=f"(d[19]), "=f"(d[20]), "=f"(d[21]), "=f"(d[22]), "=f"(d[23]),
          "=f"(d[24]), "=f"(d[25]), "=f"(d[26]), "=f"(d[27]), "=f"(d[28]), "=f"(d[29]), "=f"(d[30]), "=f"(d[31]), "=f"(d[32]), "=f"(d[33]), "=f"(d[34]), "=f"(d[35]),
          "=f"(d[36]), "=f"(d[37]), "=f"(d[38]), "=f"(d[39]), "=f"(d[40]), "=f"(d[41]), "=f"(d[42]), "=f"(d[43]), "=f"(d[44]), "=f"(d[45]), "=f"(d[46]), "=f"(d[47]),
          "=f"(d[48]), "=f"(d[49]), "=f"(d[50]), "=f"(d[51]), "=f"(d[52]), "=f"(d[53]), "=f"(d[54]), "=f"(d[55]), "=f"(d[56]), "=f"(d[57]), "=f"(d[58]), "=f"(d[59]),
          "=f"(d[60]), "=f"(d[61]), "=f"(d[62]), "=f"(d[63]), "=f"(d[64]), "=f"(d[65]), "=f"(d[66]), "=f"(d[67]), "=f"(d[68]), "=f"(d[69]), "=f"(d[70]), "=f"(d[71]),
          "=f"(d[72]), "=f"(d[73]), "=f"(d[74]), "=f"(d[75]), "=f"(d[76]), "=f"(d[77]), "=f"(d[78]), "=f"(d[79]), "=f"(d[80]), "=f"(d[81]), "=f"(d[82]), "=f"(d[83]),
          "=f"(d[84]), "=f"(d[85]), "=f"(d[86]), "=f"(d[87]), "=f"(d[88]), "=f"(d[89]), "=f"(d[90]), "=f"(d[91]), "=f"(d[92]), "=f"(d[93]), "=f"(d[94]), "=f"(d[95])
        : "l"(desca), "l"(desc));
}
__device__ __forceinline__ void wg_qk_init(uint32_t (&d)[32], uint32_t a0, uint32_t a1, uint32_t a2, uint32_t a3, uint64_t desc) {
    asm volatile("{\n.reg .pred p;\nsetp.ne.b32 p, 0, 0;\n"
        "wgmma.mma_async.sync.aligned.m64n128k16.f16.f16.f16 "
        "{%0,%1,%2,%3,%4,%5,%6,%7,%8,%9,%10,%11,%12,%13,%14,%15,%16,%17,%18,%19,%20,%21,%22,%23,%24,%25,%26,%27,%28,%29,%30,%31}, "
        "{%32,%33,%34,%35}, %36, p, 1, 1, 0;\n}\n"
        : "=r"(d[0]), "=r"(d[1]), "=r"(d[2]), "=r"(d[3]), "=r"(d[4]), "=r"(d[5]), "=r"(d[6]), "=r"(d[7]), "=r"(d[8]), "=r"(d[9]), "=r"(d[10]), "=r"(d[11]),
          "=r"(d[12]), "=r"(d[13]), "=r"(d[14]), "=r"(d[15]), "=r"(d[16]), "=r"(d[17]), "=r"(d[18]), "=r"(d[19]), "=r"(d[20]), "=r"(d[21]), "=r"(d[22]), "=r"(d[23]),
          "=r"(d[24]), "=r"(d[25]), "=r"(d[26]), "=r"(d[27]), "=r"(d[28]), "=r"(d[29]), "=r"(d[30]), "=r"(d[31])
        : "r"(a0), "r"(a1), "r"(a2), "r"(a3), "l"(desc));
}
__device__ __forceinline__ void wg_qk_acc(uint32_t (&d)[32], uint32_t a0, uint32_t a1, uint32_t a2, uint32_t a3, uint64_t desc) {
    asm volatile("{\n.reg .pred p;\nsetp.ne.b32 p, 1, 0;\n"
        "wgmma.mma_async.sync.aligned.m64n128k16.f16.f16.f16 "
        "{%0,%1,%2,%3,%4,%5,%6,%7,%8,%9,%10,%11,%12,%13,%14,%15,%16,%17,%18,%19,%20,%21,%22,%23,%24,%25,%26,%27,%28,%29,%30,%31}, "
        "{%32,%33,%34,%35}, %36, p, 1, 1, 0;\n}\n"
        : "+r"(d[0]), "+r"(d[1]), "+r"(d[2]), "+r"(d[3]), "+r"(d[4]), "+r"(d[5]), "+r"(d[6]), "+r"(d[7]), "+r"(d[8]), "+r"(d[9]), "+r"(d[10]), "+r"(d[11]),
          "+r"(d[12]), "+r"(d[13]), "+r"(d[14]), "+r"(d[15]), "+r"(d[16]), "+r"(d[17]), "+r"(d[18]), "+r"(d[19]), "+r"(d[20]), "+r"(d[21]), "+r"(d[22]), "+r"(d[23]),
          "+r"(d[24]), "+r"(d[25]), "+r"(d[26]), "+r"(d[27]), "+r"(d[28]), "+r"(d[29]), "+r"(d[30]), "+r"(d[31])
        : "r"(a0), "r"(a1), "r"(a2), "r"(a3), "l"(desc));
}
__device__ __forceinline__ void wg_pv_init(uint32_t (&d)[10], uint32_t a0, uint32_t a1, uint32_t a2, uint32_t a3, uint64_t desc) {
    asm volatile("{\n.reg .pred p;\nsetp.ne.b32 p, 0, 0;\n"
        "wgmma.mma_async.sync.aligned.m64n40k16.f16.f16.f16 "
        "{%0,%1,%2,%3,%4,%5,%6,%7,%8,%9}, "
        "{%10,%11,%12,%13}, %14, p, 1, 1, 1;\n}\n"
        : "=r"(d[0]), "=r"(d[1]), "=r"(d[2]), "=r"(d[3]), "=r"(d[4]), "=r"(d[5]), "=r"(d[6]), "=r"(d[7]), "=r"(d[8]), "=r"(d[9])
        : "r"(a0), "r"(a1), "r"(a2), "r"(a3), "l"(desc));
}
__device__ __forceinline__ void wg_pv_acc(uint32_t (&d)[10], uint32_t a0, uint32_t a1, uint32_t a2, uint32_t a3, uint64_t desc) {
    asm volatile("{\n.reg .pred p;\nsetp.ne.b32 p, 1, 0;\n"
        "wgmma.mma_async.sync.aligned.m64n40k16.f16.f16.f16 "
        "{%0,%1,%2,%3,%4,%5,%6,%7,%8,%9}, "
        "{%10,%11,%12,%13}, %14, p, 1, 1, 1;\n}\n"
        : "+r"(d[0]), "+r"(d[1]), "+r"(d[2]), "+r"(d[3]), "+r"(d[4]), "+r"(d[5]), "+r"(d[6]), "+r"(d[7]), "+r"(d[8]), "+r"(d[9])
        : "r"(a0), "r"(a1), "r"(a2), "r"(a3), "l"(desc));
}

constexpr uint32_t SB = SMEM_BASE;
constexpr uint32_t R_SLOT = 18432, A_RING = SB, A_KP = SB + 73728, A_QX = SB + 81920, A_STB = SB + 98304;
constexpr uint32_t F_GU0 = SB + 98304, F_GU1 = SB + 163840, F_WD = F_GU0;
__host__ __device__ constexpr uint32_t o_a(uint32_t s) { return s == 0 ? SB : s == 1 ? A_QX : F_GU0 + (s - 2) * 32768; }
__host__ __device__ constexpr uint32_t o_b(uint32_t s) { return s < 2 ? SB + 16384 + s * 16384 : F_GU0 + 16384 + (s - 2) * 32768; }
constexpr uint32_t XT0 = SB + 49152, XT1 = XT0 + 16384, YT0 = o_a(0), YT1 = o_a(1);
constexpr uint32_t Q_ABYTES = 256 * 64 * 2, Q_STB = Q_ABYTES + 192 * 64 * 2;
constexpr uint32_t Q_CS = SB + 3 * Q_STB, Q_VS = Q_CS + 768, Q_RC = Q_VS + 256, Q_FIX = Q_RC + 2048;
constexpr uint32_t SD_VEC = SB + 176128, SD_W = SB + 180224;
static_assert(Q_FIX + 768 <= SD_VEC, "smem");
constexpr uint32_t M_RED = SB + 229376, M_BAR = M_RED + 2048, BAR_SET = 320, M_IVS = M_BAR + 2 * BAR_SET, M_SM = M_IVS + 128;
constexpr uint32_t M_F2 = M_SM;
constexpr uint32_t M_WS = M_SM + 16;
constexpr uint32_t M_CR = M_SM + 20;
constexpr uint32_t M_SS = M_SM + 24;
constexpr uint32_t M_RT = M_SM + 32;
constexpr uint32_t M_SR = M_SM + 128;
constexpr int K_SMEM = M_SR + 128 - SB;
static_assert(K_SMEM == 232448, "smem");
constexpr uint32_t B_QF = 0, B_AF = 24, B_OF = 56, B_RES = 88, B_GU = 96, B_WD = 104, B_RT = 112, B_SW = 120, B_ONE = 128, B_QE = 136, B_OE = 160, B_PX = 192,
                   B_AE = 216, B_OD = 248, B_FG = 280, B_FD = 288, B_XS = 296, B_KS = 304, B_END = 320;
constexpr int NB_ML = 1, NB_CONS = 2, NB_SIDE = 3, NB_EPI = 4;

struct Maps { CUtensorMap x[2], wqkv, o, wo[2], r, g, u, d; };

template <int N>
__device__ __forceinline__ void halve(float (&v)[8], int lane, int bit) {
    const bool up = lane & bit;
    #pragma unroll
    for (int i = 0; i < N; i++) v[i] = (up ? v[N + i] : v[i]) + __shfl_xor_sync(0xffffffffu, up ? v[i] : v[N + i], bit);
}

__device__ __forceinline__ void reset_exchange(int c, int t) {
    #pragma unroll 1
    for (int i = t; i < FILL; i += 96) g_u.fill[c][i] = make_uint4(EMPTY, EMPTY, EMPTY, EMPTY);
}
__device__ __forceinline__ void prep_work(const bf16* __restrict__ x0, const bf16* __restrict__ w_r, uint32_t lb) {
    const int t = tid_now() - 288, c = cta_now(), lane = t & 31, warp = warp_uniform(t >> 5);
    const uint32_t wb = SD_W + warp * 8192;
    mbar_nap(lb + B_SW, 0);
    {
        float cs[8], cq[8];
        #pragma unroll
        for (int i = 0; i < 8; i++) { cs[i] = 0.f; cq[i] = 0.f; }
        #pragma unroll 1
        for (int h = 0; h < 2; h++) {
            #pragma unroll 2
            for (int r = 0; r < 16; r++) {
                const uint4 u = lds128(wb + h * 24576 + (lane >> 3) * 128 + r * 512 + (((lane & 7) ^ ((r * 4 + (lane >> 3)) & 7)) << 4));
                const uint32_t w[4] = {u.x, u.y, u.z, u.w};
                #pragma unroll
                for (int e = 0; e < 4; e++) {
                    const float a = bf_lo(w[e]), b = bf_hi(w[e]);
                    cs[2*e] += a; cs[2*e+1] += b; cq[2*e] = fmaf(a, a, cq[2*e]); cq[2*e+1] = fmaf(b, b, cq[2*e+1]);
                }
            }
            fence_async_smem();
            __syncwarp();
            if (elect_one()) {
                const uint32_t bytes = h == 0 ? 8192 : warp < 2 ? 4096 : 2048;
                mbar_expect_tx(lb + B_PX + warp * 8, bytes);
                bulk_load(wb + h * 24576, h && warp == 2 ? w_r : x0 + (size_t)(c * 16 + (h ? 12 + warp * 2 : warp * 4)) * D_, bytes, lb + B_PX + warp * 8);
            }
            __syncwarp();
        }
        halve<4>(cs, lane, 16); halve<2>(cs, lane, 8);
        halve<4>(cq, lane, 16); halve<2>(cq, lane, 8);
        *reinterpret_cast<float4*>(&g_cs[c >> 4][warp * D_ + (c & 15) * 64 + (lane & 7) * 8 + (lane >> 3) * 2]) = make_float4(cs[0], cq[0], cs[1], cq[1]);
    }
    TL(288, 22);
    reset_exchange(c, t);
    mbar_nap(lb + B_PX + warp * 8, 0);
    #pragma unroll 1
    for (int i = 0; i < (warp < 2 ? 6 : 5); i++) {
        const int r = i < 4 ? warp * 4 + i : 8 + warp * 2 + i;
        float s0 = 0.f, s1 = 0.f, q0 = 0.f, q1 = 0.f;
        #pragma unroll 2
        for (int j = 0; j < 4; j++) {
            const uint4 u = lds128(wb + (i >> 2) * 16384 + i * 2048 + j * 512 + lane * 16);
            const uint32_t w[4] = {u.x, u.y, u.z, u.w};
            #pragma unroll
            for (int e = 0; e < 4; e++) { const float a = bf_lo(w[e]), b = bf_hi(w[e]); s0 += a; s1 += b; q0 = fmaf(a, a, q0); q1 = fmaf(b, b, q1); }
        }
        s0 += s1; q0 += q1;
        float v = (lane & 16 ? q0 : s0) + __shfl_xor_sync(0xffffffffu, lane & 16 ? s0 : q0, 16);
        #pragma unroll
        for (int o = 8; o > 0; o >>= 1) v += __shfl_xor_sync(0xffffffffu, v, o);
        const float mean = v * (1.f / D_), sq = __shfl_xor_sync(0xffffffffu, mean, 16);
        if (lane == 0) {
            if (r < 16) g_rs0[c * 16 + r] = make_float2(fmaxf(sq - mean * mean, 0.f), mean);
            else stsf(M_WS, v);
        }
    }
    named_sync(NB_SIDE, 96);
    if (t == 0) { TL(288, 23); ctr_arrive(&g_pctr); ctr_wait(&g_pctr, 128); TL(288, 24); }
    named_sync(NB_SIDE, 96);
}

__device__ __forceinline__ void head_scales(float fq, float fk, float& sq, float& sk, float& ss) {
    const bool ok = fq <= 16384.f && fk <= 16384.f && fq * fk <= 50000.f;
    const int a = min(max((((int)(__float_as_uint(fq) >> 23) - 125) >> 1) - 8, -60), 60), b = min(max((((int)(__float_as_uint(fk) >> 23) - 125) >> 1) - 8, -60), 60);
    sq = QSCALE * __uint_as_float((uint32_t)(ok ? 127 : 127 - a) << 23);
    sk = __uint_as_float((uint32_t)(ok ? 127 : 127 - b) << 23);
    ss = ok ? 0.f : __uint_as_float((uint32_t)(127 + a + b) << 23);
}

__device__ __forceinline__ void epi_inputs(int L, const bf16* __restrict__ w_r) {
    const int t = tid_now() - 288, c = cta_now(), mt = c >> 4, nt = c & 15, lane = t & 31;
    const uint32_t wr = t < 64 ? __ldg(reinterpret_cast<const uint32_t*>(w_r) + (c & 7) * 64 + t) : 0x3F803F80u;
    #pragma unroll 1
    for (int k = 0; k < 3; k++) {
        const int i = t + 96 * k, col = (i >> 6) * D_ + nt * 64 + (i & 63);
        const float2* rsp = (L ? g_x.rs1 : g_rs0) + mt * 256 + (i & 255);
        uint2 sv = ld_x64(rsp);
        if (k < 2) {
            float2 p[8];
            #pragma unroll
            for (int j = 0; j < 8; j++) p[j] = __ldcg(&g_cs[j][col]);
            stsf(Q_CS + i * 4, ((p[0].x + p[1].x) + (p[2].x + p[3].x)) + ((p[4].x + p[5].x) + (p[6].x + p[7].x)));
            const float zz = ((p[0].y + p[1].y) + (p[2].y + p[3].y)) + ((p[4].y + p[5].y) + (p[6].y + p[7].y));
            const float zs = warp_sum(zz);
            if (i < 128) { if (lane == 0) stsf(M_SR + (i >> 5) * 4, zs); }
            else {
                const int e = (int)(__float_as_uint(zz) >> 23) - 127;
                const int sh = min(max(((e + 2) >> 1) + 3, -60), 60);
                sts32(Q_VS + (i - 128) * 4, (uint32_t)(127 - sh) << 23);
                sts16(M_IVS + ((i & 32) + (i & 6) * 4 + ((i >> 2) & 6) + (i & 1)) * 2, (uint32_t)(127 + sh - 4) << 7);
            }
        }
        else {
            named_sync(NB_SIDE, 96);
            if (t < 2) {
                float sq, sk, ss;
                head_scales(ldsf(M_SR + t * 4), ldsf(M_SR + 8 + t * 4), sq, sk, ss);
                stsf(M_F2 + t * 4, sq); stsf(M_F2 + 8 + t * 4, sk); stsf(M_SS + t * 4, ss);
            }
            __syncwarp();
        }
        uint32_t n = 0;
        #pragma unroll 1
        while (warp_any(sv.x == EMPTY)) { sv = ld_x64(rsp); poll_tick(n); }
        const float var = __uint_as_float(sv.x), a = L ? 1.f + rsq(var + LN_EPS) : 1.f;
        sts64(Q_RC + (i & 255) * 8, __float_as_uint(a * rsq(a * a * var + LN_EPS)), sv.y ^ 0x80000000u);
    }
    if (t < 68) sts32(M_RED + t * 4, wr);
}

__device__ __forceinline__ void ffn_finish(int L, bf16* __restrict__ out) {
    const int t = tid_now() - 288, c = cta_now(), lane = t & 31, warp = warp_uniform(t >> 5);
    TL(288, L * 32 + 29);
    const uint4 rv = lds128(M_RT + 16 * L);
    const int idx = (int)rv.w;
    const uint32_t* xsrc = &g_x.cand[L][idx >> 7][(c >> 2) * 16 + (t & 3) * 4 + (c & 3)];
    const uint8_t* fsrc = &g_x.x[idx >> 8][((idx >> 7) & 1) * 8 + (c >> 4)];
    uint32_t xw, busy;
    float a[4] = {0.f, 0.f, 0.f, 0.f};
    {
        const float* src = &g_x.ypart[L][c][0][t * 4];
        uint4 v[3];
        uint32_t n = 0;
        #pragma unroll 1
        do {
            v[0] = ld_x128(src); v[1] = ld_x128(src + 384);
            v[2] = make_uint4(0u, 0u, 0u, 0u);
            xw = 0u; busy = 0u;
            if (warp == 0) {
                v[2] = ld_x128(src + 768); xw = ld_x32(xsrc);
                asm volatile("ld.relaxed.gpu.global.u8 %0, [%1];" : "=r"(busy) : "l"(fsrc) : "memory");
            }
            poll_tick(n);
        } while (warp_any(any_empty(v[0]) || any_empty(v[1]) || any_empty(v[2]) || xw == EMPTY || busy != 0));
        TL(288, L * 32 + 30); TL(352, L * 32 + 31);
        #pragma unroll
        for (int i = 0; i < 3; i++) { a[0] += __uint_as_float(v[i].x); a[1] += __uint_as_float(v[i].y); a[2] += __uint_as_float(v[i].z); a[3] += __uint_as_float(v[i].w); }
    }
    #pragma unroll
    for (int o = 2; o < 32; o <<= 1) {
        #pragma unroll
        for (int i = 0; i < 4; i++) a[i] += __shfl_xor_sync(0xffffffffu, a[i], o);
    }
    if (lane < 2) sts128(M_SR + warp * 32 + lane * 16, __float_as_uint(a[0]), __float_as_uint(a[1]), __float_as_uint(a[2]), __float_as_uint(a[3]));
    named_sync(NB_SIDE, 96);
    if (t < 4) {
        const float2 y0 = lds64f(M_SR + t * 8), y1 = lds64f(M_SR + 32 + t * 8), y2 = lds64f(M_SR + 64 + t * 8);
        const uint32_t y = pack_bf16(y0.x + y1.x + y2.x, y0.y + y1.y + y2.y);
        const float rsel = bf_round(rcp(1.f + __expf(-bf_round(__uint_as_float(rv.x)))));
        const uint32_t xn = ln2(xw, ln2_coef(__uint_as_float(rv.y), __uint_as_float(rv.z)));
        const uint32_t res = badd2(xw, badd2(xn, pack_bf16(bf_lo(y) * rsel, bf_hi(y) * rsel)));
        if (L == 0) st_x32(&g_x.x2row[c * 4 + t], res);
        reinterpret_cast<uint32_t*>(L ? out : g_x1)[idx * (D_ / 2) + c * 4 + t] = res;
    }
}

__device__ __forceinline__ void fix_row(uint32_t lb) {
    const int t = tid_now() - 288, c = cta_now(), lane = t & 31, warp = warp_uniform(t >> 5);
    uint4 v[2];
    {
        uint32_t n = 0;
        #pragma unroll 1
        do {
            v[0] = ld_x128(g_x.x2row + t * 4);
            v[1] = make_uint4(0u, 0u, 0u, 0u);
            if (warp == 0) v[1] = ld_x128(g_x.x2row + (96 + t) * 4);
            poll_tick(n);
        } while (warp_any(any_empty(v[0]) || any_empty(v[1])));
    }
    const uint32_t w[8] = {v[0].x, v[0].y, v[0].z, v[0].w, v[1].x, v[1].y, v[1].z, v[1].w};
    float su = 0.f, sq = 0.f;
    #pragma unroll
    for (int i = 0; i < 8; i++) { const float a = bf_lo(w[i]), b = bf_hi(w[i]); su += a + b; sq = fmaf(a, a, fmaf(b, b, sq)); }
    su = warp_sum(su); sq = warp_sum(sq);
    if (lane == 0) sts64(M_SR + 96 + warp * 8, __float_as_uint(su), __float_as_uint(sq));
    named_sync(NB_SIDE, 96);
    const float2 s0 = lds64f(M_SR + 96), s1 = lds64f(M_SR + 104), s2 = lds64f(M_SR + 112);
    const float mean = (s0.x + s1.x + s2.x) * (1.f / D_);
    const float rstd = rsq(fmaxf((s0.y + s1.y + s2.y) * (1.f / D_) - mean * mean, 0.f) + LN_EPS);
    const Ln2 k = ln2_coef(mean, rstd);
    #pragma unroll
    for (int i = 0; i < 2; i++)
        if (i == 0 || warp == 0) sts128(SD_VEC + (t + 96 * i) * 16, ln2(w[4*i], k), ln2(w[4*i+1], k), ln2(w[4*i+2], k), ln2(w[4*i+3], k));
    named_sync(NB_SIDE, 96);
    TL(288, 32 + 22);
    mbar_nap(lb + B_SW, 0);
    float a[8];
    #pragma unroll
    for (int i = 0; i < 8; i++) a[i] = 0.f;
    const uint32_t xa = base32(SD_VEC + lane * 2), wa = base32(SD_W + lane * 48 + warp * 16);
    #pragma unroll 2
    for (int b = 0; b < 32; b++) {
        const float x = bf_lo(lds16(xa + b * 64));
        const uint4 u = lds128(wa + b * 1536);
        a[0] = fmaf(x, bf_lo(u.x), a[0]); a[1] = fmaf(x, bf_hi(u.x), a[1]); a[2] = fmaf(x, bf_lo(u.y), a[2]); a[3] = fmaf(x, bf_hi(u.y), a[3]);
        a[4] = fmaf(x, bf_lo(u.z), a[4]); a[5] = fmaf(x, bf_hi(u.z), a[5]); a[6] = fmaf(x, bf_lo(u.w), a[6]); a[7] = fmaf(x, bf_hi(u.w), a[7]);
    }
    halve<4>(a, lane, 16); halve<2>(a, lane, 8); halve<1>(a, lane, 4);
    a[0] = quad_sum(a[0]);
    if ((lane & 3) == 0) st_x32(&g_x.fix[c * 24 + warp * 8 + (lane >> 2)], __float_as_uint(a[0]));
    TL(288, 32 + 23);
    if (((int)lds32(M_RT + 12) >> 8) == (c >> 4)) {
        const float* src = &g_x.fix[(t >> 5) * D_ + (c & 15) * 64 + (t & 31) * 2];
        uint2 f;
        uint32_t n = 0;
        #pragma unroll 1
        do { f = ld_x64(src); poll_tick(n); } while (warp_any(f.x == EMPTY || f.y == EMPTY));
        sts64(Q_FIX + t * 8, f.x, f.y);
    }
}

__device__ __forceinline__ void out_piece(bf16* __restrict__ out, int r, int ch, bool on) {
    const uint4 v = lds128(((ch & 8) ? YT1 : YT0) + r * 128 + (((ch ^ r) & 7) << 4)), kk = lds128(XT0 + r * 16);
    const Ln2 k = {kk.x, kk.y, kk.z, kk.w};
    const int c = blockIdx.x;
    stg128_pred(out + ((c >> 3) * 128 + r) * D_ + (c & 7) * 128 + ch * 8, make_uint4(add_ln2(v.x, k), add_ln2(v.y, k), add_ln2(v.z, k), add_ln2(v.w, k)), on);
}
__device__ __forceinline__ void publish(uint8_t* f) {
    bulk_commit();
    bulk_wait();
    fence_async_global();
    asm volatile("st.release.gpu.global.u8 [%0], 0;" :: "l"(f) : "memory");
}
__device__ __forceinline__ void side_role(const Maps& mp, const bf16* __restrict__ x0, const bf16* __restrict__ wo, const bf16* __restrict__ w_down, const bf16* __restrict__ w_r, bf16* __restrict__ out) {
    #pragma unroll 1
    for (int L = 0; L < 2; L++) {
        const uint32_t lb = M_BAR + L * BAR_SET;
        if (L == 0) prep_work(x0, w_r, lb);
        else fix_row(lb);
        epi_inputs(L, w_r);
        const int t = tid_now() - 288, c = cta_now(), mt = c >> 4, nt = c & 15, warp = warp_uniform(t >> 5);
        TL(288, L * 32 + 4);
        named_arrive(NB_EPI, 224);
        named_arrive(NB_EPI + 1, 224);
        if (warp == 0) {
            named_sync(NB_ML, 288);
            #pragma unroll
            for (int i = 0; i < 16; i++) sts128(base32(A_RING + 16384 + t * 16) + (i >> 2) * R_SLOT + (i & 3) * 512, 0x2C002C00u, 0x2C002C00u, 0x2C002C00u, 0x2C002C00u);
            fence_async_smem();
            __syncwarp();
            mbar_arrive_elect(lb + B_ONE);
        }
        if (elect_one()) {
            #pragma unroll 1
            for (int n = warp - 1; n >= 0 && n < 3 * warp - 2; n++) {
                char* dst = g_kv + (size_t)(nt * 2 + (n >> 1)) * 16 * KV_TILE;
                const int tile = 2 * mt + (n & 1);
                if (n < 3) mbar_nap(lb + (n == 2 ? B_AE + 16 : B_KS + 8 * n), 0);
                bulk_store(dst + ((tile - 1) & 15) * KV_TILE, n == 0 ? A_KP : n == 1 ? A_RING : A_STB + (n - 2) * 8192, 8192);
                bulk_store(dst + tile * KV_TILE + 8192, n < 2 ? A_RING + 8192 + n * R_SLOT : A_STB + n * 8192, 8192);
                publish(&g_x.kv[L][nt * 2 + (n >> 1)][tile]);
                if (n == 1) TL(352, L * 32 + 6);
                if (n == 0) TL(320, L * 32 + 27);
            }
            if (warp == 2) {
                const bool ffn = c < NFC;
                const uint64_t pol = policy_evict_first();
                mbar_expect_tx(lb + B_GU, ffn ? 131072 : 0);
                mbar_expect_tx(lb + B_WD, ffn ? 65536 : 0);
                l2_prefetch(reinterpret_cast<const char*>(wo) + (size_t)c * 16384, 16384);
                if (ffn) {
                    #pragma unroll 1
                    for (int i = 0; i < 12; i++) {
                        if (i < 8) tma_load_s(F_GU0 + i * 16384, (i & 1) ? &mp.u : &mp.g, c * 32, (i >> 1) * 256, lb + B_GU, pol);
                        else l2_prefetch(reinterpret_cast<const char*>(w_down) + (size_t)c * 65536 + (i - 8) * 16384, 16384);
                        __nanosleep(900);
                    }
                }
                mbar_nap(lb + B_OD, 0);
                __nanosleep(1000);
                l2_prefetch(g_u.fill[c], sizeof(g_u.fill[0]));
                if (L == 0) {
                    mbar_nap(lb + B_XS, 0);
                    tma_store(&mp.x[1], YT0, (c & 7) * 128, (c >> 3) * 128);
                    tma_store(&mp.x[1], YT1, (c & 7) * 128 + 64, (c >> 3) * 128);
                    publish(&g_x.x[mt][nt]);
                    TL(352, 18);
                }
            } else {
                #pragma unroll 1
                for (int p = 0; p < 2; p++) { mbar_sleep(lb + B_OD + (p * 2 + warp) * 8, 0); ctr_arrive(g_x.o[L][mt * 2 + warp][p]); TL(288, L * 32 + 19); }
            }
        }
        __syncwarp();
        if (L) {
            mbar_sleep(lb + B_XS, 0);
            const int cand = (int)lds32(M_CR) & 127;
            #pragma unroll 2
            for (int r = t >> 4; r < 132; r += 6) out_piece(out, r & 127, t & 15, r < 128 && r != cand);
            TL(288, 32 + 18);
            mbar_sleep(lb + B_RT, 0);
            out_piece(out, cand, t & 15, t < 16 && lds32(M_CR) != lds32(M_RT + 28));
        }
        const uint32_t late = mbar_test(lb + B_FD, 0);
        mbar_sleep(lb + B_FD, 0);
        __nanosleep(late ? 50 : 400);
        if (c == 0 && t == 0 && L == 0) g_pctr = 0;
        ffn_finish(L, out);
        TL(288, L * 32 + 20);
    }
}

struct Cols { float2 c[4], v[4]; };
template <int HH>
__device__ __forceinline__ void load_cols(Cols& k, uint32_t cs) {
    #pragma unroll
    for (int jj = 0; jj < 4; jj++) {
        k.c[jj] = lds64f(cs + (HH * 32 + jj * 8) * 4);
        if (HH >= 4) k.v[jj] = lds64f(cs + (Q_VS - Q_CS) + ((HH & 1) * 32 + jj * 8) * 4);
    }
}
template <int HH>
__device__ __forceinline__ void qkv_epi_head(const float (&acc0)[96], const float (&acc1)[96], const float (&cf)[4], const float (&nm)[4], const Cols& k, float hs, uint32_t (&pk)[4][4]) {
    #pragma unroll
    for (int jj = 0; jj < 4; jj++) {
        #pragma unroll
        for (int i = 0; i < 4; i++) {
            const float* a = (i >> 1) ? acc1 : acc0;
            const float sc = HH < 4 ? cf[i] * hs : cf[i];
            float x = fmaf(nm[i], k.c[jj].x, a[4 * (4 * HH + jj) + 2 * (i & 1)]) * sc;
            float y = fmaf(nm[i], k.c[jj].y, a[4 * (4 * HH + jj) + 2 * (i & 1) + 1]) * sc;
            if (HH >= 4) { x *= k.v[jj].x; y *= k.v[jj].y; }
            pk[i][jj] = pack_f16(x, y);
        }
    }
}
__device__ __forceinline__ void stage_kv(uint32_t dst, const uint32_t (&pk)[4][4]) {
    #pragma unroll
    for (int i = 0; i < 4; i++) stsm4(dst + (i >> 1) * 1024 + (i & 1) * 128, pk[i][0], pk[i][1], pk[i][2], pk[i][3]);
}
template <int OFF>
__device__ __forceinline__ void patch_row(float (&acc)[96], uint32_t fx) {
    #pragma unroll
    for (int j = 0; j < 24; j++) { const float2 f = lds64f(fx + j * 32); acc[4 * j + OFF] = f.x; acc[4 * j + OFF + 1] = f.y; }
}
template <bool INIT>
__device__ __forceinline__ void qkv_step(float (&acc0)[96], float (&acc1)[96], uint64_t da, uint64_t db) {
    wg_fence();
    #pragma unroll
    for (int kk = 0; kk < 4; kk++) {
        if (INIT && kk == 0) { wg_gemm_n192_init(acc0, da, db); wg_gemm_n192_init(acc1, da + (8192 >> 4), db); }
        else { wg_gemm_n192(acc0, da + kk * 2, db + kk * 128); wg_gemm_n192(acc1, da + (8192 >> 4) + kk * 2, db + kk * 128); }
    }
    wg_commit();
}
__device__ __forceinline__ void qkv_phase(int L, uint32_t lb, int wg, uint32_t (&qa)[8], uint32_t (&qb)[8], uint32_t (&SA)[32], uint32_t (&SB_)[32]) {
    float acc0[96], acc1[96];
    {
        const bool leader = (tid_now() & 127) == 0;
        const uint64_t da0 = opaque(desc_sw128(SB + wg * 16384, 16, 1024)), db0 = opaque(desc_sw128(SB + Q_ABYTES, 8192, 1024));
        mbar_spin(lb + B_QF, 0);
        TL(0, L * 32 + 1); CK(0, L * 32 + 10);
        qkv_step<true>(acc0, acc1, da0, db0);
        uint32_t st = 1, ph = 0;
        #pragma unroll 1
        for (int k = 1; k < 16; k++) {
            mbar_spin(lb + B_QF + 8 * st, ph);
            if (k == 14 && wg) named_sync(NB_CONS, 256);
            qkv_step<false>(acc0, acc1, da0 + st * (Q_STB >> 4), db0 + st * (Q_STB >> 4));
            if (k == 15 && !wg) named_arrive(NB_CONS, 256);
            wg_wait<1>();
            if (leader) mbar_arrive(lb + B_QE + 8 * (st == 0 ? 2 : st - 1));
            if (++st == 3) { st = 0; ph ^= 1; }
        }
    }
    named_sync(NB_EPI + wg, 224);
    const int tid = tid_now(), lane = tid & 31, w = (tid >> 5) & 3, g = lane >> 2, t = lane & 3;
    const int lr0 = wg * 128 + w * 16 + g;
    float cf[4], nm[4];
    #pragma unroll
    for (int i = 0; i < 4; i++) { const float2 r = lds64f(base32(Q_RC + lr0 * 8) + ((i >> 1) * 64 + (i & 1) * 8) * 8); cf[i] = r.x; nm[i] = r.y; }
    const uint32_t cs = base32(Q_CS + t * 8);
    const int d = L ? (int)lds32(M_RT + 12) - ((cta_now() >> 4) * 256 + lr0) : -1;
    const uint4 hs = lds128(M_F2);
    const uint32_t ko = base32((lane >> 3) * 2048 + (w * 16 + (lane & 7)) * 16);
    Cols k0, k1;
    load_cols<2>(k0, cs);
    wg_wait<0>();
    pin(acc0); pin(acc1);
    TL(128, L * 32 + 2); CK(128, L * 32 + 11);
    named_arrive(NB_ML, 288);
    if ((tid & 127) == 0) mbar_arrive(lb + B_QE);
    if (__builtin_expect((d & ~72) == 0, 0)) {
        if (d == 0) { patch_row<0>(acc0, cs + (Q_FIX - Q_CS)); cf[0] = 1.f; nm[0] = 0.f; }
        else if (d == 8) { patch_row<2>(acc0, cs + (Q_FIX - Q_CS)); cf[1] = 1.f; nm[1] = 0.f; }
        else if (d == 64) { patch_row<0>(acc1, cs + (Q_FIX - Q_CS)); cf[2] = 1.f; nm[2] = 0.f; }
        else { patch_row<2>(acc1, cs + (Q_FIX - Q_CS)); cf[3] = 1.f; nm[3] = 0.f; }
    }
    __syncwarp();
    uint32_t pk[4][4];
    qkv_epi_head<2>(acc0, acc1, cf, nm, k0, __uint_as_float(hs.z), pk);
    load_cols<4>(k1, cs);
    mbar_spin(lb + B_QE + 8 - 8 * wg, wg);
    stage_kv((wg ? A_RING : A_KP) + ko, pk);
    qkv_epi_head<4>(acc0, acc1, cf, nm, k1, 1.f, pk);
    load_cols<3>(k0, cs);
    stage_kv(A_RING + wg * R_SLOT + 8192 + ko, pk);
    fence_async_smem();
    __syncwarp();
    mbar_arrive_elect(lb + B_KS + 8 * wg);
    qkv_epi_head<3>(acc0, acc1, cf, nm, k0, __uint_as_float(hs.w), pk);
    load_cols<0>(k1, cs);
    load_cols<5>(k0, cs);
    stage_kv(A_STB + wg * 8192 + ko, pk);
    qkv_epi_head<0>(acc0, acc1, cf, nm, k1, __uint_as_float(hs.x), pk);
    #pragma unroll
    for (int s = 0; s < 2; s++) {
        qa[4*s] = pk[0][2*s]; qa[4*s+1] = pk[1][2*s]; qa[4*s+2] = pk[0][2*s+1]; qa[4*s+3] = pk[1][2*s+1];
        qb[4*s] = pk[2][2*s]; qb[4*s+1] = pk[3][2*s]; qb[4*s+2] = pk[2][2*s+1]; qb[4*s+3] = pk[3][2*s+1];
    }
    mbar_spin(lb + B_KS, 0);
    {
        constexpr uint64_t dk = desc_plain(A_KP, 2048, 128);
        wg_fence();
        wg_qk_init(SA, qa[0], qa[1], qa[2], qa[3], dk);
        wg_qk_acc(SA, qa[4], qa[5], qa[6], qa[7], dk + 256);
        wg_qk_init(SB_, qb[0], qb[1], qb[2], qb[3], dk);
        wg_commit();
    }
    qkv_epi_head<5>(acc0, acc1, cf, nm, k0, 1.f, pk);
    load_cols<1>(k1, cs);
    stage_kv(A_STB + 16384 + wg * 8192 + ko, pk);
    qkv_epi_head<1>(acc0, acc1, cf, nm, k1, __uint_as_float(hs.y), pk);
    #pragma unroll
    for (int u = 0; u < 2; u++)
        #pragma unroll
        for (int s = 0; s < 2; s++) sts128(A_QX + (u * 2 + s) * 4096 + tid * 16, pk[2*u][2*s], pk[2*u+1][2*s], pk[2*u][2*s+1], pk[2*u+1][2*s+1]);
    fence_async_smem();
    wg_wait<0>();
    pin(SA); pin(SB_);
    TL(128, L * 32 + 5); CK(128, L * 32 + 12);
}

#define PMASK 0x0000AAAAu
#define IMASK 0x10101010u
__host__ __device__ constexpr bool is_poly(int j) { return !((PMASK >> j) & 1); }
struct Shift { uint32_t f0, f1, n0, n1, bad; };

__device__ __forceinline__ uint32_t exp2_mufu(uint32_t s, uint32_t nm) {
    uint32_t r;
    asm("ex2.approx.f16x2 %0, %1;" : "=r"(r) : "r"(hadd2(s, nm)));
    return r;
}
__device__ __forceinline__ uint32_t exp2_fix(uint32_t s, uint32_t fm, uint32_t ca, uint32_t& U, bool mul, uint32_t sixteen) {
    uint32_t G, D;
    asm("fma.rn.relu.f16x2 %0, %1, %2, %3;" : "=r"(U) : "r"(s), "r"(0x00400040u), "r"(fm));
    asm("fma.rn.f16x2 %0, %1, %2, %3;" : "=r"(G) : "r"(U & 0x003F003Fu), "r"(ca), "r"(0x98B898B8u));
    asm("{.reg .b32 n; neg.f16x2 n, %1; fma.rn.relu.f16x2 %0, %1, n, %2;}" : "=r"(D) : "r"(G), "r"(0x00570057u));
    if (mul) return U * sixteen - D;
    return (U << 4) - D;
}
__device__ __forceinline__ uint32_t or3(uint32_t a, uint32_t b, uint32_t c) { uint32_t r; asm("lop3.b32 %0, %1, %2, %3, 0xFE;" : "=r"(r) : "r"(a), "r"(b), "r"(c)); return r; }
__device__ __forceinline__ void exp_tile(const uint32_t (&S)[32], uint32_t (&P)[32], Shift& h, uint32_t ca, uint32_t sixteen) {
    uint32_t U[33];
    int n = 0;
    #pragma unroll
    for (int i = 0; i < 32; i++) {
        if (is_poly(i)) P[i] = exp2_fix(S[i], (i & 1) ? h.f1 : h.f0, ca, U[n++], (IMASK >> i) & 1, sixteen);
        else P[i] = exp2_mufu(S[i], (i & 1) ? h.n1 : h.n0);
    }
    U[n] = 0u;
    #pragma unroll
    for (int i = 0; i < 32; i += 6) {
        if (i + 5 <= n) h.bad = or3(h.bad, or3(U[i], U[i + 1], U[i + 2]), or3(U[i + 3], U[i + 4], U[i + 5]));
        else {
            #pragma unroll
            for (int j = i; j < i + 6; j += 2) if (j < n) h.bad = or3(h.bad, U[j], U[j + 1]);
        }
    }
    pin(P);
}
__device__ __forceinline__ uint32_t hfma2(uint32_t a, uint32_t b, uint32_t c) { uint32_t r; asm("fma.rn.f16x2 %0, %1, %2, %3;" : "=r"(r) : "r"(a), "r"(b), "r"(c)); return r; }
__device__ __forceinline__ void unit_start(const uint32_t (&S)[32], Shift& h, uint32_t (&o2)[10]) {
    uint32_t m[4] = {S[0], S[1], S[2], S[3]};
    #pragma unroll
    for (int i = 1; i < 8; i++)
        #pragma unroll
        for (int e = 0; e < 4; e++) m[e] = hmax2(m[e], S[4 * i + e]);
    const uint32_t a = hadd2(m[0], m[2]), c = hadd2(m[1], m[3]);
    uint32_t x = hadd2(__byte_perm(a, c, 0x5410), __byte_perm(a, c, 0x7632));
    x = hadd2(x, __shfl_xor_sync(0xffffffffu, x, 1));
    x = hadd2(x, __shfl_xor_sync(0xffffffffu, x, 2));
    const uint32_t T = hfma2(x, 0xAC00AC00u, 0x5DEB5DEBu);
    const uint32_t n = hadd2(T, 0xDE00DE00u), f = hfma2(n, 0x00400040u, 0x03C003C0u);
    h.n0 = __byte_perm(n, 0, 0x1010); h.n1 = __byte_perm(n, 0, 0x3232);
    h.f0 = __byte_perm(f, 0, 0x1010); h.f1 = __byte_perm(f, 0, 0x3232);
    h.bad = T ^ 0x58005800u;
    #pragma unroll
    for (int i = 0; i < 10; i++) o2[i] = 0u;
}
__device__ __forceinline__ uint32_t o_offset() {
    const int c = cta_now(), tid = tid_now();
    return ((c >> 4) * 256 + (tid & 128) + ((tid >> 1) & 48) + ((tid >> 2) & 7)) * (D_ * 2) + (c & 15) * 64 + (tid & 3) * 16;
}
template <int PASS, int UNIT>
__device__ __forceinline__ void unit_end(const uint32_t (&o)[10], uint32_t bad, uint32_t lb, uint32_t oo, uint32_t& fail, const uint4 iv) {
    float v[20];
    #pragma unroll
    for (int i = 0; i < 10; i++) h2_unpack(o[i], v[2 * i], v[2 * i + 1]);
    const float i0 = rcp(v[16]), i1 = rcp(v[18]);
    uint32_t r[8], z = 0;
    #pragma unroll
    for (int j = 0; j < 4; j++) {
        r[j] = pack_bf16(v[4*j] * i0, v[4*j+1] * i0); r[4 + j] = pack_bf16(v[4*j+2] * i1, v[4*j+3] * i1);
        z = bfma2(r[j], r[4 + j], z);
    }
    const bool good = o[8] - 0x34003400u < 0x48000000u && o[9] - 0x34003400u < 0x48000000u &&
                      ((bad & 0xF800F800u) | (bmul2(z, 0u) & 0x7FFF7FFFu) | (fail & (1u << (2 * PASS + UNIT)))) == 0;
    const bool all = __all_sync(0xffffffffu, good);
    char* dst = reinterpret_cast<char*>(g_o) + oo + (UNIT * 64 * D_ + PASS * 512) * 2;
    stg128_pred(dst, make_uint4(bmul2(r[0], iv.x), bmul2(r[1], iv.y), bmul2(r[2], iv.z), bmul2(r[3], iv.w)), all);
    stg128_pred(dst + 16 * D_, make_uint4(bmul2(r[4], iv.x), bmul2(r[5], iv.y), bmul2(r[6], iv.z), bmul2(r[7], iv.w)), all);
    if (__builtin_expect(!all, 0)) {
        fail |= 1u << (2 * PASS + UNIT);
        if (PASS == 0) {
            #pragma unroll
            for (int s = 0; s < 2; s++) g_qsave[cta_now()][UNIT * 2 + s][tid_now()] = lds128(A_KP + (UNIT * 2 + s) * 4096 + tid_now() * 16);
        }
    }
    __syncwarp();
    mbar_arrive_elect_p(lb + PASS * 16, all);
}
__device__ __forceinline__ void swap_q(uint32_t (&q)[8], uint32_t a) {
    asm volatile("{\n.reg .pred p;\nsetp.ne.u32 p, %8, 0;\n"
                 "@p st.shared.v4.b32 [%8 + -8192], {%0, %1, %2, %3};\n@p st.shared.v4.b32 [%8 + -4096], {%4, %5, %6, %7};\n"
                 "@p ld.shared.v4.b32 {%0, %1, %2, %3}, [%8];\n@p ld.shared.v4.b32 {%4, %5, %6, %7}, [%8 + 4096];\n}"
                 : "+r"(q[0]), "+r"(q[1]), "+r"(q[2]), "+r"(q[3]), "+r"(q[4]), "+r"(q[5]), "+r"(q[6]), "+r"(q[7]) : "r"(a) : "memory");
}
static_assert(A_QX == A_KP + 8192, "parking places");
template <bool INIT>
__device__ __forceinline__ void issue_pv(uint32_t (&o)[10], const uint32_t (&P)[32], uint64_t dv) {
    if (INIT) wg_pv_init(o, P[0], P[1], P[2], P[3], dv); else wg_pv_acc(o, P[0], P[1], P[2], P[3], dv);
    #pragma unroll
    for (int k = 1; k < 8; k++) wg_pv_acc(o, P[4*k], P[4*k+1], P[4*k+2], P[4*k+3], dv + k * 16);
}

__device__ __forceinline__ uint4 quad_transpose(uint32_t x0, uint32_t x1, uint32_t x2, uint32_t x3, int t) {
    const bool b0 = t & 1, b1 = t & 2;
    uint32_t s0 = b0 ? x0 : x1, s1 = b0 ? x2 : x3;
    s0 = __shfl_xor_sync(0xffffffffu, s0, 1); s1 = __shfl_xor_sync(0xffffffffu, s1, 1);
    const uint32_t y0 = b0 ? s0 : x0, y1 = b0 ? x1 : s0, y2 = b0 ? s1 : x2, y3 = b0 ? x3 : s1;
    uint32_t u0 = b1 ? y0 : y2, u1 = b1 ? y1 : y3;
    u0 = __shfl_xor_sync(0xffffffffu, u0, 2); u1 = __shfl_xor_sync(0xffffffffu, u1, 2);
    return b1 ? make_uint4(u0, u1, y2, y3) : make_uint4(y0, y1, u0, u1);
}
__device__ __forceinline__ uint32_t movm(uint32_t v) { uint32_t r; asm volatile("movmatrix.sync.aligned.m8n8.trans.b16 %0, %1;" : "=r"(r) : "r"(v)); return r; }
__device__ __forceinline__ void attn_repair(const uint4 qx, const uint4 qy, uint32_t lb, int pass, int unit) {
    const int tid = tid_now(), g = (tid & 31) >> 2, t = tid & 3;
    float ss = ldsf(M_SS + pass * 4);
    if (ss == 0.f) ss = 1.f;
    const uint4 q0 = quad_transpose(qx.x, qx.z, qy.x, qy.z, t), q1 = quad_transpose(qx.y, qx.w, qy.y, qy.w, t);
    const char* kv = g_kv + (size_t)((cta_now() & 15) * 2 + pass) * 16 * KV_TILE + t * 2048 + g * 16;
    float o[4][4], m0 = -INFINITY, m1 = -INFINITY, l0 = 0.f, l1 = 0.f;
    #pragma unroll
    for (int j = 0; j < 4; j++) { o[j][0] = 0.f; o[j][1] = 0.f; o[j][2] = 0.f; o[j][3] = 0.f; }
    uint4 kf[8];
    #pragma unroll
    for (int i = 0; i < 8; i++) kf[i] = __ldcg(reinterpret_cast<const uint4*>(kv + 15 * KV_TILE + i * 128));
    #pragma unroll 1
    for (int b = 0; b < 32; b++) {
        uint4 vf[8];
        #pragma unroll
        for (int i = 0; i < 8; i++) vf[i] = __ldcg(reinterpret_cast<const uint4*>(kv + (b >> 1) * KV_TILE + (b & 1) * 1024 + 8192 + i * 128));
        float s[8][4];
        #pragma unroll
        for (int i = 0; i < 8; i++) {
            s[i][0] = 0.f; s[i][1] = 0.f; s[i][2] = 0.f; s[i][3] = 0.f;
            mma_f16(s[i], q0.x, q1.x, q0.y, q1.y, kf[i].x, kf[i].y); mma_f16(s[i], q0.z, q1.z, q0.w, q1.w, kf[i].z, kf[i].w);
        }
        #pragma unroll
        for (int i = 0; i < 8; i++) kf[i] = __ldcg(reinterpret_cast<const uint4*>(kv + (((b - 1) >> 1) & 15) * KV_TILE + (~b & 1) * 1024 + i * 128));
        float t0 = m0, t1 = m1;
        #pragma unroll
        for (int i = 0; i < 8; i++) { t0 = fmaxf(t0, fmaxf(s[i][0], s[i][1])); t1 = fmaxf(t1, fmaxf(s[i][2], s[i][3])); }
        t0 = quad_max(t0); t1 = quad_max(t1);
        const float a0 = ex2((m0 - t0) * ss), a1 = ex2((m1 - t1) * ss);
        m0 = t0; m1 = t1;
        l0 *= a0; l1 *= a1;
        #pragma unroll
        for (int j = 0; j < 4; j++) { o[j][0] *= a0; o[j][1] *= a0; o[j][2] *= a1; o[j][3] *= a1; }
        #pragma unroll
        for (int k = 0; k < 4; k++) {
            uint32_t pf[4];
            #pragma unroll
            for (int e = 0; e < 2; e++) {
                const float p0 = ex2((s[2*k+e][0] - m0) * ss), p1 = ex2((s[2*k+e][1] - m0) * ss), p2 = ex2((s[2*k+e][2] - m1) * ss), p3 = ex2((s[2*k+e][3] - m1) * ss);
                l0 += p0 + p1; l1 += p2 + p3;
                pf[2*e] = pack_f16(p0, p1); pf[2*e+1] = pack_f16(p2, p3);
            }
            mma_f16(o[0], pf[0], pf[1], pf[2], pf[3], movm(vf[2*k].x), movm(vf[2*k+1].x));
            mma_f16(o[1], pf[0], pf[1], pf[2], pf[3], movm(vf[2*k].y), movm(vf[2*k+1].y));
            mma_f16(o[2], pf[0], pf[1], pf[2], pf[3], movm(vf[2*k].z), movm(vf[2*k+1].z));
            mma_f16(o[3], pf[0], pf[1], pf[2], pf[3], movm(vf[2*k].w), movm(vf[2*k+1].w));
        }
    }
    const float i0 = 16.f * rcp(quad_sum(l0)), i1 = 16.f * rcp(quad_sum(l1));
    uint32_t* dst = reinterpret_cast<uint32_t*>(reinterpret_cast<char*>(g_o) + (o_offset() & ~48u) + (unit * 64 * D_ + pass * 512) * 2) + t;
    #pragma unroll
    for (int j = 0; j < 4; j++) {
        const uint32_t iv = lds32(M_IVS + pass * 64 + j * 16 + t * 4);
        dst[j * 4] = pack_bf16(o[j][0] * i0 * bf_lo(iv), o[j][1] * i0 * bf_hi(iv));
        dst[j * 4 + 4 * D_] = pack_bf16(o[j][2] * i1 * bf_lo(iv), o[j][3] * i1 * bf_hi(iv));
    }
    __syncwarp();
    mbar_arrive_elect(lb + B_OD + (pass * 2 + (tid >> 7)) * 8);
}

__device__ __forceinline__ void load_gu(uint32_t (&f)[64], uint32_t src, int warp, int lane) {
    const uint32_t row = (warp & 3) * 64 + (lane >> 4) * 8 + (lane & 7), ch = (lane >> 3) & 1, sw = (lane >> 1) & 3;
    const uint32_t a0 = base32(src + (warp >> 2) * 32768 + row * 64 + ((ch ^ sw) << 4)), a1 = base32(a0 ^ 32);
    #pragma unroll
    for (int i = 0; i < 16; i++) ldsm4t(f[4*i], f[4*i+1], f[4*i+2], f[4*i+3], ((i & 1) ? a1 : a0) + ((i >> 1) & 1) * 16384 + (i >> 2) * 1024);
}

__device__ __forceinline__ void arrive_loaded(uint32_t bar, const uint32_t (&f)[64], uint32_t zero) {
    uint32_t x = 0;
    #pragma unroll
    for (int i = 0; i < 16; i++) x |= f[4 * i];
    mbar_arrive_elect(bar + (x & zero));
}
__device__ __forceinline__ void flush(uint32_t (&o2)[10], const uint32_t (&o)[10]) {
    #pragma unroll
    for (int i = 0; i < 10; i++) o2[i] = hadd2(o2[i], o[i]);
}
__device__ __forceinline__ void attention_phase(int L, uint32_t lb, int wg, uint32_t (&qa)[8], uint32_t (&qb)[8], uint32_t (&SA)[32], uint32_t (&SB_)[32], uint64_t dk0, uint64_t dv0, uint32_t ca, uint32_t (&wa)[64], uint32_t zero, uint32_t sixteen) {
    uint32_t PA[32], PB[32], oa[10], ob[10], oa2[10], ob2[10];
    Shift ha, hb;
    uint32_t fail = (lds32(M_SS) ? 3u : 0u) | (lds32(M_SS + 4) ? 12u : 0u);
    ca += base32(fail) >> 4;
    const uint32_t oo = o_offset(), odb = lb + B_OD + wg * 8;
    constexpr uint64_t SL = R_SLOT >> 4, KH = 4096 >> 4;
    uint64_t dkd = dk0 + ((A_KP - A_RING) >> 4);
    unit_start(SA, ha, oa2);
    exp_tile(SA, PA, ha, ca, sixteen);
    #pragma unroll
    for (int i = 0; i < 10; i++) { ob[i] = 0u; ob2[i] = 0u; }
    hb = ha;
    mbar_spin(lb + B_KS + 8, 0);
    mbar_spin(lb + B_ONE, 0);
    #pragma unroll 1
    for (int it = 0; ; it++) {
        const uint32_t ph = it & 1;
        uint32_t qsw = 0;
        #pragma unroll
        for (int u = 0; u < 4; u++) {
            const uint64_t dk = opaque(dk0) + u * SL, dv = opaque(dv0) + u * SL;
            wg_fence();
            if (u == 0) { wg_qk_acc(SB_, qb[4], qb[5], qb[6], qb[7], dkd + KH); wg_commit(); }
            if (u == 0) issue_pv<true>(oa, PA, dv); else issue_pv<false>(oa, PA, dv);
            wg_qk_init(SA, qa[0], qa[1], qa[2], qa[3], dk);
            wg_qk_acc(SA, qa[4], qa[5], qa[6], qa[7], dk + KH);
            wg_commit();
            wg_wait<1>();
            pin(SB_); pin(ob);
            if (u == 0) {
                mbar_arrive_elect_p(lb + B_AE + 24, it);
                flush(ob2, ob);
                if (__builtin_expect((it & 3) == 0, 0)) {
                    if (it) unit_end<0, 1>(ob2, hb.bad, odb, oo, fail, lds128(M_IVS + (oo & 48)));
                    unit_start(SB_, hb, ob2);
                }
            } else mbar_arrive_elect(lb + B_AE + 8 * (u - 1));
            if (u == 3) swap_q(qb, qsw ? qsw + 8192 : 0u);
            uint32_t ready = 0;
            if (u < 3) ready = mbar_test(lb + B_AF + 8 * (u + 1), ph);
            exp_tile(SB_, PB, hb, ca, sixteen);
            wg_fence();
            if (u == 0) issue_pv<true>(ob, PB, dv); else issue_pv<false>(ob, PB, dv);
            wg_qk_init(SB_, qb[0], qb[1], qb[2], qb[3], dk);
            if (u < 3) wg_qk_acc(SB_, qb[4], qb[5], qb[6], qb[7], dk + KH);
            wg_commit();
            if (u < 3) mbar_spin_unless(ready, lb + B_AF + 8 * (u + 1), ph);
            wg_wait<1>();
            pin(SA); pin(oa);
            if (u == 2) { qsw = it == 3 ? A_QX + tid_now() * 16 : 0u; swap_q(qa, qsw); }
            if (u == 3) {
                flush(oa2, oa);
                if (__builtin_expect((it & 3) == 3, 0)) {
                    TL(0, L * 32 + 7 + (it >> 2)); CK(0, L * 32 + 1 + (it >> 2));
                    if (it == 7) goto done;
                    unit_end<0, 0>(oa2, ha.bad, odb, oo, fail, lds128(M_IVS + (oo & 48)));
                    unit_start(SA, ha, oa2);
                }
            }
            exp_tile(SA, PA, ha, ca, sixteen);
        }
        mbar_spin(lb + B_AF, ph ^ 1);
        wg_wait<0>();
        dkd = dk0 + 3 * SL;
    }
done:
    const uint4 iv = lds128(M_IVS + 64 + (oo & 48));
    mbar_spin(lb + B_GU, 0);
    load_gu(wa, F_GU0, tid_now() >> 5, tid_now() & 31);
    unit_end<1, 0>(oa2, ha.bad, odb, oo, fail, iv);
    wg_wait<0>();
    pin(ob);
    mbar_arrive_elect(lb + B_AE + 24);
    flush(ob2, ob);
    unit_end<1, 1>(ob2, hb.bad, odb, oo, fail, iv);
    arrive_loaded(lb + B_FG, wa, zero);
    if (__builtin_expect(fail != 0, 0)) {
        uint4* const qs = &g_qsave[cta_now()][0][tid_now()];
        qs[4 * 256] = make_uint4(qa[0], qa[1], qa[2], qa[3]); qs[5 * 256] = make_uint4(qa[4], qa[5], qa[6], qa[7]);
        qs[6 * 256] = make_uint4(qb[0], qb[1], qb[2], qb[3]); qs[7 * 256] = make_uint4(qb[4], qb[5], qb[6], qb[7]);
        #pragma unroll
        for (int i = 0; i < 16; i++) qs[(8 + i) * 256] = make_uint4(wa[4*i], wa[4*i+1], wa[4*i+2], wa[4*i+3]);
        #pragma unroll 1
        for (int r = 0; r < 4; r++)
            if ((fail >> r) & 1) attn_repair(__ldcg(qs + r * 512), __ldcg(qs + r * 512 + 256), lb, r >> 1, r & 1);
        #pragma unroll
        for (int i = 0; i < 16; i++) { const uint4 v = __ldcg(qs + (8 + i) * 256); wa[4*i] = v.x; wa[4*i+1] = v.y; wa[4*i+2] = v.z; wa[4*i+3] = v.w; }
    }
    TL(0, L * 32 + 9); CK(0, L * 32 + 8);
}

__device__ __forceinline__ void oproj_steps(float (&acc)[64], uint32_t lb, int wg, int k0, int k1) {
    const bool leader = (tid_now() & 127) == 0;
    #pragma unroll 1
    for (int k = k0; k < k1; k++) {
        const uint32_t st = k & 3;
        mbar_spin(lb + B_OF + 8 * st, (k >> 2) & 1);
        const uint64_t da = desc_sw128(o_a(st) + wg * 8192, 16, 1024);
        const uint64_t db = desc_sw128(o_b(st), 8192, 1024);
        wg_fence();
        #pragma unroll
        for (int kk = 0; kk < 4; kk++) wg_gemm_n128(acc, da + kk * 2, db + kk * 128);
        wg_commit();
        wg_wait<1>();
        if (leader && k > 0) mbar_arrive(lb + B_OE + 8 * ((k - 1) & 3));
    }
}

__device__ __forceinline__ uint4 best_of(const uint4& e, int sh, int mask) {
    const uint32_t m = redux_max(e.x), row = redux_min(e.x == m ? e.w : 0x7FFFFFFFu), src = (row >> sh) & mask;
    return make_uint4(m, __shfl_sync(0xffffffffu, e.y, src), __shfl_sync(0xffffffffu, e.z, src), row);
}
__device__ __forceinline__ void load_wd(uint32_t (&wd)[64], uint32_t lb, int warp, int lane) {
    mbar_spin(lb + B_WD, 0);
    const uint32_t a0 = F_WD + warp * 8192 + ((lane >> 4) * 8 + (lane & 7)) * 128, ch = ((lane >> 3) & 1) ^ (lane & 7);
    #pragma unroll
    for (int i = 0; i < 16; i++) ldsm4t(wd[4*i], wd[4*i+1], wd[4*i+2], wd[4*i+3], base32(a0 + ((ch ^ (i & 6)) << 4)) + (i >> 3) * 4096 + (i & 1) * 2048);
}
__device__ __forceinline__ void stage_tile(const uint32_t (&xa)[4], const uint32_t (&xv)[32]) {
    #pragma unroll
    for (int m = 0; m < 8; m++) stsm4(xa[m & 3] + (m < 4 ? YT0 - XT0 : YT1 - XT0), xv[4*m], xv[4*m+1], xv[4*m+2], xv[4*m+3]);
    fence_async_smem();
    __syncwarp();
}

__device__ __forceinline__ void tail_phase(int L, uint32_t lb, int wg, const uint32_t (&wa)[64]) {
    const int c = cta_now(), blk = c >> 3, cb = c & 7, tid = tid_now();
    const int lane = tid & 31, w = (tid >> 5) & 3, g = lane >> 2, t = lane & 3;
    const int lr0 = wg * 64 + w * 16 + g;
    uint32_t xa[4];
    #pragma unroll
    for (int m = 0; m < 4; m++) xa[m] = base32(XT0 + (wg * 64 + w * 16 + (lane & 15)) * 128 + (((lane >> 4) ^ (lane & 7) ^ (2 * m)) << 4));
    uint32_t xv[32];
    const bool ffn = c < NFC;
    uint32_t wb[64], wd[64];
    float own[6];
    {
        float acc[64];
        #pragma unroll
        for (int i = 0; i < 64; i++) acc[i] = 0.f;
        pin(acc);
        float2 rs0 = make_float2(0.f, 0.f), rs1 = rs0;
        if (L) { rs0 = __ldcg(&g_x.rs1[blk * 128 + lr0]); rs1 = __ldcg(&g_x.rs1[blk * 128 + lr0 + 8]); }
        oproj_steps(acc, lb, wg, 0, 8);
        mbar_spin(lb + B_RES, 0);
        #pragma unroll
        for (int m = 0; m < 8; m++) ldsm4(xv[4*m], xv[4*m+1], xv[4*m+2], xv[4*m+3], xa[m & 3] + (m < 4 ? 0 : XT1 - XT0));
        if (L) {
            const int d = (int)lds32(M_RT + 12) - (blk * 128 + lr0);
            const Ln2 k0 = ln2_coef(rs0.y, d == 0 ? 0.f : rsq(rs0.x + LN_EPS)), k1 = ln2_coef(rs1.y, d == 8 ? 0.f : rsq(rs1.x + LN_EPS));
            #pragma unroll
            for (int j = 0; j < 16; j++) { xv[2*j] = add_ln2(xv[2*j], k0); xv[2*j+1] = add_ln2(xv[2*j+1], k1); }
        }
        pin(xv);
        oproj_steps(acc, lb, wg, 8, 16);
        uint32_t wv[16];
        #pragma unroll
        for (int i = 0; i < 4; i++) ldsm4(wv[4*i], wv[4*i+1], wv[4*i+2], wv[4*i+3], (lane & 1) ? M_RED + (lane >> 3) * 16 + i * 64 : M_RED + 256);
        wg_wait<0>();
        pin(acc);
        if ((tid & 127) == 0) mbar_arrive(lb + B_OE + 24);
        TL(0, L * 32 + 11); CK(0, L * 32 + 13);
        float sa[4] = {0.f, 0.f, 0.f, 0.f}, sb[4] = {0.f, 0.f, 0.f, 0.f}, sc[4] = {0.f, 0.f, 0.f, 0.f};
        float sd[4] = {0.f, 0.f, 0.f, 0.f}, se[4] = {0.f, 0.f, 0.f, 0.f};
        #pragma unroll
        for (int m = 0; m < 8; m++) {
            #pragma unroll
            for (int i = 0; i < 4; i++) xv[4*m+i] = badd2(xv[4*m+i], pack_bf16(acc[8*m + 2*i], acc[8*m + 2*i + 1]));
            mma_bf16(sa, xv[4*m], xv[4*m+1], xv[4*m+2], xv[4*m+3], wv[2*m], wv[2*m+1]);
            mma_bf16_k8(sb, xv[4*m], xv[4*m+1], xv[4*m]); mma_bf16_k8(sc, xv[4*m], xv[4*m+1], xv[4*m+1]);
            mma_bf16_k8(sd, xv[4*m+2], xv[4*m+3], xv[4*m+2]); mma_bf16_k8(se, xv[4*m+2], xv[4*m+3], xv[4*m+3]);
        }
        const float q0 = (g & 1) ? sb[1] + sd[1] : sb[0] + sd[0], q1 = (g & 1) ? sc[3] + se[3] : sc[2] + se[2];
        if (t == (g >> 1)) {
            st_x128(&g_x.part[L][blk][cb][lr0], __float_as_uint(sa[0]), __float_as_uint(q0), __float_as_uint(sa[1]), 0u);
            st_x128(&g_x.part[L][blk][cb][lr0 + 8], __float_as_uint(sa[2]), __float_as_uint(q1), __float_as_uint(sa[3]), 0u);
        }
        __syncwarp();
        own[0] = sa[0]; own[1] = __shfl_sync(0xffffffffu, q0, (lane & 28) + (g >> 1)); own[2] = sa[1];
        own[3] = sa[2]; own[4] = __shfl_sync(0xffffffffu, q1, (lane & 28) + (g >> 1)); own[5] = sa[3];
    }
    TL(0, L * 32 + 12);
    load_gu(wb, F_GU1, tid >> 5, lane);
    stage_tile(xa, xv);
    float mean[2], rstd[2], score[2];
    {
        const bool o0 = cb == 2 * t, o1 = cb == 2 * t + 1;
        const uint4* const psrc = &g_x.part[L][blk][2 * t][lr0];
        uint4 p[4];
        uint32_t n = 0;
        #pragma unroll 1
        do {
            p[0] = ld_x128(psrc); p[1] = ld_x128(psrc + 128); p[2] = ld_x128(psrc + 8); p[3] = ld_x128(psrc + 136);
            poll_tick(n);
        } while (warp_any((!o0 && (p[0].w | p[2].w) != 0) || (!o1 && (p[1].w | p[3].w) != 0)));
        mbar_arrive_elect_p(lb + B_XS, L == 0);
        const float ws = ldsf(M_WS);
        #pragma unroll
        for (int h = 0; h < 2; h++) {
            const float su = quad_sum((o0 ? own[3*h] : __uint_as_float(p[2*h].x)) + (o1 ? own[3*h] : __uint_as_float(p[2*h+1].x)));
            const float sq = quad_sum((o0 ? own[3*h+1] : __uint_as_float(p[2*h].y)) + (o1 ? own[3*h+1] : __uint_as_float(p[2*h+1].y)));
            const float sd = quad_sum((o0 ? own[3*h+2] : __uint_as_float(p[2*h].z)) + (o1 ? own[3*h+2] : __uint_as_float(p[2*h+1].z)));
            mean[h] = su * (1.f / D_);
            const float var = fmaxf(sq * (1.f / D_) - mean[h] * mean[h], 0.f);
            rstd[h] = rsq(var + LN_EPS);
            score[h] = rstd[h] * (sd - mean[h] * ws);
            if (L && t == h) { const Ln2 k = ln2_coef(mean[h], rstd[h]); sts128(XT0 + (lr0 + 8 * h) * 16, k.nm, k.rh, k.rl, k.c); }
            if (L == 0 && cb == 0 && t == h) st_x64(&g_x.rs1[blk * 128 + lr0 + 8 * h], __float_as_uint(var), __float_as_uint(mean[h]));
        }
    }
    TL(0, L * 32 + 13);
    uint4 f;
    {
        const uint32_t k0 = order_bits(score[0]), k1 = order_bits(score[1]);
        const bool up = k1 > k0;
        const uint32_t kb = max(k0, k1), row = blk * 128 + lr0 + (up ? 8 : 0), m = redux_max(kb);
        if (redux_min(kb == m ? row : 0x7FFFFFFFu) == row && t == 0) sts128(M_SR + (tid >> 5) * 16, kb, __float_as_uint(up ? mean[1] : mean[0]), __float_as_uint(up ? rstd[1] : rstd[0]), row);
        named_sync(NB_CONS, 256);
        f = best_of(lds128(M_SR + (lane & 7) * 16), 4, 7);
        if (tid < 16) st_x128(&g_x.hdr[L][tid * 8 + cb][blk], f.x, f.y, f.z, f.w);
        const int d = (int)f.w - (blk * 128 + lr0);
        if ((d & ~8) == 0) {
            #pragma unroll
            for (int b = 0; b < 4; b++)
                st_x128(&g_x.cand[L][blk][cb * 64 + b * 16 + t * 4], d ? xv[8*b+1] : xv[8*b], d ? xv[8*b+3] : xv[8*b+2], d ? xv[8*b+5] : xv[8*b+4], d ? xv[8*b+7] : xv[8*b+6]);
        }
        __syncwarp();
    }
    TL(0, L * 32 + 28);
    if (tid == 0) sts32(M_CR, f.w);
    __syncwarp();
    mbar_arrive_elect_p(lb + B_XS, L);
    load_wd(wd, lb, tid >> 5, lane);
    TL(0, L * 32 + 25);
    uint4 e;
    {
        uint32_t n = 0;
        #pragma unroll 1
        do { e = ld_x128(&g_x.hdr[L][c][lane & 15]); poll_tick(n); } while (warp_any(e.w == EMPTY && (lane & 15) != blk));
        if ((lane & 15) == blk) e = f;
        e = best_of(e, 7, 15);
    }
    TL(0, L * 32 + 14);
    if (tid == 0) sts128(M_RT + 16 * L, (e.x & 0x80000000u) ? e.x ^ 0x80000000u : ~e.x, e.y, e.z, e.w);
    if (tid == 0) mbar_arrive(lb + B_RT);
    if (ffn) {
        const uint32_t* src = &g_x.cand[L][e.w >> 7][(tid >> 5) * 32 + t * 4];
        const Ln2 kx = ln2_coef(__uint_as_float(e.y), __uint_as_float(e.z));
        uint4 x[4];
        uint32_t n = 0;
        #pragma unroll 1
        do {
            x[0] = ld_x128(src); x[1] = ld_x128(src + 16); x[2] = ld_x128(src + 256); x[3] = ld_x128(src + 272);
            poll_tick(n);
        } while (warp_any(x[0].x == EMPTY || x[1].x == EMPTY || x[2].x == EMPTY || x[3].x == EMPTY));
        TL(0, L * 32 + 15);
        float d[4][4];
        #pragma unroll
        for (int i = 0; i < 4; i++) { d[i][0] = 0.f; d[i][1] = 0.f; d[i][2] = 0.f; d[i][3] = 0.f; }
        #pragma unroll
        for (int k = 0; k < 8; k++) {
            const uint32_t b0 = ln2((k & 1) ? x[k >> 1].z : x[k >> 1].x, kx), b1 = ln2((k & 1) ? x[k >> 1].w : x[k >> 1].y, kx);
            const uint32_t* f = (k < 4 ? wa : wb) + (k & 3) * 16;
            #pragma unroll
            for (int i = 0; i < 4; i++) mma_bf16(d[i], f[4*i], f[4*i+1], f[4*i+2], f[4*i+3], b0, b1);
        }
        #pragma unroll
        for (int h = 0; h < 2; h++) {
            const float a = (t & 1) ? d[1][2*h] : d[0][2*h], b = (t & 1) ? d[3][2*h] : d[2][2*h];
            stsf(M_RED + ((tid >> 5) * 64 + t * 16 + h * 8 + g) * 4, (t & 2) ? b : a);
        }
        named_sync(NB_CONS, 256);
        TL(0, L * 32 + 16);
        float s0 = 0.f, s1 = 0.f;
        #pragma unroll
        for (int i = 0; i < 8; i++) { const float2 v = lds64f(base32(M_RED + lane * 8) + i * 256); s0 += v.x; s1 += v.y; }
        const uint32_t mine = pack_bf16(s0, s1), other = __shfl_xor_sync(0xffffffffu, mine, 16);
        const uint32_t gv = lane < 16 ? mine : other, uv = lane < 16 ? other : mine;
        const float g0 = bf_lo(gv), g1 = bf_hi(gv);
        const uint32_t hv = bmul2(pack_bf16(g0 * rcp(1.f + __expf(-g0)), g1 * rcp(1.f + __expf(-g1))), uv);
        uint32_t hb[4];
        #pragma unroll
        for (int i = 0; i < 4; i++) hb[i] = __shfl_sync(0xffffffffu, hv, 4 * i + t);
        float y[8][4];
        #pragma unroll
        for (int i = 0; i < 8; i++) {
            y[i][0] = 0.f; y[i][1] = 0.f; y[i][2] = 0.f; y[i][3] = 0.f;
            mma_bf16(y[i], wd[8*i], wd[8*i+1], wd[8*i+2], wd[8*i+3], hb[0], hb[1]);
            mma_bf16(y[i], wd[8*i+4], wd[8*i+5], wd[8*i+6], wd[8*i+7], hb[2], hb[3]);
        }
        float* dst = &g_x.ypart[L][(tid >> 5) * 16 + t * 4][c][g];
        #pragma unroll
        for (int i = 0; i < 2; i++)
            #pragma unroll
            for (int h = 0; h < 2; h++) {
                const float a = (t & 1) ? y[2 + i][2*h] : y[i][2*h], b = (t & 1) ? y[6 + i][2*h] : y[4 + i][2*h];
                st_x32(dst + (i * 2 + h) * (NFC * 8), __float_as_uint((t & 2) ? b : a));
            }
    }
    __syncwarp();
    mbar_arrive_elect(lb + B_FD);
    TL(0, L * 32 + 17);
}

__device__ __forceinline__ void qkv_load_w(const Maps& mp, uint32_t dst, int k, uint32_t fb) { tma_load3(dst, &mp.wqkv, (blockIdx.x & 15) * 64, k * 64, 0, fb); }
__device__ __forceinline__ void qkv_load_x(const CUtensorMap* tx, uint32_t sa, int k, uint32_t fb) {
    #pragma unroll
    for (int a = 0; a < 2; a++) tma_load(sa + a * 16384, tx, k * 64, (blockIdx.x >> 4) * 256 + a * 128, fb);
}
__device__ __forceinline__ void producer_role(const Maps& mp) {
    const int c = blockIdx.x, mt = c >> 4, nt = c & 15, blk = c >> 3, cb = c & 7;
    const uint64_t pol = policy_evict_first();
    #pragma unroll 1
    for (int L = 0; L < 2; L++) {
        const uint32_t lb = M_BAR + L * BAR_SET;
        const CUtensorMap* tx = &mp.x[L];
        mbar_expect_tx(lb + B_SW, 49152);
        if (L == 0) {
            mbar_nap(lb + B_QF, 0);
            qkv_load_w(mp, SD_W, mt * 2, lb + B_SW);
            qkv_load_w(mp, SD_W + 24576, mt * 2 + 1, lb + B_SW);
        }
        {
            uint32_t st = 0, ph = L;
            #pragma unroll 1
            for (int k = L ? 0 : 3; k < 16; k++) {
                mbar_sleep(k < 2 ? M_BAR + (k ? B_FD : B_XS) : lb + B_QE + 8 * st, k < 2 ? 0 : ph);
                const uint32_t fb = lb + B_QF + 8 * st, sa = SB + st * Q_STB;
                mbar_expect_tx(fb, Q_STB);
                qkv_load_w(mp, sa + Q_ABYTES, k, fb);
                if (k == 0) {
                    __nanosleep(800);
                    flags16_wait(g_x.x[mt]);
                    fence_async_global();
                    mbar_nap(M_BAR + B_RT, 0);
                    TL(256, 32);
                }
                qkv_load_x(tx, sa, k, fb);
                if (L && k >= 3 && k < 7) tma_load(SD_W + (k - 3) * 12288, &mp.r, c * 24, (k - 3) * 256, lb + B_SW);
                if (++st == 3) { st = 0; ph ^= 1; }
            }
        }
        mbar_sleep(lb + B_QE, 1);
        TL(256, L * 32 + 26);
        mbar_arrive(lb + B_AF);
        {
            const char* kv = g_kv + (size_t)nt * 32 * KV_TILE;
            const uint8_t* fl = g_x.kv[L][nt * 2];
            __nanosleep(800);
            #pragma unroll 1
            for (int j = 1; j < 4; j++) {
                flag_wait(fl + ((2 * mt + j + 1) & 15));
                fence_async_global();
                const uint32_t bytes = j == 1 ? 8192 : 16384;
                mbar_expect_tx(lb + B_AF + 8 * j, bytes);
                bulk_load(A_RING + j * R_SLOT, kv + ((2 * mt + j) & 15) * KV_TILE, bytes, lb + B_AF + 8 * j);
                if (j == 1) TL(256, L * 32 + 21);
            }
            flags16_wait(fl);
            fence_async_global();
            #pragma unroll 1
            for (int it = 1; it < 8; it++) {
                #pragma unroll
                for (int u = 0; u < 4; u++) {
                    const char* src = kv + ((2 * mt + 4 * it + u) & 15) * KV_TILE;
                    const uint32_t fb = lb + B_AF + 8 * u, dst = A_RING + u * R_SLOT;
                    mbar_nap(lb + B_AE + 8 * u, (it - 1) & 1);
                    mbar_expect_tx(fb, 16384);
                    if (u < 3) bulk_load(dst, src, 16384, fb);
                    else {
                        bulk_load(dst + 8192, src + 8192, 8192, fb);
                        if (it == 3) {
                            flags16_wait(fl + 128);
                            fence_async_global();
                            kv += 16 * KV_TILE; src += 16 * KV_TILE;
                        }
                        bulk_load(dst, src, 8192, fb);
                    }
                }
            }
        }
        #pragma unroll 1
        for (int it = 0; it < 4; it++) {
            #pragma unroll
            for (int s = 0; s < 4; s++) {
                mbar_spin(lb + (it ? B_OE + 8 * s : s < 2 ? B_AE + 8 + 8 * s : B_FG), it ? (it - 1) & 1 : s < 2);
                const uint32_t fb = lb + B_OF + 8 * s;
                mbar_expect_tx(fb, 32768);
                #pragma unroll
                for (int b = 0; b < 2; b++)
                    tma_load5(o_b(s) + b * 8192, &mp.wo[it >> 1], cb * 128 + b * 64, (it & 1) * 8 + s * 2, fb);
                if (s == 0 && !(it & 1)) {
                    ctr_wait(g_x.o[L][blk][it >> 1], 15);
                    fence_async_global();
                    TL(256, L * 32 + 10);
                }
                tma_load(o_a(s), &mp.o, it * 256 + s * 64, blk * 128, fb);
            }
            if (it == 0) {
                mbar_spin(lb + B_AE + 24, 1);
                mbar_expect_tx(lb + B_RES, 32768);
                tma_load_s(XT0, tx, cb * 128, blk * 128, lb + B_RES, pol);
                tma_load_s(XT1, tx, cb * 128 + 64, blk * 128, lb + B_RES, pol);
            }
        }
        if (c < NFC) {
            #pragma unroll 1
            for (int i = 0; i < 4; i++) {
                mbar_spin(lb + B_OE + 16 + 8 * (i >> 1), 1);
                tma_load3_s(F_WD + i * 16384, &mp.d, 0, c * 32, i * 4, lb + B_WD, pol);
            }
        }
    }
}

__global__ void __launch_bounds__(384, 1) k_all(const __grid_constant__ Maps mp, const bf16* __restrict__ x0, const bf16* __restrict__ wo, const bf16* __restrict__ w_down,
                                                const bf16* __restrict__ w_r, bf16* __restrict__ out, const uint64_t dk0, const uint64_t dv0, const uint32_t ca, const uint32_t zero, const uint32_t sixteen) {
    extern __shared__ __align__(1024) char smem[];
    if (smem_u32(smem) != SB) __trap();
    const int warp = warp_uniform(threadIdx.x >> 5), wg = warp >> 2;
    TL(0, 0);
    if (warp == 8) {
      if (elect_one()) {
        tm_prefetch(&mp.x[0]); tm_prefetch(&mp.wqkv);
        #pragma unroll
        for (int s = 0; s < 3; s++) { mbar_init(M_BAR + B_QF + 8 * s, 1); mbar_init(M_BAR + BAR_SET + B_QF + 8 * s, 1); }
        fence_mbar_init();
        #pragma unroll 1
        for (int s = 0; s < 3; s++) {
            const uint32_t sa = SB + s * Q_STB, fb = M_BAR + B_QF + 8 * s;
            mbar_expect_tx(fb, Q_STB);
            qkv_load_x(&mp.x[0], sa, s, fb);
            qkv_load_w(mp, sa + Q_ABYTES, s, fb);
        }
      }
      __syncwarp();
    } else if (warp > 8) {
        if (elect_one()) {
            const uint32_t o0 = warp == 9 ? B_AF : warp == 10 ? B_QE : B_AE, o1 = warp == 9 ? B_QE : warp == 10 ? B_AE : B_END, cnt = warp == 9 ? 1 : warp == 10 ? 2 : 8;
            #pragma unroll 1
            for (uint32_t o = o0; o < o1; o += 8) { const uint32_t n = o >= B_KS ? 4 : cnt; mbar_init(M_BAR + o, n); mbar_init(M_BAR + BAR_SET + o, n); }
            fence_mbar_init();
        }
        __syncwarp();
    }
    __syncthreads();
    if (wg == 2) {
        reg_dec<40>();
        if (warp > 8) side_role(mp, x0, wo, w_down, w_r, out);
        else if (elect_one()) producer_role(mp);
    } else {
        reg_inc<232>();
        #pragma unroll 1
        for (int L = 0; L < 2; L++) {
            const uint32_t lb = M_BAR + L * BAR_SET;
            uint32_t qa[8], qb[8], sa[32], sb[32], wa[64];
            qkv_phase(L, lb, wg, qa, qb, sa, sb);
            attention_phase(L, lb, wg, qa, qb, sa, sb, dk0, dv0, ca, wa, zero, sixteen);
            tail_phase(L, lb, wg, wa);
        }
    }
}

typedef CUresult (*EncodeFn)(CUtensorMap*, CUtensorMapDataType, cuuint32_t, void*, const cuuint64_t*, const cuuint64_t*, const cuuint32_t*,
                             const cuuint32_t*, CUtensorMapInterleave, CUtensorMapSwizzle, CUtensorMapL2promotion, CUtensorMapFloatOOBfill);

void make_map(EncodeFn enc, CUtensorMap* tm, const void* ptr, int rank, const cuuint64_t* dims, const cuuint64_t* strides, const cuuint32_t* box, CUtensorMapSwizzle sw) {
    const cuuint32_t es[5] = {1, 1, 1, 1, 1};
    enc(tm, CU_TENSOR_MAP_DATA_TYPE_BFLOAT16, rank, const_cast<void*>(ptr), dims, strides, box, es, CU_TENSOR_MAP_INTERLEAVE_NONE, sw,
        box[0] == 64 ? CU_TENSOR_MAP_L2_PROMOTION_L2_128B : CU_TENSOR_MAP_L2_PROMOTION_NONE, CU_TENSOR_MAP_FLOAT_OOB_FILL_NONE);
}
void make_map2(EncodeFn enc, CUtensorMap* tm, const void* ptr, uint64_t cols, uint64_t rows, uint32_t bc, uint32_t br, CUtensorMapSwizzle sw) {
    const cuuint64_t dims[2] = {cols, rows}, strides[1] = {cols * 2};
    const cuuint32_t box[2] = {bc, br};
    make_map(enc, tm, ptr, 2, dims, strides, box, sw);
}

}

extern "C" void kernel_launch(void* const* d_in, const int* in_sizes, int n_in, void* d_out, int out_size) {
    const bf16* x0 = (const bf16*)d_in[0];
    const bf16* wqkv = (const bf16*)d_in[1];
    const bf16* wo = (const bf16*)d_in[2];
    const bf16* w_r = (const bf16*)d_in[4];
    const bf16* w_gate = (const bf16*)d_in[5];
    const bf16* w_up = (const bf16*)d_in[6];
    const bf16* w_down = (const bf16*)d_in[7];

    EncodeFn enc = nullptr;
    cudaDriverEntryPointQueryResult qr;
    cudaGetDriverEntryPoint("cuTensorMapEncodeTiled", (void**)&enc, cudaEnableDefault, &qr);
    void *p_o, *p_x1;
    cudaGetSymbolAddress(&p_o, g_o); cudaGetSymbolAddress(&p_x1, g_x1);
    const CUtensorMapSwizzle S128 = CU_TENSOR_MAP_SWIZZLE_128B, S64 = CU_TENSOR_MAP_SWIZZLE_64B, S0 = CU_TENSOR_MAP_SWIZZLE_NONE;
    Maps mp;
    make_map2(enc, &mp.x[0], x0, D_, S_, 64, 128, S128); make_map2(enc, &mp.x[1], p_x1, D_, S_, 64, 128, S128);
    make_map2(enc, &mp.o, p_o, D_, S_, 64, 128, S128);
    {
        const cuuint64_t dims[3] = {D_, D_, 3}, strides[2] = {3 * D_ * 2, D_ * 2};
        const cuuint32_t box[3] = {64, 64, 3};
        make_map(enc, &mp.wqkv, wqkv, 3, dims, strides, box, S128);
    }
    make_map2(enc, &mp.r, wqkv, 3 * D_, D_, 24, 256, S0);
    make_map2(enc, &mp.g, w_gate, FF, D_, 32, 256, S64); make_map2(enc, &mp.u, w_up, FF, D_, 32, 256, S64);
    for (int p = 0; p < 2; p++) {
        const cuuint64_t dims[5] = {D_, 2, 4, 4, 16}, strides[4] = {D_ * 2, 8 * D_ * 2, 2 * D_ * 2, 64 * D_ * 2};
        const cuuint32_t box[5] = {64, 2, 4, 4, 2};
        make_map(enc, &mp.wo[p], wo + (size_t)p * 32 * D_, 5, dims, strides, box, S128);
    }
    {
        const cuuint64_t dims[3] = {64, FF, 16}, strides[2] = {D_ * 2, 128};
        const cuuint32_t box[3] = {64, 32, 4};
        make_map(enc, &mp.d, w_down, 3, dims, strides, box, S128);
    }
    cudaFuncSetAttribute(k_all, cudaFuncAttributeMaxDynamicSharedMemorySize, K_SMEM);
    k_all<<<128, 384, K_SMEM, cudaStreamPerThread>>>(mp, x0, wo, w_down, w_r, (bf16*)d_out, desc_plain(A_RING, 2048, 128), desc_plain(A_RING + 8192, 128, 2048), 0x64A264A2u, 0u, 16u);
}
```

```cpp
#include <cuda_runtime.h>
#include <cuda_bf16.h>
#include <cuda_fp16.h>
#include <cuda.h>
#include <cudaTypedefs.h>
#include <stdint.h>

namespace {

typedef __nv_bfloat16 bf16;

constexpr int S_ = 2048, D_ = 1024, NH = 32, FF = 3584, NFC = FF / 32;
constexpr float LN_EPS = 1e-5f;
constexpr float QSCALE = 0.17677669529663687f * 1.4426950408889634f;
constexpr uint32_t EMPTY = 0xFFFFFFFFu;

constexpr int KV_TILE = 16384;
__device__ __align__(1024) char g_kv[NH * 16 * KV_TILE];
__device__ __align__(1024) bf16 g_o[S_ * D_];
__device__ __align__(1024) bf16 g_x1[S_ * D_];
__device__ __align__(16) float2 g_cs[8][3 * D_];
__device__ __align__(16) float2 g_rs0[S_];
__device__ uint4 g_qsave[128][24][256];
struct Xchg {
    uint4 part[2][16][8][128];
    float ypart[2][128][NFC][8];
    uint32_t cand[2][16][D_ / 2];
    uint4 hdr[2][128][16];
    float2 rs1[S_];
    float fix[3 * D_];
    uint32_t x2row[D_ / 2];
    uint8_t kv[2][NH][128];
    int o[2][16][2][32];
    uint8_t x[8][128];
};
constexpr int FILL = (sizeof(Xchg) / 128 + 127) / 128 * 8;
union XchgFill { Xchg x; uint4 fill[128][FILL]; };
static_assert(FILL > 768 && FILL <= 1024, "exchange area");
__device__ __align__(128) XchgFill g_u;
#define g_x g_u.x
__device__ int g_pctr;

constexpr uint32_t SMEM_BASE = 1024;

__device__ __forceinline__ int tid_now() { int v; asm volatile("mov.u32 %0, %%tid.x;" : "=r"(v)); return v; }
__device__ __forceinline__ int cta_now() { int v; asm volatile("mov.u32 %0, %%ctaid.x;" : "=r"(v)); return v; }
__device__ __forceinline__ uint64_t opaque(uint64_t v) { uint64_t r; asm volatile("mov.b64 %0, %1;" : "=l"(r) : "l"(v)); return r; }
__device__ __forceinline__ uint32_t base32(uint32_t v) { uint32_t r; asm("mov.b32 %0, %1;" : "=r"(r) : "r"(v)); return r; }
__device__ __forceinline__ uint32_t smem_u32(const void* p) { return (uint32_t)__cvta_generic_to_shared(p); }
__device__ __forceinline__ void mbar_init(uint32_t bar, int cnt) { asm volatile("mbarrier.init.shared::cta.b64 [%0], %1;" :: "r"(bar), "r"(cnt) : "memory"); }
__device__ __forceinline__ void mbar_expect_tx(uint32_t bar, uint32_t bytes) { asm volatile("mbarrier.arrive.expect_tx.shared::cta.b64 _, [%0], %1;" :: "r"(bar), "r"(bytes) : "memory"); }
__device__ __forceinline__ void mbar_arrive(uint32_t bar) { asm volatile("mbarrier.arrive.shared::cta.b64 _, [%0];" :: "r"(bar) : "memory"); }
__device__ __forceinline__ void mbar_sleep(uint32_t bar, uint32_t parity) {
    asm volatile("{\n.reg .pred p;\n.reg .u32 n;\nmov.u32 n, 0;\n"
                 "LAB_WAIT:\nmbarrier.try_wait.parity.shared::cta.b64 p, [%0], %1, 0x10000;\n@p bra LAB_DONE;\n"
                 "add.u32 n, n, 1;\nsetp.lt.u32 p, n, 0x10000;\n@p bra LAB_WAIT;\ntrap;\nLAB_DONE:\n}" :: "r"(bar), "r"(parity) : "memory");
}
__device__ __forceinline__ void mbar_nap(uint32_t bar, uint32_t parity) {
    asm volatile("{\n.reg .pred p;\nLAB_WAIT:\nmbarrier.try_wait.parity.shared::cta.b64 p, [%0], %1, 0x10000;\n@!p bra LAB_WAIT;\n}" :: "r"(bar), "r"(parity) : "memory");
}
__device__ __forceinline__ void mbar_spin(uint32_t bar, uint32_t parity) {
    asm volatile("{\n.reg .pred p;\nLAB_WAIT:\nmbarrier.try_wait.parity.shared::cta.b64 p, [%0], %1;\n@!p bra LAB_WAIT;\n}" :: "r"(bar), "r"(parity) : "memory");
}
__device__ __forceinline__ uint32_t mbar_test(uint32_t bar, uint32_t parity) {
    uint32_t ok;
    asm volatile("{\n.reg .pred p;\nmbarrier.test_wait.parity.shared::cta.b64 p, [%1], %2;\nselp.u32 %0, 1, 0, p;\n}" : "=r"(ok) : "r"(bar), "r"(parity) : "memory");
    return ok;
}
__device__ __forceinline__ void mbar_spin_unless(uint32_t ok, uint32_t bar, uint32_t parity) {
    asm volatile("{\n.reg .pred p;\nsetp.ne.u32 p, %2, 0;\n@p bra LAB_DONE;\nLAB_WAIT:\nmbarrier.try_wait.parity.shared::cta.b64 p, [%0], %1;\n@!p bra LAB_WAIT;\nLAB_DONE:\n}"
                 :: "r"(bar), "r"(parity), "r"(ok) : "memory");
}
__device__ __forceinline__ bool elect_one() {
    uint32_t r;
    asm volatile("{\n.reg .pred p;\nelect.sync _|p, 0xffffffff;\nselp.u32 %0, 1, 0, p;\n}" : "=r"(r));
    return r != 0;
}
__device__ __forceinline__ void mbar_arrive_elect(uint32_t bar) {
    asm volatile("{\n.reg .pred p;\nelect.sync _|p, 0xffffffff;\n@p mbarrier.arrive.shared::cta.b64 _, [%0];\n}" :: "r"(bar) : "memory");
}
__device__ __forceinline__ void mbar_arrive_elect_p(uint32_t bar, uint32_t on) {
    asm volatile("{\n.reg .pred p, q;\nelect.sync _|p, 0xffffffff;\nsetp.ne.and.u32 q, %1, 0, p;\n@q mbarrier.arrive.shared::cta.b64 _, [%0];\n}" :: "r"(bar), "r"(on) : "memory");
}
__device__ __forceinline__ int warp_uniform(int v) { return __shfl_sync(0xffffffffu, v, 0); }
__device__ __forceinline__ void fence_mbar_init() { asm volatile("fence.mbarrier_init.release.cluster;" ::: "memory"); }
__device__ __forceinline__ void fence_async_smem() { asm volatile("fence.proxy.async.shared::cta;" ::: "memory"); }
__device__ __forceinline__ void fence_async_global() { asm volatile("fence.proxy.async.global;" ::: "memory"); }
__device__ __forceinline__ void named_sync(int id, int n) { asm volatile("bar.sync %0, %1;" :: "r"(id), "r"(n) : "memory"); }
__device__ __forceinline__ void named_arrive(int id, int n) { asm volatile("bar.arrive %0, %1;" :: "r"(id), "r"(n) : "memory"); }
__device__ __forceinline__ void bulk_load(uint32_t dst, const void* src, uint32_t bytes, uint32_t bar) {
    asm volatile("cp.async.bulk.shared::cluster.global.mbarrier::complete_tx::bytes [%0], [%1], %2, [%3];" :: "r"(dst), "l"(src), "r"(bytes), "r"(bar) : "memory");
}
__device__ __forceinline__ void bulk_store(void* dst, uint32_t src, uint32_t bytes) {
    asm volatile("cp.async.bulk.global.shared::cta.bulk_group [%0], [%1], %2;" :: "l"(dst), "r"(src), "r"(bytes) : "memory");
}
__device__ __forceinline__ void bulk_commit() { asm volatile("cp.async.bulk.commit_group;" ::: "memory"); }
__device__ __forceinline__ void bulk_wait() { asm volatile("cp.async.bulk.wait_group 0;" ::: "memory"); }
__device__ __forceinline__ void l2_prefetch(const void* src, uint32_t bytes) {
    asm volatile("cp.async.bulk.prefetch.L2.global [%0], %1;" :: "l"(src), "r"(bytes) : "memory");
}
__device__ __forceinline__ void tma_load(uint32_t dst, const CUtensorMap* tm, int c0, int c1, uint32_t bar) {
    asm volatile("cp.async.bulk.tensor.2d.shared::cluster.global.mbarrier::complete_tx::bytes [%0], [%1, {%3, %4}], [%2];"
                 :: "r"(dst), "l"(tm), "r"(bar), "r"(c0), "r"(c1) : "memory");
}
__device__ __forceinline__ void tma_load3(uint32_t dst, const CUtensorMap* tm, int c0, int c1, int c2, uint32_t bar) {
    asm volatile("cp.async.bulk.tensor.3d.shared::cluster.global.mbarrier::complete_tx::bytes [%0], [%1, {%3, %4, %5}], [%2];"
                 :: "r"(dst), "l"(tm), "r"(bar), "r"(c0), "r"(c1), "r"(c2) : "memory");
}
__device__ __forceinline__ void tma_load5(uint32_t dst, const CUtensorMap* tm, int c0, int c4, uint32_t bar) {
    asm volatile("cp.async.bulk.tensor.5d.shared::cluster.global.mbarrier::complete_tx::bytes [%0], [%1, {%3, %5, %5, %5, %4}], [%2];"
                 :: "r"(dst), "l"(tm), "r"(bar), "r"(c0), "r"(c4), "r"(0) : "memory");
}
__device__ __forceinline__ uint64_t policy_evict_first() { uint64_t p; asm volatile("createpolicy.fractional.L2::evict_first.b64 %0, 1.0;" : "=l"(p)); return p; }
__device__ __forceinline__ void tma_load_s(uint32_t dst, const CUtensorMap* tm, int c0, int c1, uint32_t bar, uint64_t pol) {
    asm volatile("cp.async.bulk.tensor.2d.shared::cluster.global.mbarrier::complete_tx::bytes.L2::cache_hint [%0], [%1, {%3, %4}], [%2], %5;"
                 :: "r"(dst), "l"(tm), "r"(bar), "r"(c0), "r"(c1), "l"(pol) : "memory");
}
__device__ __forceinline__ void tma_load3_s(uint32_t dst, const CUtensorMap* tm, int c0, int c1, int c2, uint32_t bar, uint64_t pol) {
    asm volatile("cp.async.bulk.tensor.3d.shared::cluster.global.mbarrier::complete_tx::bytes.L2::cache_hint [%0], [%1, {%3, %4, %5}], [%2], %6;"
                 :: "r"(dst), "l"(tm), "r"(bar), "r"(c0), "r"(c1), "r"(c2), "l"(pol) : "memory");
}
__device__ __forceinline__ void tma_store(const CUtensorMap* tm, uint32_t src, int c0, int c1) {
    asm volatile("cp.async.bulk.tensor.2d.global.shared::cta.bulk_group [%0, {%2, %3}], [%1];" :: "l"(tm), "r"(src), "r"(c0), "r"(c1) : "memory");
}
__device__ __forceinline__ void tma_prefetch(const CUtensorMap* tm, int c0, int c1) {
    asm volatile("cp.async.bulk.prefetch.tensor.2d.L2.global [%0, {%1, %2}];" :: "l"(tm), "r"(c0), "r"(c1) : "memory");
}
__device__ __forceinline__ void tm_prefetch(const CUtensorMap* tm) { asm volatile("prefetch.tensormap [%0];" :: "l"(tm) : "memory"); }
__device__ __forceinline__ void wg_fence() { asm volatile("wgmma.fence.sync.aligned;" ::: "memory"); }
__device__ __forceinline__ void wg_commit() { asm volatile("wgmma.commit_group.sync.aligned;" ::: "memory"); }
template <int N> __device__ __forceinline__ void wg_wait() { asm volatile("wgmma.wait_group.sync.aligned %0;" :: "n"(N) : "memory"); }
template <int N> __device__ __forceinline__ void pin(uint32_t (&r)[N]) {
    #pragma unroll
    for (int i = 0; i < N; i++) asm volatile("" : "+r"(r[i]) :: "memory");
}
template <int N> __device__ __forceinline__ void pin(float (&r)[N]) {
    #pragma unroll
    for (int i = 0; i < N; i++) asm volatile("" : "+f"(r[i]) :: "memory");
}
template <int N> __device__ __forceinline__ void reg_inc() { asm volatile("setmaxnreg.inc.sync.aligned.u32 %0;" :: "n"(N)); }
template <int N> __device__ __forceinline__ void reg_dec() { asm volatile("setmaxnreg.dec.sync.aligned.u32 %0;" :: "n"(N)); }
__host__ __device__ constexpr uint64_t desc_plain(uint32_t addr, uint32_t lbo, uint32_t sbo) {
    return (uint64_t)((addr & 0x3FFFF) >> 4) | ((uint64_t)(lbo >> 4) << 16) | ((uint64_t)(sbo >> 4) << 32);
}
__host__ __device__ constexpr uint64_t desc_sw128(uint32_t addr, uint32_t lbo, uint32_t sbo) { return desc_plain(addr, lbo, sbo) | (1ull << 62); }
__host__ __device__ constexpr uint64_t desc_sw64(uint32_t addr, uint32_t lbo, uint32_t sbo) { return desc_plain(addr, lbo, sbo) | (2ull << 62); }

__device__ __forceinline__ uint32_t lds32(uint32_t a) { uint32_t v; asm volatile("ld.shared.b32 %0, [%1];" : "=r"(v) : "r"(a) : "memory"); return v; }
__device__ __forceinline__ uint32_t lds16(uint32_t a) { uint32_t v; asm volatile("ld.shared.u16 %0, [%1];" : "=r"(v) : "r"(a) : "memory"); return v; }
__device__ __forceinline__ float ldsf(uint32_t a) { return __uint_as_float(lds32(a)); }
__device__ __forceinline__ float2 lds64f(uint32_t a) { float2 v; asm volatile("ld.shared.v2.f32 {%0, %1}, [%2];" : "=f"(v.x), "=f"(v.y) : "r"(a) : "memory"); return v; }
__device__ __forceinline__ uint4 lds128(uint32_t a) { uint4 v; asm volatile("ld.shared.v4.b32 {%0, %1, %2, %3}, [%4];" : "=r"(v.x), "=r"(v.y), "=r"(v.z), "=r"(v.w) : "r"(a) : "memory"); return v; }
__device__ __forceinline__ void sts16(uint32_t a, uint32_t v) { asm volatile("st.shared.b16 [%0], %1;" :: "r"(a), "h"((uint16_t)v) : "memory"); }
__device__ __forceinline__ void sts32(uint32_t a, uint32_t v) { asm volatile("st.shared.b32 [%0], %1;" :: "r"(a), "r"(v) : "memory"); }
__device__ __forceinline__ void stsf(uint32_t a, float v) { sts32(a, __float_as_uint(v)); }
__device__ __forceinline__ void sts64(uint32_t a, uint32_t x, uint32_t y) { asm volatile("st.shared.v2.b32 [%0], {%1, %2};" :: "r"(a), "r"(x), "r"(y) : "memory"); }
__device__ __forceinline__ void sts128(uint32_t a, uint32_t x, uint32_t y, uint32_t z, uint32_t w) { asm volatile("st.shared.v4.b32 [%0], {%1, %2, %3, %4};" :: "r"(a), "r"(x), "r"(y), "r"(z), "r"(w) : "memory"); }
__device__ __forceinline__ void stsm4(uint32_t a, uint32_t x, uint32_t y, uint32_t z, uint32_t w) {
    asm volatile("stmatrix.sync.aligned.m8n8.x4.shared.b16 [%0], {%1, %2, %3, %4};" :: "r"(a), "r"(x), "r"(y), "r"(z), "r"(w) : "memory");
}
__device__ __forceinline__ void ldsm4(uint32_t& a0, uint32_t& a1, uint32_t& a2, uint32_t& a3, uint32_t addr) {
    asm volatile("ldmatrix.sync.aligned.m8n8.x4.shared.b16 {%0,%1,%2,%3}, [%4];" : "=r"(a0), "=r"(a1), "=r"(a2), "=r"(a3) : "r"(addr) : "memory");
}
__device__ __forceinline__ void ldsm4t(uint32_t& a0, uint32_t& a1, uint32_t& a2, uint32_t& a3, uint32_t addr) {
    asm volatile("ldmatrix.sync.aligned.m8n8.x4.trans.shared.b16 {%0,%1,%2,%3}, [%4];" : "=r"(a0), "=r"(a1), "=r"(a2), "=r"(a3) : "r"(addr) : "memory");
}
__device__ __forceinline__ void mma_bf16(float (&d)[4], uint32_t a0, uint32_t a1, uint32_t a2, uint32_t a3, uint32_t b0, uint32_t b1) {
    asm("mma.sync.aligned.m16n8k16.row.col.f32.bf16.bf16.f32 {%0,%1,%2,%3}, {%4,%5,%6,%7}, {%8,%9}, {%0,%1,%2,%3};"
        : "+f"(d[0]), "+f"(d[1]), "+f"(d[2]), "+f"(d[3]) : "r"(a0), "r"(a1), "r"(a2), "r"(a3), "r"(b0), "r"(b1));
}
__device__ __forceinline__ void mma_bf16_k8(float (&d)[4], uint32_t a0, uint32_t a1, uint32_t b0) {
    asm("mma.sync.aligned.m16n8k8.row.col.f32.bf16.bf16.f32 {%0,%1,%2,%3}, {%4,%5}, {%6}, {%0,%1,%2,%3};"
        : "+f"(d[0]), "+f"(d[1]), "+f"(d[2]), "+f"(d[3]) : "r"(a0), "r"(a1), "r"(b0));
}
__device__ __forceinline__ void mma_f16(float (&d)[4], uint32_t a0, uint32_t a1, uint32_t a2, uint32_t a3, uint32_t b0, uint32_t b1) {
    asm("mma.sync.aligned.m16n8k16.row.col.f32.f16.f16.f32 {%0,%1,%2,%3}, {%4,%5,%6,%7}, {%8,%9}, {%0,%1,%2,%3};"
        : "+f"(d[0]), "+f"(d[1]), "+f"(d[2]), "+f"(d[3]) : "r"(a0), "r"(a1), "r"(a2), "r"(a3), "r"(b0), "r"(b1));
}
__device__ __forceinline__ void stg128_pred(void* p, const uint4& v, bool on) {
    asm volatile("{\n.reg .pred q;\nsetp.ne.u32 q, %5, 0;\n@q st.global.v4.b32 [%0], {%1, %2, %3, %4};\n}"
                 :: "l"(p), "r"(v.x), "r"(v.y), "r"(v.z), "r"(v.w), "r"((uint32_t)on) : "memory");
}
__device__ __forceinline__ void st_x32(void* p, uint32_t v) { asm volatile("st.relaxed.gpu.global.u32 [%0], %1;" :: "l"(p), "r"(v) : "memory"); }
__device__ __forceinline__ void st_x64(void* p, uint32_t x, uint32_t y) {
    asm volatile("{\n.reg .b64 v;\nmov.b64 v, {%1, %2};\nst.relaxed.gpu.global.b64 [%0], v;\n}" :: "l"(p), "r"(x), "r"(y) : "memory");
}
__device__ __forceinline__ void st_x128(void* p, uint32_t x, uint32_t y, uint32_t z, uint32_t w) {
    asm volatile("{\n.reg .b64 a, b;\n.reg .b128 v;\nmov.b64 a, {%1, %2};\nmov.b64 b, {%3, %4};\nmov.b128 v, {a, b};\nst.relaxed.gpu.global.b128 [%0], v;\n}"
                 :: "l"(p), "r"(x), "r"(y), "r"(z), "r"(w) : "memory");
}
__device__ __forceinline__ uint32_t ld_x32(const void* p) { uint32_t v; asm volatile("ld.relaxed.gpu.global.u32 %0, [%1];" : "=r"(v) : "l"(p) : "memory"); return v; }
__device__ __forceinline__ uint2 ld_x64(const void* p) {
    uint2 v; asm volatile("{\n.reg .b64 a;\nld.relaxed.gpu.global.b64 a, [%2];\nmov.b64 {%0, %1}, a;\n}" : "=r"(v.x), "=r"(v.y) : "l"(p) : "memory"); return v;
}
__device__ __forceinline__ uint4 ld_x128(const void* p) {
    uint4 v;
    asm volatile("{\n.reg .b64 a, b;\n.reg .b128 v;\nld.relaxed.gpu.global.b128 v, [%4];\nmov.b128 {a, b}, v;\nmov.b64 {%0, %1}, a;\nmov.b64 {%2, %3}, b;\n}"
                 : "=r"(v.x), "=r"(v.y), "=r"(v.z), "=r"(v.w) : "l"(p) : "memory");
    return v;
}
__device__ __forceinline__ void poll_tick(uint32_t& n) { asm volatile("{\n.reg .pred p;\nadd.u32 %0, %0, 1;\nsetp.ge.u32 p, %0, 0x800000;\n@p st.global.u32 [%1], %0;\n}" : "+r"(n) : "l"(0ull)); }
__device__ __forceinline__ void ctr_arrive(int* c) { asm volatile("red.release.gpu.global.add.s32 [%0], 1;" :: "l"(c) : "memory"); }
__device__ __forceinline__ void ctr_wait(const int* c, int target) {
    int v;
    uint32_t n = 0;
    #pragma unroll 1
    do {
        asm volatile("ld.acquire.gpu.global.s32 %0, [%1];" : "=r"(v) : "l"(c) : "memory");
        poll_tick(n);
    } while (v < target);
}
__device__ __forceinline__ void flag_wait(const uint8_t* f) {
    uint32_t n = 0, v;
    #pragma unroll 1
    do { asm volatile("ld.acquire.gpu.global.u8 %0, [%1];" : "=r"(v) : "l"(f) : "memory"); poll_tick(n); } while (v);
}
__device__ __forceinline__ void flags16_wait(const uint8_t* f) {
    uint32_t n = 0;
    uint64_t v;
    #pragma unroll 1
    do {
        asm volatile("{\n.reg .b64 a, b;\n.reg .b128 v;\nld.acquire.gpu.global.b128 v, [%1];\nmov.b128 {a, b}, v;\nor.b64 %0, a, b;\n}" : "=l"(v) : "l"(f) : "memory");
        poll_tick(n);
    } while (v != 0);
}
__device__ __forceinline__ bool any_empty(const uint4& v) { return v.x == EMPTY || v.y == EMPTY || v.z == EMPTY || v.w == EMPTY; }
__device__ __forceinline__ bool warp_any(bool p) { return __any_sync(0xffffffffu, p); }

__device__ __forceinline__ float ex2(float x) { float y; asm("ex2.approx.ftz.f32 %0, %1;" : "=f"(y) : "f"(x)); return y; }
__device__ __forceinline__ float rsq(float x) { float y; asm("rsqrt.approx.ftz.f32 %0, %1;" : "=f"(y) : "f"(x)); return y; }
__device__ __forceinline__ float rcp(float x) { float y; asm("rcp.approx.ftz.f32 %0, %1;" : "=f"(y) : "f"(x)); return y; }
__device__ __forceinline__ uint32_t pack_bf16(float lo, float hi) { uint32_t r; asm("cvt.rn.bf16x2.f32 %0, %1, %2;" : "=r"(r) : "f"(hi), "f"(lo)); return r; }
__device__ __forceinline__ uint32_t pack_f16(float lo, float hi) { uint32_t r; asm("cvt.rn.f16x2.f32 %0, %1, %2;" : "=r"(r) : "f"(hi), "f"(lo)); return r; }
__device__ __forceinline__ float bf_lo(uint32_t v) { return __uint_as_float(v << 16); }
__device__ __forceinline__ float bf_hi(uint32_t v) { return __uint_as_float(v & 0xFFFF0000u); }
__device__ __forceinline__ float bf_round(float x) { return __uint_as_float(pack_bf16(0.f, x)); }
__device__ __forceinline__ void h2_unpack(uint32_t v, float& lo, float& hi) {
    asm("{.reg .f16 l, h; mov.b32 {l, h}, %2; cvt.f32.f16 %0, l; cvt.f32.f16 %1, h;}" : "=f"(lo), "=f"(hi) : "r"(v));
}
__device__ __forceinline__ uint32_t hadd2(uint32_t a, uint32_t b) { uint32_t r; asm("add.rn.f16x2 %0, %1, %2;" : "=r"(r) : "r"(a), "r"(b)); return r; }
__device__ __forceinline__ uint32_t hmax2(uint32_t a, uint32_t b) { uint32_t r; asm("max.f16x2 %0, %1, %2;" : "=r"(r) : "r"(a), "r"(b)); return r; }
__device__ __forceinline__ uint32_t badd2(uint32_t a, uint32_t b) { uint32_t r; asm("add.rn.bf16x2 %0, %1, %2;" : "=r"(r) : "r"(a), "r"(b)); return r; }
__device__ __forceinline__ uint32_t bmul2(uint32_t a, uint32_t b) { uint32_t r; asm("mul.rn.bf16x2 %0, %1, %2;" : "=r"(r) : "r"(a), "r"(b)); return r; }
__device__ __forceinline__ float warp_sum(float v) {
    #pragma unroll
    for (int o = 16; o > 0; o >>= 1) v += __shfl_xor_sync(0xffffffffu, v, o);
    return v;
}
__device__ __forceinline__ float quad_sum(float v) { v += __shfl_xor_sync(0xffffffffu, v, 1); return v + __shfl_xor_sync(0xffffffffu, v, 2); }
__device__ __forceinline__ float quad_max(float v) { v = fmaxf(v, __shfl_xor_sync(0xffffffffu, v, 1)); return fmaxf(v, __shfl_xor_sync(0xffffffffu, v, 2)); }
__device__ __forceinline__ uint32_t redux_max(uint32_t v) { uint32_t r; asm volatile("redux.sync.max.u32 %0, %1, 0xffffffff;" : "=r"(r) : "r"(v)); return r; }
__device__ __forceinline__ uint32_t redux_min(uint32_t v) { uint32_t r; asm volatile("redux.sync.min.u32 %0, %1, 0xffffffff;" : "=r"(r) : "r"(v)); return r; }
__device__ __forceinline__ uint32_t order_bits(float r) { const uint32_t u = __float_as_uint(r); return (u & 0x80000000u) ? ~u : (u | 0x80000000u); }
struct Ln2 { uint32_t nm, rh, rl, c; };
__device__ __forceinline__ Ln2 ln2_coef(float mean, float rstd) {
    const uint32_t a = pack_bf16(-mean, rstd), b = pack_bf16((-mean - bf_lo(a)) * rstd, rstd - bf_hi(a));
    return {__byte_perm(a, 0, 0x1010), __byte_perm(a, 0, 0x3232), __byte_perm(b, 0, 0x3232), __byte_perm(b, 0, 0x1010)};
}
__device__ __forceinline__ uint32_t bfma2(uint32_t a, uint32_t b, uint32_t c) { uint32_t r; asm("fma.rn.bf16x2 %0, %1, %2, %3;" : "=r"(r) : "r"(a), "r"(b), "r"(c)); return r; }
__device__ __forceinline__ uint32_t ln2(uint32_t v, const Ln2& k) { const uint32_t d = badd2(v, k.nm); return bfma2(d, k.rh, bfma2(d, k.rl, k.c)); }
__device__ __forceinline__ uint32_t add_ln2(uint32_t v, const Ln2& k) { return badd2(v, ln2(v, k)); }

#define TL(TID, i)
#define CK(TID, i)

__device__ __forceinline__ void wg_gemm_n128(float (&d)[64], uint64_t desca, uint64_t desc) {
    asm volatile("{\n.reg .pred p;\nsetp.ne.b32 p, 1, 0;\n"
        "wgmma.mma_async.sync.aligned.m64n128k16.f32.bf16.bf16 "
        "{%0,%1,%2,%3,%4,%5,%6,%7,%8,%9,%10,%11,%12,%13,%14,%15,%16,%17,%18,%19,%20,%21,%22,%23,%24,%25,%26,%27,%28,%29,%30,%31,%32,%33,%34,%35,%36,%37,%38,%39,%40,%41,%42,%43,%44,%45,%46,%47,%48,%49,%50,%51,%52,%53,%54,%55,%56,%57,%58,%59,%60,%61,%62,%63}, "
        "%64, %65, p, 1, 1, 0, 1;\n}\n"
        : "+f"(d[0]), "+f"(d[1]), "+f"(d[2]), "+f"(d[3]), "+f"(d[4]), "+f"(d[5]), "+f"(d[6]), "+f"(d[7]), "+f"(d[8]), "+f"(d[9]), "+f"(d[10]), "+f"(d[11]),
          "+f"(d[12]), "+f"(d[13]), "+f"(d[14]), "+f"(d[15]), "+f"(d[16]), "+f"(d[17]), "+f"(d[18]), "+f"(d[19]), "+f"(d[20]), "+f"(d[21]), "+f"(d[22]), "+f"(d[23]),
          "+f"(d[24]), "+f"(d[25]), "+f"(d[26]), "+f"(d[27]), "+f"(d[28]), "+f"(d[29]), "+f"(d[30]), "+f"(d[31]), "+f"(d[32]), "+f"(d[33]), "+f"(d[34]), "+f"(d[35]),
          "+f"(d[36]), "+f"(d[37]), "+f"(d[38]), "+f"(d[39]), "+f"(d[40]), "+f"(d[41]), "+f"(d[42]), "+f"(d[43]), "+f"(d[44]), "+f"(d[45]), "+f"(d[46]), "+f"(d[47]),
          "+f"(d[48]), "+f"(d[49]), "+f"(d[50]), "+f"(d[51]), "+f"(d[52]), "+f"(d[53]), "+f"(d[54]), "+f"(d[55]), "+f"(d[56]), "+f"(d[57]), "+f"(d[58]), "+f"(d[59]),
          "+f"(d[60]), "+f"(d[61]), "+f"(d[62]), "+f"(d[63])
        : "l"(desca), "l"(desc));
}
__device__ __forceinline__ void wg_gemm_n192(float (&d)[96], uint64_t desca, uint64_t desc) {
    asm volatile("{\n.reg .pred p;\nsetp.ne.b32 p, 1, 0;\n"
        "wgmma.mma_async.sync.aligned.m64n192k16.f32.bf16.bf16 "
        "{%0,%1,%2,%3,%4,%5,%6,%7,%8,%9,%10,%11,%12,%13,%14,%15,%16,%17,%18,%19,%20,%21,%22,%23,%24,%25,%26,%27,%28,%29,%30,%31,%32,%33,%34,%35,%36,%37,%38,%39,%40,%41,%42,%43,%44,%45,%46,%47,%48,%49,%50,%51,%52,%53,%54,%55,%56,%57,%58,%59,%60,%61,%62,%63,%64,%65,%66,%67,%68,%69,%70,%71,%72,%73,%74,%75,%76,%77,%78,%79,%80,%81,%82,%83,%84,%85,%86,%87,%88,%89,%90,%91,%92,%93,%94,%95}, "
        "%96, %97, p, 1, 1, 0, 1;\n}\n"
        : "+f"(d[0]), "+f"(d[1]), "+f"(d[2]), "+f"(d[3]), "+f"(d[4]), "+f"(d[5]), "+f"(d[6]), "+f"(d[7]), "+f"(d[8]), "+f"(d[9]), "+f"(d[10]), "+f"(d[11]),
          "+f"(d[12]), "+f"(d[13]), "+f"(d[14]), "+f"(d[15]), "+f"(d[16]), "+f"(d[17]), "+f"(d[18]), "+f"(d[19]), "+f"(d[20]), "+f"(d[21]), "+f"(d[22]), "+f"(d[23]),
          "+f"(d[24]), "+f"(d[25]), "+f"(d[26]), "+f"(d[27]), "+f"(d[28]), "+f"(d[29]), "+f"(d[30]), "+f"(d[31]), "+f"(d[32]), "+f"(d[33]), "+f"(d[34]), "+f"(d[35]),
          "+f"(d[36]), "+f"(d[37]), "+f"(d[38]), "+f"(d[39]), "+f"(d[40]), "+f"(d[41]), "+f"(d[42]), "+f"(d[43]), "+f"(d[44]), "+f"(d[45]), "+f"(d[46]), "+f"(d[47]),
          "+f"(d[48]), "+f"(d[49]), "+f"(d[50]), "+f"(d[51]), "+f"(d[52]), "+f"(d[53]), "+f"(d[54]), "+f"(d[55]), "+f"(d[56]), "+f"(d[57]), "+f"(d[58]), "+f"(d[59]),
          "+f"(d[60]), "+f"(d[61]), "+f"(d[62]), "+f"(d[63]), "+f"(d[64]), "+f"(d[65]), "+f"(d[66]), "+f"(d[67]), "+f"(d[68]), "+f"(d[69]), "+f"(d[70]), "+f"(d[71]),
          "+f"(d[72]), "+f"(d[73]), "+f"(d[74]), "+f"(d[75]), "+f"(d[76]), "+f"(d[77]), "+f"(d[78]), "+f"(d[79]), "+f"(d[80]), "+f"(d[81]), "+f"(d[82]), "+f"(d[83]),
          "+f"(d[84]), "+f"(d[85]), "+f"(d[86]), "+f"(d[87]), "+f"(d[88]), "+f"(d[89]), "+f"(d[90]), "+f"(d[91]), "+f"(d[92]), "+f"(d[93]), "+f"(d[94]), "+f"(d[95])
        : "l"(desca), "l"(desc));
}
__device__ __forceinline__ void wg_gemm_n192_init(float (&d)[96], uint64_t desca, uint64_t desc) {
    asm volatile("{\n.reg .pred p;\nsetp.ne.b32 p, 0, 0;\n"
        "wgmma.mma_async.sync.aligned.m64n192k16.f32.bf16.bf16 "
        "{%0,%1,%2,%3,%4,%5,%6,%7,%8,%9,%10,%11,%12,%13,%14,%15,%16,%17,%18,%19,%20,%21,%22,%23,%24,%25,%26,%27,%28,%29,%30,%31,%32,%33,%34,%35,%36,%37,%38,%39,%40,%41,%42,%43,%44,%45,%46,%47,%48,%49,%50,%51,%52,%53,%54,%55,%56,%57,%58,%59,%60,%61,%62,%63,%64,%65,%66,%67,%68,%69,%70,%71,%72,%73,%74,%75,%76,%77,%78,%79,%80,%81,%82,%83,%84,%85,%86,%87,%88,%89,%90,%91,%92,%93,%94,%95}, "
        "%96, %97, p, 1, 1, 0, 1;\n}\n"
        : "=f"(d[0]), "=f"(d[1]), "=f"(d[2]), "=f"(d[3]), "=f"(d[4]), "=f"(d[5]), "=f"(d[6]), "=f"(d[7]), "=f"(d[8]), "=f"(d[9]), "=f"(d[10]), "=f"(d[11]),
          "=f"(d[12]), "=f"(d[13]), "=f"(d[14]), "=f"(d[15]), "=f"(d[16]), "=f"(d[17]), "=f"(d[18]), "=f"(d[19]), "=f"(d[20]), "=f"(d[21]), "=f"(d[22]), "=f"(d[23]),
          "=f"(d[24]), "=f"(d[25]), "=f"(d[26]), "=f"(d[27]), "=f"(d[28]), "=f"(d[29]), "=f"(d[30]), "=f"(d[31]), "=f"(d[32]), "=f"(d[33]), "=f"(d[34]), "=f"(d[35]),
          "=f"(d[36]), "=f"(d[37]), "=f"(d[38]), "=f"(d[39]), "=f"(d[40]), "=f"(d[41]), "=f"(d[42]), "=f"(d[43]), "=f"(d[44]), "=f"(d[45]), "=f"(d[46]), "=f"(d[47]),
          "=f"(d[48]), "=f"(d[49]), "=f"(d[50]), "=f"(d[51]), "=f"(d[52]), "=f"(d[53]), "=f"(d[54]), "=f"(d[55]), "=f"(d[56]), "=f"(d[57]), "=f"(d[58]), "=f"(d[59]),
          "=f"(d[60]), "=f"(d[61]), "=f"(d[62]), "=f"(d[63]), "=f"(d[64]), "=f"(d[65]), "=f"(d[66]), "=f"(d[67]), "=f"(d[68]), "=f"(d[69]), "=f"(d[70]), "=f"(d[71]),
          "=f"(d[72]), "=f"(d[73]), "=f"(d[74]), "=f"(d[75]), "=f"(d[76]), "=f"(d[77]), "=f"(d[78]), "=f"(d[79]), "=f"(d[80]), "=f"(d[81]), "=f"(d[82]), "=f"(d[83]),
          "=f"(d[84]), "=f"(d[85]), "=f"(d[86]), "=f"(d[87]), "=f"(d[88]), "=f"(d[89]), "=f"(d[90]), "=f"(d[91]), "=f"(d[92]), "=f"(d[93]), "=f"(d[94]), "=f"(d[95])
        : "l"(desca), "l"(desc));
}
__device__ __forceinline__ void wg_qk_init(uint32_t (&d)[32], uint32_t a0, uint32_t a1, uint32_t a2, uint32_t a3, uint64_t desc) {
    asm volatile("{\n.reg .pred p;\nsetp.ne.b32 p, 0, 0;\n"
        "wgmma.mma_async.sync.aligned.m64n128k16.f16.f16.f16 "
        "{%0,%1,%2,%3,%4,%5,%6,%7,%8,%9,%10,%11,%12,%13,%14,%15,%16,%17,%18,%19,%20,%21,%22,%23,%24,%25,%26,%27,%28,%29,%30,%31}, "
        "{%32,%33,%34,%35}, %36, p, 1, 1, 0;\n}\n"
        : "=r"(d[0]), "=r"(d[1]), "=r"(d[2]), "=r"(d[3]), "=r"(d[4]), "=r"(d[5]), "=r"(d[6]), "=r"(d[7]), "=r"(d[8]), "=r"(d[9]), "=r"(d[10]), "=r"(d[11]),
          "=r"(d[12]), "=r"(d[13]), "=r"(d[14]), "=r"(d[15]), "=r"(d[16]), "=r"(d[17]), "=r"(d[18]), "=r"(d[19]), "=r"(d[20]), "=r"(d[21]), "=r"(d[22]), "=r"(d[23]),
          "=r"(d[24]), "=r"(d[25]), "=r"(d[26]), "=r"(d[27]), "=r"(d[28]), "=r"(d[29]), "=r"(d[30]), "=r"(d[31])
        : "r"(a0), "r"(a1), "r"(a2), "r"(a3), "l"(desc));
}
__device__ __forceinline__ void wg_qk_acc(uint32_t (&d)[32], uint32_t a0, uint32_t a1, uint32_t a2, uint32_t a3, uint64_t desc) {
    asm volatile("{\n.reg .pred p;\nsetp.ne.b32 p, 1, 0;\n"
        "wgmma.mma_async.sync.aligned.m64n128k16.f16.f16.f16 "
        "{%0,%1,%2,%3,%4,%5,%6,%7,%8,%9,%10,%11,%12,%13,%14,%15,%16,%17,%18,%19,%20,%21,%22,%23,%24,%25,%26,%27,%28,%29,%30,%31}, "
        "{%32,%33,%34,%35}, %36, p, 1, 1, 0;\n}\n"
        : "+r"(d[0]), "+r"(d[1]), "+r"(d[2]), "+r"(d[3]), "+r"(d[4]), "+r"(d[5]), "+r"(d[6]), "+r"(d[7]), "+r"(d[8]), "+r"(d[9]), "+r"(d[10]), "+r"(d[11]),
          "+r"(d[12]), "+r"(d[13]), "+r"(d[14]), "+r"(d[15]), "+r"(d[16]), "+r"(d[17]), "+r"(d[18]), "+r"(d[19]), "+r"(d[20]), "+r"(d[21]), "+r"(d[22]), "+r"(d[23]),
          "+r"(d[24]), "+r"(d[25]), "+r"(d[26]), "+r"(d[27]), "+r"(d[28]), "+r"(d[29]), "+r"(d[30]), "+r"(d[31])
        : "r"(a0), "r"(a1), "r"(a2), "r"(a3), "l"(desc));
}
__device__ __forceinline__ void wg_pv_init(uint32_t (&d)[10], uint32_t a0, uint32_t a1, uint32_t a2, uint32_t a3, uint64_t desc) {
    asm volatile("{\n.reg .pred p;\nsetp.ne.b32 p, 0, 0;\n"
        "wgmma.mma_async.sync.aligned.m64n40k16.f16.f16.f16 "
        "{%0,%1,%2,%3,%4,%5,%6,%7,%8,%9}, "
        "{%10,%11,%12,%13}, %14, p, 1, 1, 1;\n}\n"
        : "=r"(d[0]), "=r"(d[1]), "=r"(d[2]), "=r"(d[3]), "=r"(d[4]), "=r"(d[5]), "=r"(d[6]), "=r"(d[7]), "=r"(d[8]), "=r"(d[9])
        : "r"(a0), "r"(a1), "r"(a2), "r"(a3), "l"(desc));
}
__device__ __forceinline__ void wg_pv_acc(uint32_t (&d)[10], uint32_t a0, uint32_t a1, uint32_t a2, uint32_t a3, uint64_t desc) {
    asm volatile("{\n.reg .pred p;\nsetp.ne.b32 p, 1, 0;\n"
        "wgmma.mma_async.sync.aligned.m64n40k16.f16.f16.f16 "
        "{%0,%1,%2,%3,%4,%5,%6,%7,%8,%9}, "
        "{%10,%11,%12,%13}, %14, p, 1, 1, 1;\n}\n"
        : "+r"(d[0]), "+r"(d[1]), "+r"(d[2]), "+r"(d[3]), "+r"(d[4]), "+r"(d[5]), "+r"(d[6]), "+r"(d[7]), "+r"(d[8]), "+r"(d[9])
        : "r"(a0), "r"(a1), "r"(a2), "r"(a3), "l"(desc));
}

constexpr uint32_t SB = SMEM_BASE;
constexpr uint32_t R_SLOT = 18432, A_RING = SB, A_KP = SB + 73728, A_QX = SB + 81920, A_STB = SB + 98304;
constexpr uint32_t F_GU0 = SB + 98304, F_GU1 = SB + 163840, F_WD = F_GU0;
__host__ __device__ constexpr uint32_t o_a(uint32_t s) { return s == 0 ? SB : s == 1 ? A_QX : F_GU0 + (s - 2) * 32768; }
__host__ __device__ constexpr uint32_t o_b(uint32_t s) { return s < 2 ? SB + 16384 + s * 16384 : F_GU0 + 16384 + (s - 2) * 32768; }
constexpr uint32_t XT0 = SB + 49152, XT1 = XT0 + 16384, YT0 = o_a(0), YT1 = o_a(1);
constexpr uint32_t Q_ABYTES = 256 * 64 * 2, Q_STB = Q_ABYTES + 192 * 64 * 2;
constexpr uint32_t Q_CS = SB + 3 * Q_STB, Q_VS = Q_CS + 768, Q_RC = Q_VS + 256, Q_FIX = Q_RC + 2048;
constexpr uint32_t SD_VEC = SB + 176128, SD_W = SB + 180224;
static_assert(Q_FIX + 768 <= SD_VEC, "smem");
constexpr uint32_t M_RED = SB + 229376, M_BAR = M_RED + 2048, BAR_SET = 336, M_IVS = M_BAR + 2 * BAR_SET, M_SM = M_IVS + 128;
constexpr uint32_t M_F2 = M_SM;
constexpr uint32_t M_WS = M_SM + 16;
constexpr uint32_t M_CR = M_SM + 20;
constexpr uint32_t M_SS = M_SM + 24;
constexpr uint32_t M_RT = M_SM + 32;
constexpr uint32_t M_SR = M_SM + 96;
constexpr int K_SMEM = M_SR + 128 - SB;
static_assert(K_SMEM == 232448, "smem");
constexpr uint32_t B_QF = 0, B_AF = 24, B_OF = 56, B_RES = 88, B_GU = 96, B_WD = 104, B_RT = 112, B_SW = 120, B_ONE = 128, B_XD = 136, B_QE = 144, B_OE = 168,
                   B_PX = 200, B_AE = 224, B_OD = 256, B_FG = 288, B_FD = 296, B_XS = 304, B_KS = 312, B_END = 328;
constexpr int NB_ML = 1, NB_CONS = 2, NB_SIDE = 3, NB_EPI = 4;

__device__ __forceinline__ int mt_of(int c) { return (c >> 2) & 7; }
__device__ __forceinline__ int nt_of(int c) { return (c >> 5) * 4 + (c & 3); }
__device__ __forceinline__ int blk_of(int c) { return c >> 3; }
__device__ __forceinline__ int cb_of(int c) { return c & 7; }

struct Maps { CUtensorMap x[2], wqkv, o, wo[2], r, g, u, d; };

template <int N>
__device__ __forceinline__ void halve(float (&v)[8], int lane, int bit) {
    const bool up = lane & bit;
    #pragma unroll
    for (int i = 0; i < N; i++) v[i] = (up ? v[N + i] : v[i]) + __shfl_xor_sync(0xffffffffu, up ? v[i] : v[N + i], bit);
}

__device__ __forceinline__ void reset_exchange(int c, int t) {
    #pragma unroll 1
    for (int i = t; i < FILL; i += 96) g_u.fill[c][i] = make_uint4(EMPTY, EMPTY, EMPTY, EMPTY);
}
__device__ __forceinline__ void prep_work(const bf16* __restrict__ x0, const bf16* __restrict__ w_r, uint32_t lb) {
    const int t = tid_now() - 288, c = cta_now(), lane = t & 31, warp = warp_uniform(t >> 5);
    const uint32_t wb = SD_W + warp * 8192;
    mbar_nap(lb + B_SW, 0);
    {
        float cs[8], cq[8];
        #pragma unroll
        for (int i = 0; i < 8; i++) { cs[i] = 0.f; cq[i] = 0.f; }
        #pragma unroll 1
        for (int h = 0; h < 2; h++) {
            #pragma unroll 2
            for (int r = 0; r < 16; r++) {
                const uint4 u = lds128(wb + h * 24576 + (lane >> 3) * 128 + r * 512 + (((lane & 7) ^ ((r * 4 + (lane >> 3)) & 7)) << 4));
                const uint32_t w[4] = {u.x, u.y, u.z, u.w};
                #pragma unroll
                for (int e = 0; e < 4; e++) {
                    const float a = bf_lo(w[e]), b = bf_hi(w[e]);
                    cs[2*e] += a; cs[2*e+1] += b; cq[2*e] = fmaf(a, a, cq[2*e]); cq[2*e+1] = fmaf(b, b, cq[2*e+1]);
                }
            }
            fence_async_smem();
            __syncwarp();
            if (elect_one()) {
                const uint32_t bytes = h == 0 ? 8192 : warp < 2 ? 4096 : 2048;
                mbar_expect_tx(lb + B_PX + warp * 8, bytes);
                bulk_load(wb + h * 24576, h && warp == 2 ? w_r : x0 + (size_t)(c * 16 + (h ? 12 + warp * 2 : warp * 4)) * D_, bytes, lb + B_PX + warp * 8);
            }
            __syncwarp();
        }
        halve<4>(cs, lane, 16); halve<2>(cs, lane, 8);
        halve<4>(cq, lane, 16); halve<2>(cq, lane, 8);
        *reinterpret_cast<float4*>(&g_cs[mt_of(c)][warp * D_ + nt_of(c) * 64 + (lane & 7) * 8 + (lane >> 3) * 2]) = make_float4(cs[0], cq[0], cs[1], cq[1]);
    }
    TL(288, 22);
    reset_exchange(c, t);
    mbar_nap(lb + B_PX + warp * 8, 0);
    #pragma unroll 1
    for (int i = 0; i < (warp < 2 ? 6 : 5); i++) {
        const int r = i < 4 ? warp * 4 + i : 8 + warp * 2 + i;
        float s0 = 0.f, s1 = 0.f, q0 = 0.f, q1 = 0.f;
        #pragma unroll 2
        for (int j = 0; j < 4; j++) {
            const uint4 u = lds128(wb + (i >> 2) * 16384 + i * 2048 + j * 512 + lane * 16);
            const uint32_t w[4] = {u.x, u.y, u.z, u.w};
            #pragma unroll
            for (int e = 0; e < 4; e++) { const float a = bf_lo(w[e]), b = bf_hi(w[e]); s0 += a; s1 += b; q0 = fmaf(a, a, q0); q1 = fmaf(b, b, q1); }
        }
        s0 += s1; q0 += q1;
        float v = (lane & 16 ? q0 : s0) + __shfl_xor_sync(0xffffffffu, lane & 16 ? s0 : q0, 16);
        #pragma unroll
        for (int o = 8; o > 0; o >>= 1) v += __shfl_xor_sync(0xffffffffu, v, o);
        const float mean = v * (1.f / D_), sq = __shfl_xor_sync(0xffffffffu, mean, 16);
        if (lane == 0) {
            if (r < 16) g_rs0[c * 16 + r] = make_float2(fmaxf(sq - mean * mean, 0.f), mean);
            else stsf(M_WS, v);
        }
    }
    named_sync(NB_SIDE, 96);
    if (t == 0) { TL(288, 23); ctr_arrive(&g_pctr); ctr_wait(&g_pctr, 128); TL(288, 24); }
    named_sync(NB_SIDE, 96);
}

__device__ __forceinline__ void head_scales(float fq, float fk, float& sq, float& sk, float& ss) {
    const bool ok = fq <= 16384.f && fk <= 16384.f && fq * fk <= 50000.f;
    const int a = min(max((((int)(__float_as_uint(fq) >> 23) - 125) >> 1) - 8, -60), 60), b = min(max((((int)(__float_as_uint(fk) >> 23) - 125) >> 1) - 8, -60), 60);
    sq = QSCALE * __uint_as_float((uint32_t)(ok ? 127 : 127 - a) << 23);
    sk = __uint_as_float((uint32_t)(ok ? 127 : 127 - b) << 23);
    ss = ok ? 0.f : __uint_as_float((uint32_t)(127 + a + b) << 23);
}

__device__ __forceinline__ void epi_inputs(int L, const bf16* __restrict__ w_r) {
    const int t = tid_now() - 288, c = cta_now(), mt = mt_of(c), nt = nt_of(c), lane = t & 31;
    const uint32_t wr = t < 64 ? __ldg(reinterpret_cast<const uint32_t*>(w_r) + cb_of(c) * 64 + t) : 0x3F803F80u;
    #pragma unroll 1
    for (int k = 0; k < 3; k++) {
        const int i = t + 96 * k, col = (i >> 6) * D_ + nt * 64 + (i & 63);
        const float2* rsp = (L ? g_x.rs1 : g_rs0) + mt * 256 + (i & 255);
        uint2 sv = ld_x64(rsp);
        if (k < 2) {
            float2 p[8];
            #pragma unroll
            for (int j = 0; j < 8; j++) p[j] = __ldcg(&g_cs[j][col]);
            stsf(Q_CS + i * 4, ((p[0].x + p[1].x) + (p[2].x + p[3].x)) + ((p[4].x + p[5].x) + (p[6].x + p[7].x)));
            const float zz = ((p[0].y + p[1].y) + (p[2].y + p[3].y)) + ((p[4].y + p[5].y) + (p[6].y + p[7].y));
            const float zs = warp_sum(zz);
            if (i < 128) { if (lane == 0) stsf(M_SR + (i >> 5) * 4, zs); }
            else {
                const int e = (int)(__float_as_uint(zz) >> 23) - 127;
                const int sh = min(max(((e + 2) >> 1) + 3, -60), 60);
                sts32(Q_VS + (i - 128) * 4, (uint32_t)(127 - sh) << 23);
                sts16(M_IVS + ((i & 32) + (i & 6) * 4 + ((i >> 2) & 6) + (i & 1)) * 2, (uint32_t)(127 + sh - 4) << 7);
            }
        }
        else {
            named_sync(NB_SIDE, 96);
            if (t < 2) {
                float sq, sk, ss;
                head_scales(ldsf(M_SR + t * 4), ldsf(M_SR + 8 + t * 4), sq, sk, ss);
                stsf(M_F2 + t * 4, sq); stsf(M_F2 + 8 + t * 4, sk); stsf(M_SS + t * 4, ss);
            }
            __syncwarp();
        }
        uint32_t n = 0;
        #pragma unroll 1
        while (warp_any(sv.x == EMPTY)) { sv = ld_x64(rsp); poll_tick(n); }
        const float var = __uint_as_float(sv.x), a = L ? 1.f + rsq(var + LN_EPS) : 1.f;
        sts64(Q_RC + (i & 255) * 8, __float_as_uint(a * rsq(a * a * var + LN_EPS)), sv.y ^ 0x80000000u);
    }
    if (t < 68) sts32(M_RED + t * 4, wr);
}

__device__ __forceinline__ void ffn_finish(int L, bf16* __restrict__ out) {
    const int t = tid_now() - 288, c = cta_now(), lane = t & 31, warp = warp_uniform(t >> 5);
    TL(288, L * 32 + 29);
    const uint4 rv = lds128(M_RT + 16 * L);
    const int idx = (int)rv.w;
    const uint32_t* xsrc = &g_x.cand[L][idx >> 7][(c >> 2) * 16 + (t & 3) * 4 + (c & 3)];
    const uint8_t* fsrc = &g_x.x[idx >> 8][((idx >> 7) & 1) * 8 + (c >> 4)];
    uint32_t xw, busy;
    float a[4] = {0.f, 0.f, 0.f, 0.f};
    {
        const float* src = &g_x.ypart[L][c][0][t * 4];
        uint4 v[3];
        uint32_t n = 0;
        #pragma unroll 1
        do {
            v[0] = ld_x128(src); v[1] = ld_x128(src + 384);
            v[2] = make_uint4(0u, 0u, 0u, 0u);
            xw = 0u; busy = 0u;
            if (warp == 0) {
                v[2] = ld_x128(src + 768); xw = ld_x32(xsrc);
                asm volatile("ld.relaxed.gpu.global.u8 %0, [%1];" : "=r"(busy) : "l"(fsrc) : "memory");
            }
            poll_tick(n);
        } while (warp_any(any_empty(v[0]) || any_empty(v[1]) || any_empty(v[2]) || xw == EMPTY || busy != 0));
        TL(288, L * 32 + 30); TL(352, L * 32 + 31);
        #pragma unroll
        for (int i = 0; i < 3; i++) { a[0] += __uint_as_float(v[i].x); a[1] += __uint_as_float(v[i].y); a[2] += __uint_as_float(v[i].z); a[3] += __uint_as_float(v[i].w); }
    }
    #pragma unroll
    for (int o = 2; o < 32; o <<= 1) {
        #pragma unroll
        for (int i = 0; i < 4; i++) a[i] += __shfl_xor_sync(0xffffffffu, a[i], o);
    }
    if (lane < 2) sts128(M_SR + warp * 32 + lane * 16, __float_as_uint(a[0]), __float_as_uint(a[1]), __float_as_uint(a[2]), __float_as_uint(a[3]));
    named_sync(NB_SIDE, 96);
    if (t < 4) {
        const float2 y0 = lds64f(M_SR + t * 8), y1 = lds64f(M_SR + 32 + t * 8), y2 = lds64f(M_SR + 64 + t * 8);
        const uint32_t y = pack_bf16(y0.x + y1.x + y2.x, y0.y + y1.y + y2.y);
        const float rsel = bf_round(rcp(1.f + __expf(-bf_round(__uint_as_float(rv.x)))));
        const uint32_t xn = ln2(xw, ln2_coef(__uint_as_float(rv.y), __uint_as_float(rv.z)));
        const uint32_t res = badd2(xw, badd2(xn, pack_bf16(bf_lo(y) * rsel, bf_hi(y) * rsel)));
        if (L == 0) st_x32(&g_x.x2row[c * 4 + t], res);
        reinterpret_cast<uint32_t*>(L ? out : g_x1)[idx * (D_ / 2) + c * 4 + t] = res;
    }
}

__device__ __forceinline__ void fix_row(uint32_t lb) {
    const int t = tid_now() - 288, c = cta_now(), lane = t & 31, warp = warp_uniform(t >> 5);
    uint4 v[2];
    {
        uint32_t n = 0;
        #pragma unroll 1
        do {
            v[0] = ld_x128(g_x.x2row + t * 4);
            v[1] = make_uint4(0u, 0u, 0u, 0u);
            if (warp == 0) v[1] = ld_x128(g_x.x2row + (96 + t) * 4);
            poll_tick(n);
        } while (warp_any(any_empty(v[0]) || any_empty(v[1])));
    }
    const uint32_t w[8] = {v[0].x, v[0].y, v[0].z, v[0].w, v[1].x, v[1].y, v[1].z, v[1].w};
    float su = 0.f, sq = 0.f;
    #pragma unroll
    for (int i = 0; i < 8; i++) { const float a = bf_lo(w[i]), b = bf_hi(w[i]); su += a + b; sq = fmaf(a, a, fmaf(b, b, sq)); }
    su = warp_sum(su); sq = warp_sum(sq);
    if (lane == 0) sts64(M_SR + 96 + warp * 8, __float_as_uint(su), __float_as_uint(sq));
    named_sync(NB_SIDE, 96);
    const float2 s0 = lds64f(M_SR + 96), s1 = lds64f(M_SR + 104), s2 = lds64f(M_SR + 112);
    const float mean = (s0.x + s1.x + s2.x) * (1.f / D_);
    const float rstd = rsq(fmaxf((s0.y + s1.y + s2.y) * (1.f / D_) - mean * mean, 0.f) + LN_EPS);
    const Ln2 k = ln2_coef(mean, rstd);
    #pragma unroll
    for (int i = 0; i < 2; i++)
        if (i == 0 || warp == 0) sts128(SD_VEC + (t + 96 * i) * 16, ln2(w[4*i], k), ln2(w[4*i+1], k), ln2(w[4*i+2], k), ln2(w[4*i+3], k));
    named_sync(NB_SIDE, 96);
    TL(288, 32 + 22);
    mbar_nap(lb + B_SW, 0);
    float a[8];
    #pragma unroll
    for (int i = 0; i < 8; i++) a[i] = 0.f;
    const uint32_t xa = base32(SD_VEC + lane * 2), wa = base32(SD_W + lane * 48 + warp * 16);
    #pragma unroll 2
    for (int b = 0; b < 32; b++) {
        const float x = bf_lo(lds16(xa + b * 64));
        const uint4 u = lds128(wa + b * 1536);
        a[0] = fmaf(x, bf_lo(u.x), a[0]); a[1] = fmaf(x, bf_hi(u.x), a[1]); a[2] = fmaf(x, bf_lo(u.y), a[2]); a[3] = fmaf(x, bf_hi(u.y), a[3]);
        a[4] = fmaf(x, bf_lo(u.z), a[4]); a[5] = fmaf(x, bf_hi(u.z), a[5]); a[6] = fmaf(x, bf_lo(u.w), a[6]); a[7] = fmaf(x, bf_hi(u.w), a[7]);
    }
    halve<4>(a, lane, 16); halve<2>(a, lane, 8); halve<1>(a, lane, 4);
    a[0] = quad_sum(a[0]);
    if ((lane & 3) == 0) st_x32(&g_x.fix[c * 24 + warp * 8 + (lane >> 2)], __float_as_uint(a[0]));
    TL(288, 32 + 23);
    if (((int)lds32(M_RT + 12) >> 8) == mt_of(c)) {
        const float* src = &g_x.fix[(t >> 5) * D_ + nt_of(c) * 64 + (t & 31) * 2];
        uint2 f;
        uint32_t n = 0;
        #pragma unroll 1
        do { f = ld_x64(src); poll_tick(n); } while (warp_any(f.x == EMPTY || f.y == EMPTY));
        sts64(Q_FIX + t * 8, f.x, f.y);
    }
}

__device__ __forceinline__ void out_piece(bf16* __restrict__ out, int r, int ch, bool on) {
    const uint4 v = lds128(((ch & 8) ? YT1 : YT0) + r * 128 + (((ch ^ r) & 7) << 4)), kk = lds128(XT0 + r * 16);
    const Ln2 k = {kk.x, kk.y, kk.z, kk.w};
    const int c = blockIdx.x;
    stg128_pred(out + (blk_of(c) * 128 + r) * D_ + cb_of(c) * 128 + ch * 8, make_uint4(add_ln2(v.x, k), add_ln2(v.y, k), add_ln2(v.z, k), add_ln2(v.w, k)), on);
}
__device__ __forceinline__ void publish(uint8_t* f) {
    bulk_commit();
    bulk_wait();
    fence_async_global();
    asm volatile("st.release.gpu.global.u8 [%0], 0;" :: "l"(f) : "memory");
}
__device__ __forceinline__ void side_role(const Maps& mp, const bf16* __restrict__ x0, const bf16* __restrict__ wo, const bf16* __restrict__ w_down, const bf16* __restrict__ w_r, bf16* __restrict__ out) {
    #pragma unroll 1
    for (int L = 0; L < 2; L++) {
        const uint32_t lb = M_BAR + L * BAR_SET;
        if (L == 0) prep_work(x0, w_r, lb);
        else fix_row(lb);
        epi_inputs(L, w_r);
        const int t = tid_now() - 288, c = cta_now(), mt = mt_of(c), nt = nt_of(c), warp = warp_uniform(t >> 5);
        TL(288, L * 32 + 4);
        named_arrive(NB_EPI, 224);
        named_arrive(NB_EPI + 1, 224);
        if (warp == 0) {
            named_sync(NB_ML, 288);
            #pragma unroll
            for (int i = 0; i < 16; i++) sts128(base32(A_RING + 16384 + t * 16) + (i >> 2) * R_SLOT + (i & 3) * 512, 0x2C002C00u, 0x2C002C00u, 0x2C002C00u, 0x2C002C00u);
            fence_async_smem();
            __syncwarp();
            mbar_arrive_elect(lb + B_ONE);
        }
        if (elect_one()) {
            #pragma unroll 1
            for (int n = warp - 1; n >= 0 && n < 3 * warp - 2; n++) {
                char* dst = g_kv + (size_t)(nt * 2 + (n >> 1)) * 16 * KV_TILE;
                const int tile = 2 * mt + (n & 1);
                if (n < 3) mbar_nap(lb + (n == 2 ? B_AE + 16 : B_KS + 8 * n), 0);
                bulk_store(dst + ((tile - 1) & 15) * KV_TILE, n == 0 ? A_KP : n == 1 ? A_RING : A_STB + (n - 2) * 8192, 8192);
                bulk_store(dst + tile * KV_TILE + 8192, n < 2 ? A_RING + 8192 + n * R_SLOT : A_STB + n * 8192, 8192);
                publish(&g_x.kv[L][nt * 2 + (n >> 1)][tile]);
                if (n == 1) TL(352, L * 32 + 6);
                if (n == 0) TL(320, L * 32 + 27);
            }
            if (warp == 2) {
                const bool ffn = c < NFC;
                const uint64_t pol = policy_evict_first();
                mbar_expect_tx(lb + B_GU, ffn ? 131072 : 0);
                mbar_expect_tx(lb + B_WD, ffn ? 65536 : 0);
                l2_prefetch(reinterpret_cast<const char*>(wo) + (size_t)c * 16384, 16384);
                if (ffn) {
                    #pragma unroll 1
                    for (int i = 0; i < 12; i++) {
                        if (i < 8) tma_load_s(F_GU0 + i * 16384, (i & 1) ? &mp.u : &mp.g, c * 32, (i >> 1) * 256, lb + B_GU, pol);
                        else l2_prefetch(reinterpret_cast<const char*>(w_down) + (size_t)c * 65536 + (i - 8) * 16384, 16384);
                        __nanosleep(900);
                    }
                }
                mbar_nap(lb + B_OD, 0);
                __nanosleep(1000);
                l2_prefetch(g_u.fill[c], sizeof(g_u.fill[0]));
                if (L == 0) {
                    mbar_nap(lb + B_XS, 0);
                    tma_store(&mp.x[1], YT0, cb_of(c) * 128, blk_of(c) * 128);
                    tma_store(&mp.x[1], YT1, cb_of(c) * 128 + 64, blk_of(c) * 128);
                    publish(&g_x.x[blk_of(c) >> 1][(blk_of(c) & 1) * 8 + cb_of(c)]);
                    mbar_arrive(lb + B_XD);
                    TL(352, 18);
                }
            } else {
                #pragma unroll 1
                for (int p = 0; p < 2; p++) { mbar_sleep(lb + B_OD + (p * 2 + warp) * 8, 0); ctr_arrive(g_x.o[L][mt * 2 + warp][p]); TL(288, L * 32 + 19); }
            }
        }
        __syncwarp();
        if (L) {
            mbar_sleep(lb + B_XS, 0);
            const int cand = (int)lds32(M_CR) & 127;
            #pragma unroll 2
            for (int r = t >> 4; r < 132; r += 6) out_piece(out, r & 127, t & 15, r < 128 && r != cand);
            TL(288, 32 + 18);
            mbar_sleep(lb + B_RT, 0);
            out_piece(out, cand, t & 15, t < 16 && lds32(M_CR) != lds32(M_RT + 28));
        }
        const uint32_t late = mbar_test(lb + B_FD, 0);
        mbar_sleep(lb + B_FD, 0);
        __nanosleep(late ? 50 : 400);
        if (c == 0 && t == 0 && L == 0) g_pctr = 0;
        ffn_finish(L, out);
        TL(288, L * 32 + 20);
    }
}

struct Cols { float2 c[4], v[4]; };
template <int HH>
__device__ __forceinline__ void load_cols(Cols& k, uint32_t cs) {
    #pragma unroll
    for (int jj = 0; jj < 4; jj++) {
        k.c[jj] = lds64f(cs + (HH * 32 + jj * 8) * 4);
        if (HH >= 4) k.v[jj] = lds64f(cs + (Q_VS - Q_CS) + ((HH & 1) * 32 + jj * 8) * 4);
    }
}
template <int HH>
__device__ __forceinline__ void qkv_epi_head(const float (&acc0)[96], const float (&acc1)[96], const float (&cf)[4], const float (&nm)[4], const Cols& k, float hs, uint32_t (&pk)[4][4]) {
    #pragma unroll
    for (int jj = 0; jj < 4; jj++) {
        #pragma unroll
        for (int i = 0; i < 4; i++) {
            const float* a = (i >> 1) ? acc1 : acc0;
            const float sc = HH < 4 ? cf[i] * hs : cf[i];
            float x = fmaf(nm[i], k.c[jj].x, a[4 * (4 * HH + jj) + 2 * (i & 1)]) * sc;
            float y = fmaf(nm[i], k.c[jj].y, a[4 * (4 * HH + jj) + 2 * (i & 1) + 1]) * sc;
            if (HH >= 4) { x *= k.v[jj].x; y *= k.v[jj].y; }
            pk[i][jj] = pack_f16(x, y);
        }
    }
}
__device__ __forceinline__ void stage_kv(uint32_t dst, const uint32_t (&pk)[4][4]) {
    #pragma unroll
    for (int i = 0; i < 4; i++) stsm4(dst + (i >> 1) * 1024 + (i & 1) * 128, pk[i][0], pk[i][1], pk[i][2], pk[i][3]);
}
template <int OFF>
__device__ __forceinline__ void patch_row(float (&acc)[96], uint32_t fx) {
    #pragma unroll
    for (int j = 0; j < 24; j++) { const float2 f = lds64f(fx + j * 32); acc[4 * j + OFF] = f.x; acc[4 * j + OFF + 1] = f.y; }
}
template <bool INIT>
__device__ __forceinline__ void qkv_step(float (&acc0)[96], float (&acc1)[96], uint64_t da, uint64_t db) {
    wg_fence();
    #pragma unroll
    for (int kk = 0; kk < 4; kk++) {
        if (INIT && kk == 0) { wg_gemm_n192_init(acc0, da, db); wg_gemm_n192_init(acc1, da + (8192 >> 4), db); }
        else { wg_gemm_n192(acc0, da + kk * 2, db + kk * 128); wg_gemm_n192(acc1, da + (8192 >> 4) + kk * 2, db + kk * 128); }
    }
    wg_commit();
}
__device__ __forceinline__ void qkv_phase(int L, uint32_t lb, int wg, uint32_t (&qa)[8], uint32_t (&qb)[8], uint32_t (&SA)[32], uint32_t (&SB_)[32]) {
    float acc0[96], acc1[96];
    {
        const bool leader = (tid_now() & 127) == 0;
        const uint64_t da0 = opaque(desc_sw128(SB + wg * 16384, 16, 1024)), db0 = opaque(desc_sw128(SB + Q_ABYTES, 8192, 1024));
        mbar_spin(lb + B_QF, 0);
        TL(0, L * 32 + 1); CK(0, L * 32 + 10);
        qkv_step<true>(acc0, acc1, da0, db0);
        uint32_t st = 1, ph = 0;
        #pragma unroll 1
        for (int k = 1; k < 16; k++) {
            mbar_spin(lb + B_QF + 8 * st, ph);
            if (k == 14 && wg) named_sync(NB_CONS, 256);
            qkv_step<false>(acc0, acc1, da0 + st * (Q_STB >> 4), db0 + st * (Q_STB >> 4));
            if (k == 15 && !wg) named_arrive(NB_CONS, 256);
            wg_wait<1>();
            if (leader) mbar_arrive(lb + B_QE + 8 * (st == 0 ? 2 : st - 1));
            if (++st == 3) { st = 0; ph ^= 1; }
        }
    }
    named_sync(NB_EPI + wg, 224);
    const int tid = tid_now(), lane = tid & 31, w = (tid >> 5) & 3, g = lane >> 2, t = lane & 3;
    const int lr0 = wg * 128 + w * 16 + g;
    float cf[4], nm[4];
    #pragma unroll
    for (int i = 0; i < 4; i++) { const float2 r = lds64f(base32(Q_RC + lr0 * 8) + ((i >> 1) * 64 + (i & 1) * 8) * 8); cf[i] = r.x; nm[i] = r.y; }
    const uint32_t cs = base32(Q_CS + t * 8);
    const int d = L ? (int)lds32(M_RT + 12) - (mt_of(cta_now()) * 256 + lr0) : -1;
    const uint4 hs = lds128(M_F2);
    const uint32_t ko = base32((lane >> 3) * 2048 + (w * 16 + (lane & 7)) * 16);
    Cols k0, k1;
    load_cols<2>(k0, cs);
    wg_wait<0>();
    pin(acc0); pin(acc1);
    TL(128, L * 32 + 2); CK(128, L * 32 + 11);
    named_arrive(NB_ML, 288);
    if ((tid & 127) == 0) mbar_arrive(lb + B_QE);
    if (__builtin_expect((d & ~72) == 0, 0)) {
        if (d == 0) { patch_row<0>(acc0, cs + (Q_FIX - Q_CS)); cf[0] = 1.f; nm[0] = 0.f; }
        else if (d == 8) { patch_row<2>(acc0, cs + (Q_FIX - Q_CS)); cf[1] = 1.f; nm[1] = 0.f; }
        else if (d == 64) { patch_row<0>(acc1, cs + (Q_FIX - Q_CS)); cf[2] = 1.f; nm[2] = 0.f; }
        else { patch_row<2>(acc1, cs + (Q_FIX - Q_CS)); cf[3] = 1.f; nm[3] = 0.f; }
    }
    __syncwarp();
    uint32_t pk[4][4];
    qkv_epi_head<2>(acc0, acc1, cf, nm, k0, __uint_as_float(hs.z), pk);
    load_cols<4>(k1, cs);
    mbar_spin(lb + B_QE + 8 - 8 * wg, wg);
    stage_kv((wg ? A_RING : A_KP) + ko, pk);
    qkv_epi_head<4>(acc0, acc1, cf, nm, k1, 1.f, pk);
    load_cols<3>(k0, cs);
    stage_kv(A_RING + wg * R_SLOT + 8192 + ko, pk);
    fence_async_smem();
    __syncwarp();
    mbar_arrive_elect(lb + B_KS + 8 * wg);
    qkv_epi_head<3>(acc0, acc1, cf, nm, k0, __uint_as_float(hs.w), pk);
    load_cols<0>(k1, cs);
    load_cols<5>(k0, cs);
    stage_kv(A_STB + wg * 8192 + ko, pk);
    qkv_epi_head<0>(acc0, acc1, cf, nm, k1, __uint_as_float(hs.x), pk);
    #pragma unroll
    for (int s = 0; s < 2; s++) {
        qa[4*s] = pk[0][2*s]; qa[4*s+1] = pk[1][2*s]; qa[4*s+2] = pk[0][2*s+1]; qa[4*s+3] = pk[1][2*s+1];
        qb[4*s] = pk[2][2*s]; qb[4*s+1] = pk[3][2*s]; qb[4*s+2] = pk[2][2*s+1]; qb[4*s+3] = pk[3][2*s+1];
    }
    mbar_spin(lb + B_KS, 0);
    {
        constexpr uint64_t dk = desc_plain(A_KP, 2048, 128);
        wg_fence();
        wg_qk_init(SA, qa[0], qa[1], qa[2], qa[3], dk);
        wg_qk_acc(SA, qa[4], qa[5], qa[6], qa[7], dk + 256);
        wg_qk_init(SB_, qb[0], qb[1], qb[2], qb[3], dk);
        wg_commit();
    }
    qkv_epi_head<5>(acc0, acc1, cf, nm, k0, 1.f, pk);
    load_cols<1>(k1, cs);
    stage_kv(A_STB + 16384 + wg * 8192 + ko, pk);
    qkv_epi_head<1>(acc0, acc1, cf, nm, k1, __uint_as_float(hs.y), pk);
    #pragma unroll
    for (int u = 0; u < 2; u++)
        #pragma unroll
        for (int s = 0; s < 2; s++) sts128(A_QX + (u * 2 + s) * 4096 + tid * 16, pk[2*u][2*s], pk[2*u+1][2*s], pk[2*u][2*s+1], pk[2*u+1][2*s+1]);
    fence_async_smem();
    wg_wait<0>();
    pin(SA); pin(SB_);
    TL(128, L * 32 + 5); CK(128, L * 32 + 12);
}

#define PMASK 0x0000AAAAu
#define IMASK 0x10101010u
__host__ __device__ constexpr bool is_poly(int j) { return !((PMASK >> j) & 1); }
struct Shift { uint32_t f0, f1, n0, n1, bad; };

__device__ __forceinline__ uint32_t exp2_mufu(uint32_t s, uint32_t nm) {
    uint32_t r;
    asm("ex2.approx.f16x2 %0, %1;" : "=r"(r) : "r"(hadd2(s, nm)));
    return r;
}
__device__ __forceinline__ uint32_t exp2_fix(uint32_t s, uint32_t fm, uint32_t ca, uint32_t& U, bool mul, uint32_t sixteen) {
    uint32_t G, D;
    asm("fma.rn.relu.f16x2 %0, %1, %2, %3;" : "=r"(U) : "r"(s), "r"(0x00400040u), "r"(fm));
    asm("fma.rn.f16x2 %0, %1, %2, %3;" : "=r"(G) : "r"(U & 0x003F003Fu), "r"(ca), "r"(0x98B898B8u));
    asm("{.reg .b32 n; neg.f16x2 n, %1; fma.rn.relu.f16x2 %0, %1, n, %2;}" : "=r"(D) : "r"(G), "r"(0x00570057u));
    if (mul) return U * sixteen - D;
    return (U << 4) - D;
}
__device__ __forceinline__ uint32_t or3(uint32_t a, uint32_t b, uint32_t c) { uint32_t r; asm("lop3.b32 %0, %1, %2, %3, 0xFE;" : "=r"(r) : "r"(a), "r"(b), "r"(c)); return r; }
__device__ __forceinline__ void exp_tile(const uint32_t (&S)[32], uint32_t (&P)[32], Shift& h, uint32_t ca, uint32_t sixteen) {
    uint32_t U[33];
    int n = 0;
    #pragma unroll
    for (int i = 0; i < 32; i++) {
        if (is_poly(i)) P[i] = exp2_fix(S[i], (i & 1) ? h.f1 : h.f0, ca, U[n++], (IMASK >> i) & 1, sixteen);
        else P[i] = exp2_mufu(S[i], (i & 1) ? h.n1 : h.n0);
    }
    U[n] = 0u;
    #pragma unroll
    for (int i = 0; i < 32; i += 6) {
        if (i + 5 <= n) h.bad = or3(h.bad, or3(U[i], U[i + 1], U[i + 2]), or3(U[i + 3], U[i + 4], U[i + 5]));
        else {
            #pragma unroll
            for (int j = i; j < i + 6; j += 2) if (j < n) h.bad = or3(h.bad, U[j], U[j + 1]);
        }
    }
    pin(P);
}
__device__ __forceinline__ uint32_t hfma2(uint32_t a, uint32_t b, uint32_t c) { uint32_t r; asm("fma.rn.f16x2 %0, %1, %2, %3;" : "=r"(r) : "r"(a), "r"(b), "r"(c)); return r; }
__device__ __forceinline__ void unit_start(const uint32_t (&S)[32], Shift& h, uint32_t (&o2)[10]) {
    uint32_t m[4] = {S[0], S[1], S[2], S[3]};
    #pragma unroll
    for (int i = 1; i < 8; i++)
        #pragma unroll
        for (int e = 0; e < 4; e++) m[e] = hmax2(m[e], S[4 * i + e]);
    const uint32_t a = hadd2(m[0], m[2]), c = hadd2(m[1], m[3]);
    uint32_t x = hadd2(__byte_perm(a, c, 0x5410), __byte_perm(a, c, 0x7632));
    x = hadd2(x, __shfl_xor_sync(0xffffffffu, x, 1));
    x = hadd2(x, __shfl_xor_sync(0xffffffffu, x, 2));
    const uint32_t T = hfma2(x, 0xAC00AC00u, 0x5DEB5DEBu);
    const uint32_t n = hadd2(T, 0xDE00DE00u), f = hfma2(n, 0x00400040u, 0x03C003C0u);
    h.n0 = __byte_perm(n, 0, 0x1010); h.n1 = __byte_perm(n, 0, 0x3232);
    h.f0 = __byte_perm(f, 0, 0x1010); h.f1 = __byte_perm(f, 0, 0x3232);
    h.bad = T ^ 0x58005800u;
    #pragma unroll
    for (int i = 0; i < 10; i++) o2[i] = 0u;
}
__device__ __forceinline__ uint32_t o_offset() {
    const int c = cta_now(), tid = tid_now();
    return (mt_of(c) * 256 + (tid & 128) + ((tid >> 1) & 48) + ((tid >> 2) & 7)) * (D_ * 2) + nt_of(c) * 64 + (tid & 3) * 16;
}
template <int PASS, int UNIT>
__device__ __forceinline__ void unit_end(const uint32_t (&o)[10], uint32_t bad, uint32_t lb, uint32_t oo, uint32_t& fail, const uint4 iv) {
    float v[20];
    #pragma unroll
    for (int i = 0; i < 10; i++) h2_unpack(o[i], v[2 * i], v[2 * i + 1]);
    const float i0 = rcp(v[16]), i1 = rcp(v[18]);
    uint32_t r[8], z = 0;
    #pragma unroll
    for (int j = 0; j < 4; j++) {
        r[j] = pack_bf16(v[4*j] * i0, v[4*j+1] * i0); r[4 + j] = pack_bf16(v[4*j+2] * i1, v[4*j+3] * i1);
        z = bfma2(r[j], r[4 + j], z);
    }
    const bool good = o[8] - 0x34003400u < 0x48000000u && o[9] - 0x34003400u < 0x48000000u &&
                      ((bad & 0xF800F800u) | (bmul2(z, 0u) & 0x7FFF7FFFu) | (fail & (1u << (2 * PASS + UNIT)))) == 0;
    const bool all = __all_sync(0xffffffffu, good);
    char* dst = reinterpret_cast<char*>(g_o) + oo + (UNIT * 64 * D_ + PASS * 512) * 2;
    stg128_pred(dst, make_uint4(bmul2(r[0], iv.x), bmul2(r[1], iv.y), bmul2(r[2], iv.z), bmul2(r[3], iv.w)), all);
    stg128_pred(dst + 16 * D_, make_uint4(bmul2(r[4], iv.x), bmul2(r[5], iv.y), bmul2(r[6], iv.z), bmul2(r[7], iv.w)), all);
    if (__builtin_expect(!all, 0)) {
        fail |= 1u << (2 * PASS + UNIT);
        if (PASS == 0) {
            #pragma unroll
            for (int s = 0; s < 2; s++) g_qsave[cta_now()][UNIT * 2 + s][tid_now()] = lds128(A_KP + (UNIT * 2 + s) * 4096 + tid_now() * 16);
        }
    }
    __syncwarp();
    mbar_arrive_elect_p(lb + PASS * 16, all);
}
__device__ __forceinline__ void swap_q(uint32_t (&q)[8], uint32_t a) {
    asm volatile("{\n.reg .pred p;\nsetp.ne.u32 p, %8, 0;\n"
                 "@p st.shared.v4.b32 [%8 + -8192], {%0, %1, %2, %3};\n@p st.shared.v4.b32 [%8 + -4096], {%4, %5, %6, %7};\n"
                 "@p ld.shared.v4.b32 {%0, %1, %2, %3}, [%8];\n@p ld.shared.v4.b32 {%4, %5, %6, %7}, [%8 + 4096];\n}"
                 : "+r"(q[0]), "+r"(q[1]), "+r"(q[2]), "+r"(q[3]), "+r"(q[4]), "+r"(q[5]), "+r"(q[6]), "+r"(q[7]) : "r"(a) : "memory");
}
static_assert(A_QX == A_KP + 8192, "parking places");
template <bool INIT>
__device__ __forceinline__ void issue_pv(uint32_t (&o)[10], const uint32_t (&P)[32], uint64_t dv) {
    if (INIT) wg_pv_init(o, P[0], P[1], P[2], P[3], dv); else wg_pv_acc(o, P[0], P[1], P[2], P[3], dv);
    #pragma unroll
    for (int k = 1; k < 8; k++) wg_pv_acc(o, P[4*k], P[4*k+1], P[4*k+2], P[4*k+3], dv + k * 16);
}

__device__ __forceinline__ uint4 quad_transpose(uint32_t x0, uint32_t x1, uint32_t x2, uint32_t x3, int t) {
    const bool b0 = t & 1, b1 = t & 2;
    uint32_t s0 = b0 ? x0 : x1, s1 = b0 ? x2 : x3;
    s0 = __shfl_xor_sync(0xffffffffu, s0, 1); s1 = __shfl_xor_sync(0xffffffffu, s1, 1);
    const uint32_t y0 = b0 ? s0 : x0, y1 = b0 ? x1 : s0, y2 = b0 ? s1 : x2, y3 = b0 ? x3 : s1;
    uint32_t u0 = b1 ? y0 : y2, u1 = b1 ? y1 : y3;
    u0 = __shfl_xor_sync(0xffffffffu, u0, 2); u1 = __shfl_xor_sync(0xffffffffu, u1, 2);
    return b1 ? make_uint4(u0, u1, y2, y3) : make_uint4(y0, y1, u0, u1);
}
__device__ __forceinline__ uint32_t movm(uint32_t v) { uint32_t r; asm volatile("movmatrix.sync.aligned.m8n8.trans.b16 %0, %1;" : "=r"(r) : "r"(v)); return r; }
__device__ __forceinline__ void attn_repair(const uint4 qx, const uint4 qy, uint32_t lb, int pass, int unit) {
    const int tid = tid_now(), g = (tid & 31) >> 2, t = tid & 3;
    float ss = ldsf(M_SS + pass * 4);
    if (ss == 0.f) ss = 1.f;
    const uint4 q0 = quad_transpose(qx.x, qx.z, qy.x, qy.z, t), q1 = quad_transpose(qx.y, qx.w, qy.y, qy.w, t);
    const char* kv = g_kv + (size_t)(nt_of(cta_now()) * 2 + pass) * 16 * KV_TILE + t * 2048 + g * 16;
    float o[4][4], m0 = -INFINITY, m1 = -INFINITY, l0 = 0.f, l1 = 0.f;
    #pragma unroll
    for (int j = 0; j < 4; j++) { o[j][0] = 0.f; o[j][1] = 0.f; o[j][2] = 0.f; o[j][3] = 0.f; }
    uint4 kf[8];
    #pragma unroll
    for (int i = 0; i < 8; i++) kf[i] = __ldcg(reinterpret_cast<const uint4*>(kv + 15 * KV_TILE + i * 128));
    #pragma unroll 1
    for (int b = 0; b < 32; b++) {
        uint4 vf[8];
        #pragma unroll
        for (int i = 0; i < 8; i++) vf[i] = __ldcg(reinterpret_cast<const uint4*>(kv + (b >> 1) * KV_TILE + (b & 1) * 1024 + 8192 + i * 128));
        float s[8][4];
        #pragma unroll
        for (int i = 0; i < 8; i++) {
            s[i][0] = 0.f; s[i][1] = 0.f; s[i][2] = 0.f; s[i][3] = 0.f;
            mma_f16(s[i], q0.x, q1.x, q0.y, q1.y, kf[i].x, kf[i].y); mma_f16(s[i], q0.z, q1.z, q0.w, q1.w, kf[i].z, kf[i].w);
        }
        #pragma unroll
        for (int i = 0; i < 8; i++) kf[i] = __ldcg(reinterpret_cast<const uint4*>(kv + (((b - 1) >> 1) & 15) * KV_TILE + (~b & 1) * 1024 + i * 128));
        float t0 = m0, t1 = m1;
        #pragma unroll
        for (int i = 0; i < 8; i++) { t0 = fmaxf(t0, fmaxf(s[i][0], s[i][1])); t1 = fmaxf(t1, fmaxf(s[i][2], s[i][3])); }
        t0 = quad_max(t0); t1 = quad_max(t1);
        const float a0 = ex2((m0 - t0) * ss), a1 = ex2((m1 - t1) * ss);
        m0 = t0; m1 = t1;
        l0 *= a0; l1 *= a1;
        #pragma unroll
        for (int j = 0; j < 4; j++) { o[j][0] *= a0; o[j][1] *= a0; o[j][2] *= a1; o[j][3] *= a1; }
        #pragma unroll
        for (int k = 0; k < 4; k++) {
            uint32_t pf[4];
            #pragma unroll
            for (int e = 0; e < 2; e++) {
                const float p0 = ex2((s[2*k+e][0] - m0) * ss), p1 = ex2((s[2*k+e][1] - m0) * ss), p2 = ex2((s[2*k+e][2] - m1) * ss), p3 = ex2((s[2*k+e][3] - m1) * ss);
                l0 += p0 + p1; l1 += p2 + p3;
                pf[2*e] = pack_f16(p0, p1); pf[2*e+1] = pack_f16(p2, p3);
            }
            mma_f16(o[0], pf[0], pf[1], pf[2], pf[3], movm(vf[2*k].x), movm(vf[2*k+1].x));
            mma_f16(o[1], pf[0], pf[1], pf[2], pf[3], movm(vf[2*k].y), movm(vf[2*k+1].y));
            mma_f16(o[2], pf[0], pf[1], pf[2], pf[3], movm(vf[2*k].z), movm(vf[2*k+1].z));
            mma_f16(o[3], pf[0], pf[1], pf[2], pf[3], movm(vf[2*k].w), movm(vf[2*k+1].w));
        }
    }
    const float i0 = 16.f * rcp(quad_sum(l0)), i1 = 16.f * rcp(quad_sum(l1));
    uint32_t* dst = reinterpret_cast<uint32_t*>(reinterpret_cast<char*>(g_o) + (o_offset() & ~48u) + (unit * 64 * D_ + pass * 512) * 2) + t;
    #pragma unroll
    for (int j = 0; j < 4; j++) {
        const uint32_t iv = lds32(M_IVS + pass * 64 + j * 16 + t * 4);
        dst[j * 4] = pack_bf16(o[j][0] * i0 * bf_lo(iv), o[j][1] * i0 * bf_hi(iv));
        dst[j * 4 + 4 * D_] = pack_bf16(o[j][2] * i1 * bf_lo(iv), o[j][3] * i1 * bf_hi(iv));
    }
    __syncwarp();
    mbar_arrive_elect(lb + B_OD + (pass * 2 + (tid >> 7)) * 8);
}

__device__ __forceinline__ void load_gu(uint32_t (&f)[64], uint32_t src, int warp, int lane) {
    const uint32_t row = (warp & 3) * 64 + (lane >> 4) * 8 + (lane & 7), ch = (lane >> 3) & 1, sw = (lane >> 1) & 3;
    const uint32_t a0 = base32(src + (warp >> 2) * 32768 + row * 64 + ((ch ^ sw) << 4)), a1 = base32(a0 ^ 32);
    #pragma unroll
    for (int i = 0; i < 16; i++) ldsm4t(f[4*i], f[4*i+1], f[4*i+2], f[4*i+3], ((i & 1) ? a1 : a0) + ((i >> 1) & 1) * 16384 + (i >> 2) * 1024);
}

__device__ __forceinline__ void arrive_loaded(uint32_t bar, const uint32_t (&f)[64], uint32_t zero) {
    uint32_t x = 0;
    #pragma unroll
    for (int i = 0; i < 16; i++) x |= f[4 * i];
    mbar_arrive_elect(bar + (x & zero));
}
__device__ __forceinline__ void flush(uint32_t (&o2)[10], const uint32_t (&o)[10]) {
    #pragma unroll
    for (int i = 0; i < 10; i++) o2[i] = hadd2(o2[i], o[i]);
}
__device__ __forceinline__ void attention_phase(int L, uint32_t lb, int wg, uint32_t (&qa)[8], uint32_t (&qb)[8], uint32_t (&SA)[32], uint32_t (&SB_)[32], uint64_t dk0, uint64_t dv0, uint32_t ca, uint32_t (&wa)[64], uint32_t zero, uint32_t sixteen) {
    uint32_t PA[32], PB[32], oa[10], ob[10], oa2[10], ob2[10];
    Shift ha, hb;
    uint32_t fail = (lds32(M_SS) ? 3u : 0u) | (lds32(M_SS + 4) ? 12u : 0u);
    ca += base32(fail) >> 4;
    const uint32_t oo = o_offset(), odb = lb + B_OD + wg * 8;
    constexpr uint64_t SL = R_SLOT >> 4, KH = 4096 >> 4;
    uint64_t dkd = dk0 + ((A_KP - A_RING) >> 4);
    unit_start(SA, ha, oa2);
    exp_tile(SA, PA, ha, ca, sixteen);
    #pragma unroll
    for (int i = 0; i < 10; i++) { ob[i] = 0u; ob2[i] = 0u; }
    hb = ha;
    mbar_spin(lb + B_KS + 8, 0);
    mbar_spin(lb + B_ONE, 0);
    #pragma unroll 1
    for (int it = 0; ; it++) {
        const uint32_t ph = it & 1;
        uint32_t qsw = 0;
        #pragma unroll
        for (int u = 0; u < 4; u++) {
            const uint64_t dk = opaque(dk0) + u * SL, dv = opaque(dv0) + u * SL;
            wg_fence();
            if (u == 0) { wg_qk_acc(SB_, qb[4], qb[5], qb[6], qb[7], dkd + KH); wg_commit(); }
            if (u == 0) issue_pv<true>(oa, PA, dv); else issue_pv<false>(oa, PA, dv);
            wg_qk_init(SA, qa[0], qa[1], qa[2], qa[3], dk);
            wg_qk_acc(SA, qa[4], qa[5], qa[6], qa[7], dk + KH);
            wg_commit();
            wg_wait<1>();
            pin(SB_); pin(ob);
            if (u == 0) {
                mbar_arrive_elect_p(lb + B_AE + 24, it);
                flush(ob2, ob);
                if (__builtin_expect((it & 3) == 0, 0)) {
                    if (it) unit_end<0, 1>(ob2, hb.bad, odb, oo, fail, lds128(M_IVS + (oo & 48)));
                    unit_start(SB_, hb, ob2);
                }
            } else mbar_arrive_elect(lb + B_AE + 8 * (u - 1));
            if (u == 3) swap_q(qb, qsw ? qsw + 8192 : 0u);
            uint32_t ready = 0;
            if (u < 3) ready = mbar_test(lb + B_AF + 8 * (u + 1), ph);
            exp_tile(SB_, PB, hb, ca, sixteen);
            wg_fence();
            if (u == 0) issue_pv<true>(ob, PB, dv); else issue_pv<false>(ob, PB, dv);
            wg_qk_init(SB_, qb[0], qb[1], qb[2], qb[3], dk);
            if (u < 3) wg_qk_acc(SB_, qb[4], qb[5], qb[6], qb[7], dk + KH);
            wg_commit();
            if (u < 3) mbar_spin_unless(ready, lb + B_AF + 8 * (u + 1), ph);
            wg_wait<1>();
            pin(SA); pin(oa);
            if (u == 2) { qsw = it == 3 ? A_QX + tid_now() * 16 : 0u; swap_q(qa, qsw); }
            if (u == 3) {
                flush(oa2, oa);
                if (__builtin_expect((it & 3) == 3, 0)) {
                    TL(0, L * 32 + 7 + (it >> 2)); CK(0, L * 32 + 1 + (it >> 2));
                    if (it == 7) goto done;
                    unit_end<0, 0>(oa2, ha.bad, odb, oo, fail, lds128(M_IVS + (oo & 48)));
                    unit_start(SA, ha, oa2);
                }
            }
            exp_tile(SA, PA, ha, ca, sixteen);
        }
        mbar_spin(lb + B_AF, ph ^ 1);
        wg_wait<0>();
        dkd = dk0 + 3 * SL;
    }
done:
    const uint4 iv = lds128(M_IVS + 64 + (oo & 48));
    mbar_spin(lb + B_GU, 0);
    load_gu(wa, F_GU0, tid_now() >> 5, tid_now() & 31);
    unit_end<1, 0>(oa2, ha.bad, odb, oo, fail, iv);
    wg_wait<0>();
    pin(ob);
    mbar_arrive_elect(lb + B_AE + 24);
    flush(ob2, ob);
    unit_end<1, 1>(ob2, hb.bad, odb, oo, fail, iv);
    arrive_loaded(lb + B_FG, wa, zero);
    if (__builtin_expect(fail != 0, 0)) {
        uint4* const qs = &g_qsave[cta_now()][0][tid_now()];
        qs[4 * 256] = make_uint4(qa[0], qa[1], qa[2], qa[3]); qs[5 * 256] = make_uint4(qa[4], qa[5], qa[6], qa[7]);
        qs[6 * 256] = make_uint4(qb[0], qb[1], qb[2], qb[3]); qs[7 * 256] = make_uint4(qb[4], qb[5], qb[6], qb[7]);
        #pragma unroll
        for (int i = 0; i < 16; i++) qs[(8 + i) * 256] = make_uint4(wa[4*i], wa[4*i+1], wa[4*i+2], wa[4*i+3]);
        #pragma unroll 1
        for (int r = 0; r < 4; r++)
            if ((fail >> r) & 1) attn_repair(__ldcg(qs + r * 512), __ldcg(qs + r * 512 + 256), lb, r >> 1, r & 1);
        #pragma unroll
        for (int i = 0; i < 16; i++) { const uint4 v = __ldcg(qs + (8 + i) * 256); wa[4*i] = v.x; wa[4*i+1] = v.y; wa[4*i+2] = v.z; wa[4*i+3] = v.w; }
    }
    TL(0, L * 32 + 9); CK(0, L * 32 + 8);
}

__device__ __forceinline__ void oproj_steps(float (&acc)[64], uint32_t lb, int wg, int k0, int k1) {
    const bool leader = (tid_now() & 127) == 0;
    #pragma unroll 1
    for (int k = k0; k < k1; k++) {
        const uint32_t st = k & 3;
        mbar_spin(lb + B_OF + 8 * st, (k >> 2) & 1);
        const uint64_t da = desc_sw128(o_a(st) + wg * 8192, 16, 1024);
        const uint64_t db = desc_sw128(o_b(st), 8192, 1024);
        wg_fence();
        #pragma unroll
        for (int kk = 0; kk < 4; kk++) wg_gemm_n128(acc, da + kk * 2, db + kk * 128);
        wg_commit();
        wg_wait<1>();
        if (leader && k > 0) mbar_arrive(lb + B_OE + 8 * ((k - 1) & 3));
    }
}

__device__ __forceinline__ uint4 best_of(const uint4& e, int sh, int mask) {
    const uint32_t m = redux_max(e.x), row = redux_min(e.x == m ? e.w : 0x7FFFFFFFu), src = (row >> sh) & mask;
    return make_uint4(m, __shfl_sync(0xffffffffu, e.y, src), __shfl_sync(0xffffffffu, e.z, src), row);
}
__device__ __forceinline__ void load_wd(uint32_t (&wd)[64], uint32_t lb, int warp, int lane) {
    mbar_spin(lb + B_WD, 0);
    const uint32_t a0 = F_WD + warp * 8192 + ((lane >> 4) * 8 + (lane & 7)) * 128, ch = ((lane >> 3) & 1) ^ (lane & 7);
    #pragma unroll
    for (int i = 0; i < 16; i++) ldsm4t(wd[4*i], wd[4*i+1], wd[4*i+2], wd[4*i+3], base32(a0 + ((ch ^ (i & 6)) << 4)) + (i >> 3) * 4096 + (i & 1) * 2048);
}
__device__ __forceinline__ void stage_tile(const uint32_t (&xa)[4], const uint32_t (&xv)[32]) {
    #pragma unroll
    for (int m = 0; m < 8; m++) stsm4(xa[m & 3] + (m < 4 ? YT0 - XT0 : YT1 - XT0), xv[4*m], xv[4*m+1], xv[4*m+2], xv[4*m+3]);
    fence_async_smem();
    __syncwarp();
}

__device__ __forceinline__ void tail_phase(int L, uint32_t lb, int wg, const uint32_t (&wa)[64]) {
    const int c = cta_now(), blk = blk_of(c), cb = cb_of(c), tid = tid_now();
    const int lane = tid & 31, w = (tid >> 5) & 3, g = lane >> 2, t = lane & 3;
    const int lr0 = wg * 64 + w * 16 + g;
    uint32_t xa[4];
    #pragma unroll
    for (int m = 0; m < 4; m++) xa[m] = base32(XT0 + (wg * 64 + w * 16 + (lane & 15)) * 128 + (((lane >> 4) ^ (lane & 7) ^ (2 * m)) << 4));
    uint32_t xv[32];
    const bool ffn = c < NFC;
    uint32_t wb[64], wd[64];
    float own[6];
    {
        float acc[64];
        #pragma unroll
        for (int i = 0; i < 64; i++) acc[i] = 0.f;
        pin(acc);
        float2 rs0 = make_float2(0.f, 0.f), rs1 = rs0;
        if (L) { rs0 = __ldcg(&g_x.rs1[blk * 128 + lr0]); rs1 = __ldcg(&g_x.rs1[blk * 128 + lr0 + 8]); }
        oproj_steps(acc, lb, wg, 0, 8);
        mbar_spin(lb + B_RES, 0);
        #pragma unroll
        for (int m = 0; m < 8; m++) ldsm4(xv[4*m], xv[4*m+1], xv[4*m+2], xv[4*m+3], xa[m & 3] + (m < 4 ? 0 : XT1 - XT0));
        if (L) {
            const int d = (int)lds32(M_RT + 12) - (blk * 128 + lr0);
            const Ln2 k0 = ln2_coef(rs0.y, d == 0 ? 0.f : rsq(rs0.x + LN_EPS)), k1 = ln2_coef(rs1.y, d == 8 ? 0.f : rsq(rs1.x + LN_EPS));
            #pragma unroll
            for (int j = 0; j < 16; j++) { xv[2*j] = add_ln2(xv[2*j], k0); xv[2*j+1] = add_ln2(xv[2*j+1], k1); }
        }
        pin(xv);
        oproj_steps(acc, lb, wg, 8, 16);
        uint32_t wv[16];
        #pragma unroll
        for (int i = 0; i < 4; i++) ldsm4(wv[4*i], wv[4*i+1], wv[4*i+2], wv[4*i+3], (lane & 1) ? M_RED + (lane >> 3) * 16 + i * 64 : M_RED + 256);
        wg_wait<0>();
        pin(acc);
        if ((tid & 127) == 0) mbar_arrive(lb + B_OE + 24);
        TL(0, L * 32 + 11); CK(0, L * 32 + 13);
        float sa[4] = {0.f, 0.f, 0.f, 0.f}, sb[4] = {0.f, 0.f, 0.f, 0.f}, sc[4] = {0.f, 0.f, 0.f, 0.f};
        float sd[4] = {0.f, 0.f, 0.f, 0.f}, se[4] = {0.f, 0.f, 0.f, 0.f};
        #pragma unroll
        for (int m = 0; m < 8; m++) {
            #pragma unroll
            for (int i = 0; i < 4; i++) xv[4*m+i] = badd2(xv[4*m+i], pack_bf16(acc[8*m + 2*i], acc[8*m + 2*i + 1]));
            mma_bf16(sa, xv[4*m], xv[4*m+1], xv[4*m+2], xv[4*m+3], wv[2*m], wv[2*m+1]);
            mma_bf16_k8(sb, xv[4*m], xv[4*m+1], xv[4*m]); mma_bf16_k8(sc, xv[4*m], xv[4*m+1], xv[4*m+1]);
            mma_bf16_k8(sd, xv[4*m+2], xv[4*m+3], xv[4*m+2]); mma_bf16_k8(se, xv[4*m+2], xv[4*m+3], xv[4*m+3]);
        }
        const float q0 = (g & 1) ? sb[1] + sd[1] : sb[0] + sd[0], q1 = (g & 1) ? sc[3] + se[3] : sc[2] + se[2];
        if (t == (g >> 1)) {
            st_x128(&g_x.part[L][blk][cb][lr0], __float_as_uint(sa[0]), __float_as_uint(q0), __float_as_uint(sa[1]), 0u);
            st_x128(&g_x.part[L][blk][cb][lr0 + 8], __float_as_uint(sa[2]), __float_as_uint(q1), __float_as_uint(sa[3]), 0u);
        }
        __syncwarp();
        own[0] = sa[0]; own[1] = __shfl_sync(0xffffffffu, q0, (lane & 28) + (g >> 1)); own[2] = sa[1];
        own[3] = sa[2]; own[4] = __shfl_sync(0xffffffffu, q1, (lane & 28) + (g >> 1)); own[5] = sa[3];
    }
    TL(0, L * 32 + 12);
    load_gu(wb, F_GU1, tid >> 5, lane);
    stage_tile(xa, xv);
    float mean[2], rstd[2], score[2];
    {
        const bool o0 = cb == 2 * t, o1 = cb == 2 * t + 1;
        const uint4* const psrc = &g_x.part[L][blk][2 * t][lr0];
        uint4 p[4];
        uint32_t n = 0;
        #pragma unroll 1
        do {
            p[0] = ld_x128(psrc); p[1] = ld_x128(psrc + 128); p[2] = ld_x128(psrc + 8); p[3] = ld_x128(psrc + 136);
            poll_tick(n);
        } while (warp_any((!o0 && (p[0].w | p[2].w) != 0) || (!o1 && (p[1].w | p[3].w) != 0)));
        mbar_arrive_elect_p(lb + B_XS, L == 0);
        const float ws = ldsf(M_WS);
        #pragma unroll
        for (int h = 0; h < 2; h++) {
            const float su = quad_sum((o0 ? own[3*h] : __uint_as_float(p[2*h].x)) + (o1 ? own[3*h] : __uint_as_float(p[2*h+1].x)));
            const float sq = quad_sum((o0 ? own[3*h+1] : __uint_as_float(p[2*h].y)) + (o1 ? own[3*h+1] : __uint_as_float(p[2*h+1].y)));
            const float sd = quad_sum((o0 ? own[3*h+2] : __uint_as_float(p[2*h].z)) + (o1 ? own[3*h+2] : __uint_as_float(p[2*h+1].z)));
            mean[h] = su * (1.f / D_);
            const float var = fmaxf(sq * (1.f / D_) - mean[h] * mean[h], 0.f);
            rstd[h] = rsq(var + LN_EPS);
            score[h] = rstd[h] * (sd - mean[h] * ws);
            if (L && t == h) { const Ln2 k = ln2_coef(mean[h], rstd[h]); sts128(XT0 + (lr0 + 8 * h) * 16, k.nm, k.rh, k.rl, k.c); }
            if (L == 0 && cb == 0 && t == h) st_x64(&g_x.rs1[blk * 128 + lr0 + 8 * h], __float_as_uint(var), __float_as_uint(mean[h]));
        }
    }
    TL(0, L * 32 + 13);
    uint4 f;
    {
        const uint32_t k0 = order_bits(score[0]), k1 = order_bits(score[1]);
        const bool up = k1 > k0;
        const uint32_t kb = max(k0, k1), row = blk * 128 + lr0 + (up ? 8 : 0), m = redux_max(kb);
        if (redux_min(kb == m ? row : 0x7FFFFFFFu) == row && t == 0) sts128(M_SR + (tid >> 5) * 16, kb, __float_as_uint(up ? mean[1] : mean[0]), __float_as_uint(up ? rstd[1] : rstd[0]), row);
        named_sync(NB_CONS, 256);
        f = best_of(lds128(M_SR + (lane & 7) * 16), 4, 7);
        if (tid < 16) st_x128(&g_x.hdr[L][tid * 8 + cb][blk], f.x, f.y, f.z, f.w);
        const int d = (int)f.w - (blk * 128 + lr0);
        if ((d & ~8) == 0) {
            #pragma unroll
            for (int b = 0; b < 4; b++)
                st_x128(&g_x.cand[L][blk][cb * 64 + b * 16 + t * 4], d ? xv[8*b+1] : xv[8*b], d ? xv[8*b+3] : xv[8*b+2], d ? xv[8*b+5] : xv[8*b+4], d ? xv[8*b+7] : xv[8*b+6]);
        }
        __syncwarp();
    }
    TL(0, L * 32 + 28);
    if (tid == 0) sts32(M_CR, f.w);
    __syncwarp();
    mbar_arrive_elect_p(lb + B_XS, L);
    load_wd(wd, lb, tid >> 5, lane);
    TL(0, L * 32 + 25);
    uint4 e;
    {
        uint32_t n = 0;
        #pragma unroll 1
        do { e = ld_x128(&g_x.hdr[L][blk * 8 + cb][lane & 15]); poll_tick(n); } while (warp_any(e.w == EMPTY && (lane & 15) != blk));
        if ((lane & 15) == blk) e = f;
        e = best_of(e, 7, 15);
    }
    TL(0, L * 32 + 14);
    if (tid == 0) sts128(M_RT + 16 * L, (e.x & 0x80000000u) ? e.x ^ 0x80000000u : ~e.x, e.y, e.z, e.w);
    if (tid == 0) mbar_arrive(lb + B_RT);
    if (ffn) {
        const uint32_t* src = &g_x.cand[L][e.w >> 7][(tid >> 5) * 32 + t * 4];
        const Ln2 kx = ln2_coef(__uint_as_float(e.y), __uint_as_float(e.z));
        uint4 x[4];
        uint32_t n = 0;
        #pragma unroll 1
        do {
            x[0] = ld_x128(src); x[1] = ld_x128(src + 16); x[2] = ld_x128(src + 256); x[3] = ld_x128(src + 272);
            poll_tick(n);
        } while (warp_any(x[0].x == EMPTY || x[1].x == EMPTY || x[2].x == EMPTY || x[3].x == EMPTY));
        TL(0, L * 32 + 15);
        float d[4][4];
        #pragma unroll
        for (int i = 0; i < 4; i++) { d[i][0] = 0.f; d[i][1] = 0.f; d[i][2] = 0.f; d[i][3] = 0.f; }
        #pragma unroll
        for (int k = 0; k < 8; k++) {
            const uint32_t b0 = ln2((k & 1) ? x[k >> 1].z : x[k >> 1].x, kx), b1 = ln2((k & 1) ? x[k >> 1].w : x[k >> 1].y, kx);
            const uint32_t* f = (k < 4 ? wa : wb) + (k & 3) * 16;
            #pragma unroll
            for (int i = 0; i < 4; i++) mma_bf16(d[i], f[4*i], f[4*i+1], f[4*i+2], f[4*i+3], b0, b1);
        }
        #pragma unroll
        for (int h = 0; h < 2; h++) {
            const float a = (t & 1) ? d[1][2*h] : d[0][2*h], b = (t & 1) ? d[3][2*h] : d[2][2*h];
            stsf(M_RED + ((tid >> 5) * 64 + t * 16 + h * 8 + g) * 4, (t & 2) ? b : a);
        }
        named_sync(NB_CONS, 256);
        TL(0, L * 32 + 16);
        float s0 = 0.f, s1 = 0.f;
        #pragma unroll
        for (int i = 0; i < 8; i++) { const float2 v = lds64f(base32(M_RED + lane * 8) + i * 256); s0 += v.x; s1 += v.y; }
        const uint32_t mine = pack_bf16(s0, s1), other = __shfl_xor_sync(0xffffffffu, mine, 16);
        const uint32_t gv = lane < 16 ? mine : other, uv = lane < 16 ? other : mine;
        const float g0 = bf_lo(gv), g1 = bf_hi(gv);
        const uint32_t hv = bmul2(pack_bf16(g0 * rcp(1.f + __expf(-g0)), g1 * rcp(1.f + __expf(-g1))), uv);
        uint32_t hb[4];
        #pragma unroll
        for (int i = 0; i < 4; i++) hb[i] = __shfl_sync(0xffffffffu, hv, 4 * i + t);
        float y[8][4];
        #pragma unroll
        for (int i = 0; i < 8; i++) {
            y[i][0] = 0.f; y[i][1] = 0.f; y[i][2] = 0.f; y[i][3] = 0.f;
            mma_bf16(y[i], wd[8*i], wd[8*i+1], wd[8*i+2], wd[8*i+3], hb[0], hb[1]);
            mma_bf16(y[i], wd[8*i+4], wd[8*i+5], wd[8*i+6], wd[8*i+7], hb[2], hb[3]);
        }
        float* dst = &g_x.ypart[L][(tid >> 5) * 16 + t * 4][c][g];
        #pragma unroll
        for (int i = 0; i < 2; i++)
            #pragma unroll
            for (int h = 0; h < 2; h++) {
                const float a = (t & 1) ? y[2 + i][2*h] : y[i][2*h], b = (t & 1) ? y[6 + i][2*h] : y[4 + i][2*h];
                st_x32(dst + (i * 2 + h) * (NFC * 8), __float_as_uint((t & 2) ? b : a));
            }
    }
    __syncwarp();
    mbar_arrive_elect(lb + B_FD);
    TL(0, L * 32 + 17);
}

__device__ __forceinline__ void qkv_load_w(const Maps& mp, uint32_t dst, int k, uint32_t fb) { tma_load3(dst, &mp.wqkv, nt_of(blockIdx.x) * 64, k * 64, 0, fb); }
__device__ __forceinline__ void qkv_load_x(const CUtensorMap* tx, uint32_t sa, int k, uint32_t fb) {
    #pragma unroll
    for (int a = 0; a < 2; a++) tma_load(sa + a * 16384, tx, k * 64, mt_of(blockIdx.x) * 256 + a * 128, fb);
}
__device__ __forceinline__ void producer_role(const Maps& mp) {
    const int c = blockIdx.x, mt = mt_of(c), nt = nt_of(c), blk = blk_of(c), cb = cb_of(c);
    const uint64_t pol = policy_evict_first();
    #pragma unroll 1
    for (int L = 0; L < 2; L++) {
        const uint32_t lb = M_BAR + L * BAR_SET;
        const CUtensorMap* tx = &mp.x[L];
        mbar_expect_tx(lb + B_SW, 49152);
        if (L == 0) {
            mbar_nap(lb + B_QF, 0);
            qkv_load_w(mp, SD_W, mt * 2, lb + B_SW);
            qkv_load_w(mp, SD_W + 24576, mt * 2 + 1, lb + B_SW);
        }
        {
            uint32_t st = 0, ph = L;
            #pragma unroll 1
            for (int k = L ? 0 : 3; k < 16; k++) {
                mbar_sleep(k < 2 ? M_BAR + (k ? B_FD : B_XS) : lb + B_QE + 8 * st, k < 2 ? 0 : ph);
                const uint32_t fb = lb + B_QF + 8 * st, sa = SB + st * Q_STB;
                mbar_expect_tx(fb, Q_STB);
                qkv_load_w(mp, sa + Q_ABYTES, k, fb);
                if (k == 0) {
                    mbar_nap(M_BAR + B_XD, 0);
                    flags16_wait(g_x.x[mt]);
                    fence_async_global();
                    mbar_nap(M_BAR + B_RT, 0);
                    TL(256, 32);
                }
                qkv_load_x(tx, sa, k, fb);
                if (L && k >= 3 && k < 7) tma_load(SD_W + (k - 3) * 12288, &mp.r, c * 24, (k - 3) * 256, lb + B_SW);
                if (++st == 3) { st = 0; ph ^= 1; }
            }
        }
        mbar_sleep(lb + B_QE, 1);
        TL(256, L * 32 + 26);
        mbar_arrive(lb + B_AF);
        {
            const char* kv = g_kv + (size_t)nt * 32 * KV_TILE;
            const uint8_t* fl = g_x.kv[L][nt * 2];
            __nanosleep(800);
            #pragma unroll 1
            for (int j = 1; j < 4; j++) {
                flag_wait(fl + ((2 * mt + j + 1) & 15));
                fence_async_global();
                const uint32_t bytes = j == 1 ? 8192 : 16384;
                mbar_expect_tx(lb + B_AF + 8 * j, bytes);
                bulk_load(A_RING + j * R_SLOT, kv + ((2 * mt + j) & 15) * KV_TILE, bytes, lb + B_AF + 8 * j);
                if (j == 1) TL(256, L * 32 + 21);
            }
            flags16_wait(fl);
            fence_async_global();
            int t0 = 2 * mt;
            #pragma unroll 1
            for (int it = 1; it < 8; it++) {
                #pragma unroll
                for (int u = 0; u < 4; u++) {
                    const char* src = kv + ((t0 + 4 * it + u) & 15) * KV_TILE;
                    const uint32_t fb = lb + B_AF + 8 * u, dst = A_RING + u * R_SLOT;
                    mbar_nap(lb + B_AE + 8 * u, (it - 1) & 1);
                    mbar_expect_tx(fb, 16384);
                    if (u < 3) bulk_load(dst, src, 16384, fb);
                    else {
                        bulk_load(dst + 8192, src + 8192, 8192, fb);
                        if (it == 3) {
                            flags16_wait(fl + 128);
                            fence_async_global();
                            kv += 16 * KV_TILE; src = kv + 15 * KV_TILE; t0 = 0;
                        }
                        bulk_load(dst, src, 8192, fb);
                    }
                }
            }
        }
        #pragma unroll 1
        for (int it = 0; it < 4; it++) {
            #pragma unroll
            for (int s = 0; s < 4; s++) {
                mbar_spin(lb + (it ? B_OE + 8 * s : s < 2 ? B_AE + 8 + 8 * s : B_FG), it ? (it - 1) & 1 : s < 2);
                const uint32_t fb = lb + B_OF + 8 * s;
                mbar_expect_tx(fb, 32768);
                #pragma unroll
                for (int b = 0; b < 2; b++)
                    tma_load5(o_b(s) + b * 8192, &mp.wo[it >> 1], cb * 128 + b * 64, (it & 1) * 8 + s * 2, fb);
                if (s == 0 && !(it & 1)) {
                    ctr_wait(g_x.o[L][blk][it >> 1], 15);
                    fence_async_global();
                    TL(256, L * 32 + 10);
                }
                tma_load(o_a(s), &mp.o, it * 256 + s * 64, blk * 128, fb);
            }
            if (it == 0) {
                mbar_spin(lb + B_AE + 24, 1);
                mbar_expect_tx(lb + B_RES, 32768);
                tma_load_s(XT0, tx, cb * 128, blk * 128, lb + B_RES, pol);
                tma_load_s(XT1, tx, cb * 128 + 64, blk * 128, lb + B_RES, pol);
            }
        }
        if (c < NFC) {
            #pragma unroll 1
            for (int i = 0; i < 4; i++) {
                mbar_spin(lb + B_OE + 16 + 8 * (i >> 1), 1);
                tma_load3_s(F_WD + i * 16384, &mp.d, 0, c * 32, i * 4, lb + B_WD, pol);
            }
        }
    }
}

__global__ void __launch_bounds__(384, 1) k_all(const __grid_constant__ Maps mp, const bf16* __restrict__ x0, const bf16* __restrict__ wo, const bf16* __restrict__ w_down,
                                                const bf16* __restrict__ w_r, bf16* __restrict__ out, const uint64_t dk0, const uint64_t dv0, const uint32_t ca, const uint32_t zero, const uint32_t sixteen) {
    extern __shared__ __align__(1024) char smem[];
    if (smem_u32(smem) != SB) __trap();
    const int warp = warp_uniform(threadIdx.x >> 5), wg = warp >> 2;
    TL(0, 0);
    if (warp == 8) {
      if (elect_one()) {
        tm_prefetch(&mp.x[0]); tm_prefetch(&mp.wqkv);
        #pragma unroll
        for (int s = 0; s < 3; s++) { mbar_init(M_BAR + B_QF + 8 * s, 1); mbar_init(M_BAR + BAR_SET + B_QF + 8 * s, 1); }
        fence_mbar_init();
        #pragma unroll 1
        for (int s = 0; s < 3; s++) {
            const uint32_t sa = SB + s * Q_STB, fb = M_BAR + B_QF + 8 * s;
            mbar_expect_tx(fb, Q_STB);
            qkv_load_x(&mp.x[0], sa, s, fb);
            qkv_load_w(mp, sa + Q_ABYTES, s, fb);
        }
      }
      __syncwarp();
    } else if (warp > 8) {
        if (elect_one()) {
            const uint32_t o0 = warp == 9 ? B_AF : warp == 10 ? B_QE : B_AE, o1 = warp == 9 ? B_QE : warp == 10 ? B_AE : B_END, cnt = warp == 9 ? 1 : warp == 10 ? 2 : 8;
            #pragma unroll 1
            for (uint32_t o = o0; o < o1; o += 8) { const uint32_t n = o >= B_KS ? 4 : cnt; mbar_init(M_BAR + o, n); mbar_init(M_BAR + BAR_SET + o, n); }
            fence_mbar_init();
        }
        __syncwarp();
    }
    __syncthreads();
    if (wg == 2) {
        reg_dec<40>();
        if (warp > 8) side_role(mp, x0, wo, w_down, w_r, out);
        else if (elect_one()) producer_role(mp);
    } else {
        reg_inc<232>();
        #pragma unroll 1
        for (int L = 0; L < 2; L++) {
            const uint32_t lb = M_BAR + L * BAR_SET;
            uint32_t qa[8], qb[8], sa[32], sb[32], wa[64];
            qkv_phase(L, lb, wg, qa, qb, sa, sb);
            attention_phase(L, lb, wg, qa, qb, sa, sb, dk0, dv0, ca, wa, zero, sixteen);
            tail_phase(L, lb, wg, wa);
        }
    }
}

typedef CUresult (*EncodeFn)(CUtensorMap*, CUtensorMapDataType, cuuint32_t, void*, const cuuint64_t*, const cuuint64_t*, const cuuint32_t*,
                             const cuuint32_t*, CUtensorMapInterleave, CUtensorMapSwizzle, CUtensorMapL2promotion, CUtensorMapFloatOOBfill);

void make_map(EncodeFn enc, CUtensorMap* tm, const void* ptr, int rank, const cuuint64_t* dims, const cuuint64_t* strides, const cuuint32_t* box, CUtensorMapSwizzle sw) {
    const cuuint32_t es[5] = {1, 1, 1, 1, 1};
    enc(tm, CU_TENSOR_MAP_DATA_TYPE_BFLOAT16, rank, const_cast<void*>(ptr), dims, strides, box, es, CU_TENSOR_MAP_INTERLEAVE_NONE, sw,
        box[0] == 64 ? CU_TENSOR_MAP_L2_PROMOTION_L2_128B : CU_TENSOR_MAP_L2_PROMOTION_NONE, CU_TENSOR_MAP_FLOAT_OOB_FILL_NONE);
}
void make_map2(EncodeFn enc, CUtensorMap* tm, const void* ptr, uint64_t cols, uint64_t rows, uint32_t bc, uint32_t br, CUtensorMapSwizzle sw) {
    const cuuint64_t dims[2] = {cols, rows}, strides[1] = {cols * 2};
    const cuuint32_t box[2] = {bc, br};
    make_map(enc, tm, ptr, 2, dims, strides, box, sw);
}

}

extern "C" void kernel_launch(void* const* d_in, const int* in_sizes, int n_in, void* d_out, int out_size) {
    const bf16* x0 = (const bf16*)d_in[0];
    const bf16* wqkv = (const bf16*)d_in[1];
    const bf16* wo = (const bf16*)d_in[2];
    const bf16* w_r = (const bf16*)d_in[4];
    const bf16* w_gate = (const bf16*)d_in[5];
    const bf16* w_up = (const bf16*)d_in[6];
    const bf16* w_down = (const bf16*)d_in[7];

    EncodeFn enc = nullptr;
    cudaDriverEntryPointQueryResult qr;
    cudaGetDriverEntryPoint("cuTensorMapEncodeTiled", (void**)&enc, cudaEnableDefault, &qr);
    void *p_o, *p_x1;
    cudaGetSymbolAddress(&p_o, g_o); cudaGetSymbolAddress(&p_x1, g_x1);
    const CUtensorMapSwizzle S128 = CU_TENSOR_MAP_SWIZZLE_128B, S64 = CU_TENSOR_MAP_SWIZZLE_64B, S0 = CU_TENSOR_MAP_SWIZZLE_NONE;
    Maps mp;
    make_map2(enc, &mp.x[0], x0, D_, S_, 64, 128, S128); make_map2(enc, &mp.x[1], p_x1, D_, S_, 64, 128, S128);
    make_map2(enc, &mp.o, p_o, D_, S_, 64, 128, S128);
    {
        const cuuint64_t dims[3] = {D_, D_, 3}, strides[2] = {3 * D_ * 2, D_ * 2};
        const cuuint32_t box[3] = {64, 64, 3};
        make_map(enc, &mp.wqkv, wqkv, 3, dims, strides, box, S128);
    }
    make_map2(enc, &mp.r, wqkv, 3 * D_, D_, 24, 256, S0);
    make_map2(enc, &mp.g, w_gate, FF, D_, 32, 256, S64); make_map2(enc, &mp.u, w_up, FF, D_, 32, 256, S64);
    for (int p = 0; p < 2; p++) {
        const cuuint64_t dims[5] = {D_, 2, 4, 4, 16}, strides[4] = {D_ * 2, 8 * D_ * 2, 2 * D_ * 2, 64 * D_ * 2};
        const cuuint32_t box[5] = {64, 2, 4, 4, 2};
        make_map(enc, &mp.wo[p], wo + (size_t)p * 32 * D_, 5, dims, strides, box, S128);
    }
    {
        const cuuint64_t dims[3] = {64, FF, 16}, strides[2] = {D_ * 2, 128};
        const cuuint32_t box[3] = {64, 32, 4};
        make_map(enc, &mp.d, w_down, 3, dims, strides, box, S128);
    }
    cudaFuncSetAttribute(k_all, cudaFuncAttributeMaxDynamicSharedMemorySize, K_SMEM);
    k_all<<<128, 384, K_SMEM, cudaStreamPerThread>>>(mp, x0, wo, w_down, w_r, (bf16*)d_out, desc_plain(A_RING, 2048, 128), desc_plain(A_RING + 8192, 128, 2048), 0x64A264A2u, 0u, 16u);
}
```

```cpp
#include <cuda_runtime.h>
#include <cuda_bf16.h>
#include <cuda_fp16.h>
#include <cuda.h>
#include <cudaTypedefs.h>
#include <stdint.h>

namespace {

typedef __nv_bfloat16 bf16;

constexpr int S_ = 2048, D_ = 1024, NH = 32, FF = 3584, NFC = FF / 32;
constexpr float LN_EPS = 1e-5f;
constexpr float QSCALE = 0.17677669529663687f * 1.4426950408889634f;
constexpr uint32_t EMPTY = 0xFFFFFFFFu;

constexpr int KV_TILE = 16384;
__device__ __align__(1024) char g_kv[NH * 16 * KV_TILE];
__device__ __align__(1024) bf16 g_o[S_ * D_];
__device__ __align__(1024) bf16 g_x1[S_ * D_];
__device__ __align__(16) float2 g_cs[8][3 * D_];
__device__ __align__(16) float2 g_rs0[S_];
__device__ uint4 g_qsave[128][24][256];
struct Xchg {
    uint4 part[2][16][8][128];
    float ypart[2][128][NFC][8];
    uint32_t cand[2][16][D_ / 2];
    uint4 hdr[2][128][16];
    float2 rs1[S_];
    float fix[3 * D_];
    uint32_t x2row[D_ / 2];
    uint8_t kv[2][NH][128];
    int o[2][16][2][32];
    uint8_t x[8][128];
};
constexpr int FILL = (sizeof(Xchg) / 128 + 127) / 128 * 8;
union XchgFill { Xchg x; uint4 fill[128][FILL]; };
static_assert(FILL > 768 && FILL <= 1024, "exchange area");
__device__ __align__(128) XchgFill g_u;
#define g_x g_u.x
__device__ int g_pctr;

constexpr uint32_t SMEM_BASE = 1024;

__device__ __forceinline__ int tid_now() { int v; asm volatile("mov.u32 %0, %%tid.x;" : "=r"(v)); return v; }
__device__ __forceinline__ int cta_now() { int v; asm volatile("mov.u32 %0, %%ctaid.x;" : "=r"(v)); return v; }
__device__ __forceinline__ uint64_t opaque(uint64_t v) { uint64_t r; asm volatile("mov.b64 %0, %1;" : "=l"(r) : "l"(v)); return r; }
__device__ __forceinline__ uint32_t base32(uint32_t v) { uint32_t r; asm("mov.b32 %0, %1;" : "=r"(r) : "r"(v)); return r; }
__device__ __forceinline__ uint32_t smem_u32(const void* p) { return (uint32_t)__cvta_generic_to_shared(p); }
__device__ __forceinline__ void mbar_init(uint32_t bar, int cnt) { asm volatile("mbarrier.init.shared::cta.b64 [%0], %1;" :: "r"(bar), "r"(cnt) : "memory"); }
__device__ __forceinline__ void mbar_expect_tx(uint32_t bar, uint32_t bytes) { asm volatile("mbarrier.arrive.expect_tx.shared::cta.b64 _, [%0], %1;" :: "r"(bar), "r"(bytes) : "memory"); }
__device__ __forceinline__ void mbar_arrive(uint32_t bar) { asm volatile("mbarrier.arrive.shared::cta.b64 _, [%0];" :: "r"(bar) : "memory"); }
__device__ __forceinline__ void mbar_sleep(uint32_t bar, uint32_t parity) {
    asm volatile("{\n.reg .pred p;\n.reg .u32 n;\nmov.u32 n, 0;\n"
                 "LAB_WAIT:\nmbarrier.try_wait.parity.shared::cta.b64 p, [%0], %1, 0x10000;\n@p bra LAB_DONE;\n"
                 "add.u32 n, n, 1;\nsetp.lt.u32 p, n, 0x10000;\n@p bra LAB_WAIT;\ntrap;\nLAB_DONE:\n}" :: "r"(bar), "r"(parity) : "memory");
}
__device__ __forceinline__ void mbar_nap(uint32_t bar, uint32_t parity) {
    asm volatile("{\n.reg .pred p;\nLAB_WAIT:\nmbarrier.try_wait.parity.shared::cta.b64 p, [%0], %1, 0x10000;\n@!p bra LAB_WAIT;\n}" :: "r"(bar), "r"(parity) : "memory");
}
__device__ __forceinline__ void mbar_spin(uint32_t bar, uint32_t parity) {
    asm volatile("{\n.reg .pred p;\nLAB_WAIT:\nmbarrier.try_wait.parity.shared::cta.b64 p, [%0], %1;\n@!p bra LAB_WAIT;\n}" :: "r"(bar), "r"(parity) : "memory");
}
__device__ __forceinline__ uint32_t mbar_test(uint32_t bar, uint32_t parity) {
    uint32_t ok;
    asm volatile("{\n.reg .pred p;\nmbarrier.test_wait.parity.shared::cta.b64 p, [%1], %2;\nselp.u32 %0, 1, 0, p;\n}" : "=r"(ok) : "r"(bar), "r"(parity) : "memory");
    return ok;
}
__device__ __forceinline__ bool elect_one() {
    uint32_t r;
    asm volatile("{\n.reg .pred p;\nelect.sync _|p, 0xffffffff;\nselp.u32 %0, 1, 0, p;\n}" : "=r"(r));
    return r != 0;
}
__device__ __forceinline__ void mbar_arrive_elect(uint32_t bar) {
    asm volatile("{\n.reg .pred p;\nelect.sync _|p, 0xffffffff;\n@p mbarrier.arrive.shared::cta.b64 _, [%0];\n}" :: "r"(bar) : "memory");
}
__device__ __forceinline__ void mbar_arrive_elect_p(uint32_t bar, uint32_t on) {
    asm volatile("{\n.reg .pred p, q;\nelect.sync _|p, 0xffffffff;\nsetp.ne.and.u32 q, %1, 0, p;\n@q mbarrier.arrive.shared::cta.b64 _, [%0];\n}" :: "r"(bar), "r"(on) : "memory");
}
__device__ __forceinline__ int warp_uniform(int v) { return __shfl_sync(0xffffffffu, v, 0); }
__device__ __forceinline__ void fence_mbar_init() { asm volatile("fence.mbarrier_init.release.cluster;" ::: "memory"); }
__device__ __forceinline__ void fence_async_smem() { asm volatile("fence.proxy.async.shared::cta;" ::: "memory"); }
__device__ __forceinline__ void fence_async_global() { asm volatile("fence.proxy.async.global;" ::: "memory"); }
__device__ __forceinline__ void named_sync(int id, int n) { asm volatile("bar.sync %0, %1;" :: "r"(id), "r"(n) : "memory"); }
__device__ __forceinline__ void named_arrive(int id, int n) { asm volatile("bar.arrive %0, %1;" :: "r"(id), "r"(n) : "memory"); }
__device__ __forceinline__ void bulk_load(uint32_t dst, const void* src, uint32_t bytes, uint32_t bar) {
    asm volatile("cp.async.bulk.shared::cluster.global.mbarrier::complete_tx::bytes [%0], [%1], %2, [%3];" :: "r"(dst), "l"(src), "r"(bytes), "r"(bar) : "memory");
}
__device__ __forceinline__ void bulk_store(void* dst, uint32_t src, uint32_t bytes) {
    asm volatile("cp.async.bulk.global.shared::cta.bulk_group [%0], [%1], %2;" :: "l"(dst), "r"(src), "r"(bytes) : "memory");
}
__device__ __forceinline__ void bulk_commit() { asm volatile("cp.async.bulk.commit_group;" ::: "memory"); }
__device__ __forceinline__ void bulk_wait() { asm volatile("cp.async.bulk.wait_group 0;" ::: "memory"); }
__device__ __forceinline__ void l2_prefetch(const void* src, uint32_t bytes) {
    asm volatile("cp.async.bulk.prefetch.L2.global [%0], %1;" :: "l"(src), "r"(bytes) : "memory");
}
__device__ __forceinline__ void tma_load(uint32_t dst, const CUtensorMap* tm, int c0, int c1, uint32_t bar) {
    asm volatile("cp.async.bulk.tensor.2d.shared::cluster.global.mbarrier::complete_tx::bytes [%0], [%1, {%3, %4}], [%2];"
                 :: "r"(dst), "l"(tm), "r"(bar), "r"(c0), "r"(c1) : "memory");
}
__device__ __forceinline__ void tma_load3(uint32_t dst, const CUtensorMap* tm, int c0, int c1, int c2, uint32_t bar) {
    asm volatile("cp.async.bulk.tensor.3d.shared::cluster.global.mbarrier::complete_tx::bytes [%0], [%1, {%3, %4, %5}], [%2];"
                 :: "r"(dst), "l"(tm), "r"(bar), "r"(c0), "r"(c1), "r"(c2) : "memory");
}
__device__ __forceinline__ void tma_load5(uint32_t dst, const CUtensorMap* tm, int c0, int c4, uint32_t bar) {
    asm volatile("cp.async.bulk.tensor.5d.shared::cluster.global.mbarrier::complete_tx::bytes [%0], [%1, {%3, %5, %5, %5, %4}], [%2];"
                 :: "r"(dst), "l"(tm), "r"(bar), "r"(c0), "r"(c4), "r"(0) : "memory");
}
__device__ __forceinline__ uint64_t policy_evict_first() { uint64_t p; asm volatile("createpolicy.fractional.L2::evict_first.b64 %0, 1.0;" : "=l"(p)); return p; }
__device__ __forceinline__ void tma_load_s(uint32_t dst, const CUtensorMap* tm, int c0, int c1, uint32_t bar, uint64_t pol) {
    asm volatile("cp.async.bulk.tensor.2d.shared::cluster.global.mbarrier::complete_tx::bytes.L2::cache_hint [%0], [%1, {%3, %4}], [%2], %5;"
                 :: "r"(dst), "l"(tm), "r"(bar), "r"(c0), "r"(c1), "l"(pol) : "memory");
}
__device__ __forceinline__ void tma_load3_s(uint32_t dst, const CUtensorMap* tm, int c0, int c1, int c2, uint32_t bar, uint64_t pol) {
    asm volatile("cp.async.bulk.tensor.3d.shared::cluster.global.mbarrier::complete_tx::bytes.L2::cache_hint [%0], [%1, {%3, %4, %5}], [%2], %6;"
                 :: "r"(dst), "l"(tm), "r"(bar), "r"(c0), "r"(c1), "r"(c2), "l"(pol) : "memory");
}
__device__ __forceinline__ void tma_store(const CUtensorMap* tm, uint32_t src, int c0, int c1) {
    asm volatile("cp.async.bulk.tensor.2d.global.shared::cta.bulk_group [%0, {%2, %3}], [%1];" :: "l"(tm), "r"(src), "r"(c0), "r"(c1) : "memory");
}
__device__ __forceinline__ void tma_prefetch(const CUtensorMap* tm, int c0, int c1) {
    asm volatile("cp.async.bulk.prefetch.tensor.2d.L2.global [%0, {%1, %2}];" :: "l"(tm), "r"(c0), "r"(c1) : "memory");
}
__device__ __forceinline__ void tm_prefetch(const CUtensorMap* tm) { asm volatile("prefetch.tensormap [%0];" :: "l"(tm) : "memory"); }
__device__ __forceinline__ void wg_fence() { asm volatile("wgmma.fence.sync.aligned;" ::: "memory"); }
__device__ __forceinline__ void wg_commit() { asm volatile("wgmma.commit_group.sync.aligned;" ::: "memory"); }
template <int N> __device__ __forceinline__ void wg_wait() { asm volatile("wgmma.wait_group.sync.aligned %0;" :: "n"(N) : "memory"); }
template <int N> __device__ __forceinline__ void pin(uint32_t (&r)[N]) {
    #pragma unroll
    for (int i = 0; i < N; i++) asm volatile("" : "+r"(r[i]) :: "memory");
}
template <int N> __device__ __forceinline__ void pin(float (&r)[N]) {
    #pragma unroll
    for (int i = 0; i < N; i++) asm volatile("" : "+f"(r[i]) :: "memory");
}
template <int N> __device__ __forceinline__ void reg_inc() { asm volatile("setmaxnreg.inc.sync.aligned.u32 %0;" :: "n"(N)); }
template <int N> __device__ __forceinline__ void reg_dec() { asm volatile("setmaxnreg.dec.sync.aligned.u32 %0;" :: "n"(N)); }
__host__ __device__ constexpr uint64_t desc_plain(uint32_t addr, uint32_t lbo, uint32_t sbo) {
    return (uint64_t)((addr & 0x3FFFF) >> 4) | ((uint64_t)(lbo >> 4) << 16) | ((uint64_t)(sbo >> 4) << 32);
}
__host__ __device__ constexpr uint64_t desc_sw128(uint32_t addr, uint32_t lbo, uint32_t sbo) { return desc_plain(addr, lbo, sbo) | (1ull << 62); }
__host__ __device__ constexpr uint64_t desc_sw64(uint32_t addr, uint32_t lbo, uint32_t sbo) { return desc_plain(addr, lbo, sbo) | (2ull << 62); }

__device__ __forceinline__ uint32_t lds32(uint32_t a) { uint32_t v; asm volatile("ld.shared.b32 %0, [%1];" : "=r"(v) : "r"(a) : "memory"); return v; }
__device__ __forceinline__ uint32_t lds16(uint32_t a) { uint32_t v; asm volatile("ld.shared.u16 %0, [%1];" : "=r"(v) : "r"(a) : "memory"); return v; }
__device__ __forceinline__ float ldsf(uint32_t a) { return __uint_as_float(lds32(a)); }
__device__ __forceinline__ float2 lds64f(uint32_t a) { float2 v; asm volatile("ld.shared.v2.f32 {%0, %1}, [%2];" : "=f"(v.x), "=f"(v.y) : "r"(a) : "memory"); return v; }
__device__ __forceinline__ uint4 lds128(uint32_t a) { uint4 v; asm volatile("ld.shared.v4.b32 {%0, %1, %2, %3}, [%4];" : "=r"(v.x), "=r"(v.y), "=r"(v.z), "=r"(v.w) : "r"(a) : "memory"); return v; }
__device__ __forceinline__ void sts16(uint32_t a, uint32_t v) { asm volatile("st.shared.b16 [%0], %1;" :: "r"(a), "h"((uint16_t)v) : "memory"); }
__device__ __forceinline__ void sts32(uint32_t a, uint32_t v) { asm volatile("st.shared.b32 [%0], %1;" :: "r"(a), "r"(v) : "memory"); }
__device__ __forceinline__ void stsf(uint32_t a, float v) { sts32(a, __float_as_uint(v)); }
__device__ __forceinline__ void sts64(uint32_t a, uint32_t x, uint32_t y) { asm volatile("st.shared.v2.b32 [%0], {%1, %2};" :: "r"(a), "r"(x), "r"(y) : "memory"); }
__device__ __forceinline__ void sts128(uint32_t a, uint32_t x, uint32_t y, uint32_t z, uint32_t w) { asm volatile("st.shared.v4.b32 [%0], {%1, %2, %3, %4};" :: "r"(a), "r"(x), "r"(y), "r"(z), "r"(w) : "memory"); }
__device__ __forceinline__ void stsm4(uint32_t a, uint32_t x, uint32_t y, uint32_t z, uint32_t w) {
    asm volatile("stmatrix.sync.aligned.m8n8.x4.shared.b16 [%0], {%1, %2, %3, %4};" :: "r"(a), "r"(x), "r"(y), "r"(z), "r"(w) : "memory");
}
__device__ __forceinline__ void ldsm4(uint32_t& a0, uint32_t& a1, uint32_t& a2, uint32_t& a3, uint32_t addr) {
    asm volatile("ldmatrix.sync.aligned.m8n8.x4.shared.b16 {%0,%1,%2,%3}, [%4];" : "=r"(a0), "=r"(a1), "=r"(a2), "=r"(a3) : "r"(addr) : "memory");
}
__device__ __forceinline__ void ldsm4t(uint32_t& a0, uint32_t& a1, uint32_t& a2, uint32_t& a3, uint32_t addr) {
    asm volatile("ldmatrix.sync.aligned.m8n8.x4.trans.shared.b16 {%0,%1,%2,%3}, [%4];" : "=r"(a0), "=r"(a1), "=r"(a2), "=r"(a3) : "r"(addr) : "memory");
}
__device__ __forceinline__ void mma_bf16(float (&d)[4], uint32_t a0, uint32_t a1, uint32_t a2, uint32_t a3, uint32_t b0, uint32_t b1) {
    asm("mma.sync.aligned.m16n8k16.row.col.f32.bf16.bf16.f32 {%0,%1,%2,%3}, {%4,%5,%6,%7}, {%8,%9}, {%0,%1,%2,%3};"
        : "+f"(d[0]), "+f"(d[1]), "+f"(d[2]), "+f"(d[3]) : "r"(a0), "r"(a1), "r"(a2), "r"(a3), "r"(b0), "r"(b1));
}
__device__ __forceinline__ void mma_bf16_k8(float (&d)[4], uint32_t a0, uint32_t a1, uint32_t b0) {
    asm("mma.sync.aligned.m16n8k8.row.col.f32.bf16.bf16.f32 {%0,%1,%2,%3}, {%4,%5}, {%6}, {%0,%1,%2,%3};"
        : "+f"(d[0]), "+f"(d[1]), "+f"(d[2]), "+f"(d[3]) : "r"(a0), "r"(a1), "r"(b0));
}
__device__ __forceinline__ void mma_f16(float (&d)[4], uint32_t a0, uint32_t a1, uint32_t a2, uint32_t a3, uint32_t b0, uint32_t b1) {
    asm("mma.sync.aligned.m16n8k16.row.col.f32.f16.f16.f32 {%0,%1,%2,%3}, {%4,%5,%6,%7}, {%8,%9}, {%0,%1,%2,%3};"
        : "+f"(d[0]), "+f"(d[1]), "+f"(d[2]), "+f"(d[3]) : "r"(a0), "r"(a1), "r"(a2), "r"(a3), "r"(b0), "r"(b1));
}
__device__ __forceinline__ void stg128_pred(void* p, const uint4& v, bool on) {
    asm volatile("{\n.reg .pred q;\nsetp.ne.u32 q, %5, 0;\n@q st.global.v4.b32 [%0], {%1, %2, %3, %4};\n}"
                 :: "l"(p), "r"(v.x), "r"(v.y), "r"(v.z), "r"(v.w), "r"((uint32_t)on) : "memory");
}
__device__ __forceinline__ void st_x32(void* p, uint32_t v) { asm volatile("st.relaxed.gpu.global.u32 [%0], %1;" :: "l"(p), "r"(v) : "memory"); }
__device__ __forceinline__ void st_x64(void* p, uint32_t x, uint32_t y) {
    asm volatile("{\n.reg .b64 v;\nmov.b64 v, {%1, %2};\nst.relaxed.gpu.global.b64 [%0], v;\n}" :: "l"(p), "r"(x), "r"(y) : "memory");
}
__device__ __forceinline__ void st_x128(void* p, uint32_t x, uint32_t y, uint32_t z, uint32_t w) {
    asm volatile("{\n.reg .b64 a, b;\n.reg .b128 v;\nmov.b64 a, {%1, %2};\nmov.b64 b, {%3, %4};\nmov.b128 v, {a, b};\nst.relaxed.gpu.global.b128 [%0], v;\n}"
                 :: "l"(p), "r"(x), "r"(y), "r"(z), "r"(w) : "memory");
}
__device__ __forceinline__ uint32_t ld_x32(const void* p) { uint32_t v; asm volatile("ld.relaxed.gpu.global.u32 %0, [%1];" : "=r"(v) : "l"(p) : "memory"); return v; }
__device__ __forceinline__ uint2 ld_x64(const void* p) {
    uint2 v; asm volatile("{\n.reg .b64 a;\nld.relaxed.gpu.global.b64 a, [%2];\nmov.b64 {%0, %1}, a;\n}" : "=r"(v.x), "=r"(v.y) : "l"(p) : "memory"); return v;
}
__device__ __forceinline__ uint4 ld_x128(const void* p) {
    uint4 v;
    asm volatile("{\n.reg .b64 a, b;\n.reg .b128 v;\nld.relaxed.gpu.global.b128 v, [%4];\nmov.b128 {a, b}, v;\nmov.b64 {%0, %1}, a;\nmov.b64 {%2, %3}, b;\n}"
                 : "=r"(v.x), "=r"(v.y), "=r"(v.z), "=r"(v.w) : "l"(p) : "memory");
    return v;
}
__device__ __forceinline__ void poll_tick(uint32_t& n) { asm volatile("{\n.reg .pred p;\nadd.u32 %0, %0, 1;\nsetp.ge.u32 p, %0, 0x800000;\n@p st.global.u32 [%1], %0;\n}" : "+r"(n) : "l"(0ull)); }
__device__ __forceinline__ void ctr_arrive(int* c) { asm volatile("red.release.gpu.global.add.s32 [%0], 1;" :: "l"(c) : "memory"); }
__device__ __forceinline__ void ctr_wait(const int* c, int target) {
    int v;
    uint32_t n = 0;
    #pragma unroll 1
    do {
        asm volatile("ld.acquire.gpu.global.s32 %0, [%1];" : "=r"(v) : "l"(c) : "memory");
        poll_tick(n);
    } while (v < target);
}
__device__ __forceinline__ void flag_wait(const uint8_t* f) {
    uint32_t n = 0, v;
    #pragma unroll 1
    do { asm volatile("ld.acquire.gpu.global.u8 %0, [%1];" : "=r"(v) : "l"(f) : "memory"); poll_tick(n); } while (v);
}
__device__ __forceinline__ void flags16_wait(const uint8_t* f) {
    uint32_t n = 0;
    uint64_t v;
    #pragma unroll 1
    do {
        asm volatile("{\n.reg .b64 a, b;\n.reg .b128 v;\nld.acquire.gpu.global.b128 v, [%1];\nmov.b128 {a, b}, v;\nor.b64 %0, a, b;\n}" : "=l"(v) : "l"(f) : "memory");
        poll_tick(n);
    } while (v != 0);
}
__device__ __forceinline__ bool any_empty(const uint4& v) { return v.x == EMPTY || v.y == EMPTY || v.z == EMPTY || v.w == EMPTY; }
__device__ __forceinline__ bool warp_any(bool p) { return __any_sync(0xffffffffu, p); }

__device__ __forceinline__ float ex2(float x) { float y; asm("ex2.approx.ftz.f32 %0, %1;" : "=f"(y) : "f"(x)); return y; }
__device__ __forceinline__ float rsq(float x) { float y; asm("rsqrt.approx.ftz.f32 %0, %1;" : "=f"(y) : "f"(x)); return y; }
__device__ __forceinline__ float rcp(float x) { float y; asm("rcp.approx.ftz.f32 %0, %1;" : "=f"(y) : "f"(x)); return y; }
__device__ __forceinline__ uint32_t pack_bf16(float lo, float hi) { uint32_t r; asm("cvt.rn.bf16x2.f32 %0, %1, %2;" : "=r"(r) : "f"(hi), "f"(lo)); return r; }
__device__ __forceinline__ uint32_t pack_f16(float lo, float hi) { uint32_t r; asm("cvt.rn.f16x2.f32 %0, %1, %2;" : "=r"(r) : "f"(hi), "f"(lo)); return r; }
__device__ __forceinline__ float bf_lo(uint32_t v) { return __uint_as_float(v << 16); }
__device__ __forceinline__ float bf_hi(uint32_t v) { return __uint_as_float(v & 0xFFFF0000u); }
__device__ __forceinline__ float bf_round(float x) { return __uint_as_float(pack_bf16(0.f, x)); }
__device__ __forceinline__ void h2_unpack(uint32_t v, float& lo, float& hi) {
    asm("{.reg .f16 l, h; mov.b32 {l, h}, %2; cvt.f32.f16 %0, l; cvt.f32.f16 %1, h;}" : "=f"(lo), "=f"(hi) : "r"(v));
}
__device__ __forceinline__ uint32_t hadd2(uint32_t a, uint32_t b) { uint32_t r; asm("add.rn.f16x2 %0, %1, %2;" : "=r"(r) : "r"(a), "r"(b)); return r; }
__device__ __forceinline__ uint32_t hmax2(uint32_t a, uint32_t b) { uint32_t r; asm("max.f16x2 %0, %1, %2;" : "=r"(r) : "r"(a), "r"(b)); return r; }
__device__ __forceinline__ uint32_t badd2(uint32_t a, uint32_t b) { uint32_t r; asm("add.rn.bf16x2 %0, %1, %2;" : "=r"(r) : "r"(a), "r"(b)); return r; }
__device__ __forceinline__ uint32_t bmul2(uint32_t a, uint32_t b) { uint32_t r; asm("mul.rn.bf16x2 %0, %1, %2;" : "=r"(r) : "r"(a), "r"(b)); return r; }
__device__ __forceinline__ float warp_sum(float v) {
    #pragma unroll
    for (int o = 16; o > 0; o >>= 1) v += __shfl_xor_sync(0xffffffffu, v, o);
    return v;
}
__device__ __forceinline__ float quad_sum(float v) { v += __shfl_xor_sync(0xffffffffu, v, 1); return v + __shfl_xor_sync(0xffffffffu, v, 2); }
__device__ __forceinline__ float quad_max(float v) { v = fmaxf(v, __shfl_xor_sync(0xffffffffu, v, 1)); return fmaxf(v, __shfl_xor_sync(0xffffffffu, v, 2)); }
__device__ __forceinline__ uint32_t redux_max(uint32_t v) { uint32_t r; asm volatile("redux.sync.max.u32 %0, %1, 0xffffffff;" : "=r"(r) : "r"(v)); return r; }
__device__ __forceinline__ uint32_t redux_min(uint32_t v) { uint32_t r; asm volatile("redux.sync.min.u32 %0, %1, 0xffffffff;" : "=r"(r) : "r"(v)); return r; }
__device__ __forceinline__ uint32_t order_bits(float r) { const uint32_t u = __float_as_uint(r); return (u & 0x80000000u) ? ~u : (u | 0x80000000u); }
struct Ln2 { uint32_t nm, rh, rl, c; };
__device__ __forceinline__ Ln2 ln2_coef(float mean, float rstd) {
    const uint32_t a = pack_bf16(-mean, rstd), b = pack_bf16((-mean - bf_lo(a)) * rstd, rstd - bf_hi(a));
    return {__byte_perm(a, 0, 0x1010), __byte_perm(a, 0, 0x3232), __byte_perm(b, 0, 0x3232), __byte_perm(b, 0, 0x1010)};
}
__device__ __forceinline__ uint32_t bfma2(uint32_t a, uint32_t b, uint32_t c) { uint32_t r; asm("fma.rn.bf16x2 %0, %1, %2, %3;" : "=r"(r) : "r"(a), "r"(b), "r"(c)); return r; }
__device__ __forceinline__ uint32_t ln2(uint32_t v, const Ln2& k) { const uint32_t d = badd2(v, k.nm); return bfma2(d, k.rh, bfma2(d, k.rl, k.c)); }
__device__ __forceinline__ uint32_t add_ln2(uint32_t v, const Ln2& k) { return badd2(v, ln2(v, k)); }

#define TL(TID, i)
#define CK(TID, i)

__device__ __forceinline__ void wg_gemm_n128(float (&d)[64], uint64_t desca, uint64_t desc) {
    asm volatile("{\n.reg .pred p;\nsetp.ne.b32 p, 1, 0;\n"
        "wgmma.mma_async.sync.aligned.m64n128k16.f32.bf16.bf16 "
        "{%0,%1,%2,%3,%4,%5,%6,%7,%8,%9,%10,%11,%12,%13,%14,%15,%16,%17,%18,%19,%20,%21,%22,%23,%24,%25,%26,%27,%28,%29,%30,%31,%32,%33,%34,%35,%36,%37,%38,%39,%40,%41,%42,%43,%44,%45,%46,%47,%48,%49,%50,%51,%52,%53,%54,%55,%56,%57,%58,%59,%60,%61,%62,%63}, "
        "%64, %65, p, 1, 1, 0, 1;\n}\n"
        : "+f"(d[0]), "+f"(d[1]), "+f"(d[2]), "+f"(d[3]), "+f"(d[4]), "+f"(d[5]), "+f"(d[6]), "+f"(d[7]), "+f"(d[8]), "+f"(d[9]), "+f"(d[10]), "+f"(d[11]),
          "+f"(d[12]), "+f"(d[13]), "+f"(d[14]), "+f"(d[15]), "+f"(d[16]), "+f"(d[17]), "+f"(d[18]), "+f"(d[19]), "+f"(d[20]), "+f"(d[21]), "+f"(d[22]), "+f"(d[23]),
          "+f"(d[24]), "+f"(d[25]), "+f"(d[26]), "+f"(d[27]), "+f"(d[28]), "+f"(d[29]), "+f"(d[30]), "+f"(d[31]), "+f"(d[32]), "+f"(d[33]), "+f"(d[34]), "+f"(d[35]),
          "+f"(d[36]), "+f"(d[37]), "+f"(d[38]), "+f"(d[39]), "+f"(d[40]), "+f"(d[41]), "+f"(d[42]), "+f"(d[43]), "+f"(d[44]), "+f"(d[45]), "+f"(d[46]), "+f"(d[47]),
          "+f"(d[48]), "+f"(d[49]), "+f"(d[50]), "+f"(d[51]), "+f"(d[52]), "+f"(d[53]), "+f"(d[54]), "+f"(d[55]), "+f"(d[56]), "+f"(d[57]), "+f"(d[58]), "+f"(d[59]),
          "+f"(d[60]), "+f"(d[61]), "+f"(d[62]), "+f"(d[63])
        : "l"(desca), "l"(desc));
}
__device__ __forceinline__ void wg_gemm_n192(float (&d)[96], uint64_t desca, uint64_t desc) {
    asm volatile("{\n.reg .pred p;\nsetp.ne.b32 p, 1, 0;\n"
        "wgmma.mma_async.sync.aligned.m64n192k16.f32.bf16.bf16 "
        "{%0,%1,%2,%3,%4,%5,%6,%7,%8,%9,%10,%11,%12,%13,%14,%15,%16,%17,%18,%19,%20,%21,%22,%23,%24,%25,%26,%27,%28,%29,%30,%31,%32,%33,%34,%35,%36,%37,%38,%39,%40,%41,%42,%43,%44,%45,%46,%47,%48,%49,%50,%51,%52,%53,%54,%55,%56,%57,%58,%59,%60,%61,%62,%63,%64,%65,%66,%67,%68,%69,%70,%71,%72,%73,%74,%75,%76,%77,%78,%79,%80,%81,%82,%83,%84,%85,%86,%87,%88,%89,%90,%91,%92,%93,%94,%95}, "
        "%96, %97, p, 1, 1, 0, 1;\n}\n"
        : "+f"(d[0]), "+f"(d[1]), "+f"(d[2]), "+f"(d[3]), "+f"(d[4]), "+f"(d[5]), "+f"(d[6]), "+f"(d[7]), "+f"(d[8]), "+f"(d[9]), "+f"(d[10]), "+f"(d[11]),
          "+f"(d[12]), "+f"(d[13]), "+f"(d[14]), "+f"(d[15]), "+f"(d[16]), "+f"(d[17]), "+f"(d[18]), "+f"(d[19]), "+f"(d[20]), "+f"(d[21]), "+f"(d[22]), "+f"(d[23]),
          "+f"(d[24]), "+f"(d[25]), "+f"(d[26]), "+f"(d[27]), "+f"(d[28]), "+f"(d[29]), "+f"(d[30]), "+f"(d[31]), "+f"(d[32]), "+f"(d[33]), "+f"(d[34]), "+f"(d[35]),
          "+f"(d[36]), "+f"(d[37]), "+f"(d[38]), "+f"(d[39]), "+f"(d[40]), "+f"(d[41]), "+f"(d[42]), "+f"(d[43]), "+f"(d[44]), "+f"(d[45]), "+f"(d[46]), "+f"(d[47]),
          "+f"(d[48]), "+f"(d[49]), "+f"(d[50]), "+f"(d[51]), "+f"(d[52]), "+f"(d[53]), "+f"(d[54]), "+f"(d[55]), "+f"(d[56]), "+f"(d[57]), "+f"(d[58]), "+f"(d[59]),
          "+f"(d[60]), "+f"(d[61]), "+f"(d[62]), "+f"(d[63]), "+f"(d[64]), "+f"(d[65]), "+f"(d[66]), "+f"(d[67]), "+f"(d[68]), "+f"(d[69]), "+f"(d[70]), "+f"(d[71]),
          "+f"(d[72]), "+f"(d[73]), "+f"(d[74]), "+f"(d[75]), "+f"(d[76]), "+f"(d[77]), "+f"(d[78]), "+f"(d[79]), "+f"(d[80]), "+f"(d[81]), "+f"(d[82]), "+f"(d[83]),
          "+f"(d[84]), "+f"(d[85]), "+f"(d[86]), "+f"(d[87]), "+f"(d[88]), "+f"(d[89]), "+f"(d[90]), "+f"(d[91]), "+f"(d[92]), "+f"(d[93]), "+f"(d[94]), "+f"(d[95])
        : "l"(desca), "l"(desc));
}
__device__ __forceinline__ void wg_gemm_n192_init(float (&d)[96], uint64_t desca, uint64_t desc) {
    asm volatile("{\n.reg .pred p;\nsetp.ne.b32 p, 0, 0;\n"
        "wgmma.mma_async.sync.aligned.m64n192k16.f32.bf16.bf16 "
        "{%0,%1,%2,%3,%4,%5,%6,%7,%8,%9,%10,%11,%12,%13,%14,%15,%16,%17,%18,%19,%20,%21,%22,%23,%24,%25,%26,%27,%28,%29,%30,%31,%32,%33,%34,%35,%36,%37,%38,%39,%40,%41,%42,%43,%44,%45,%46,%47,%48,%49,%50,%51,%52,%53,%54,%55,%56,%57,%58,%59,%60,%61,%62,%63,%64,%65,%66,%67,%68,%69,%70,%71,%72,%73,%74,%75,%76,%77,%78,%79,%80,%81,%82,%83,%84,%85,%86,%87,%88,%89,%90,%91,%92,%93,%94,%95}, "
        "%96, %97, p, 1, 1, 0, 1;\n}\n"
        : "=f"(d[0]), "=f"(d[1]), "=f"(d[2]), "=f"(d[3]), "=f"(d[4]), "=f"(d[5]), "=f"(d[6]), "=f"(d[7]), "=f"(d[8]), "=f"(d[9]), "=f"(d[10]), "=f"(d[11]),
          "=f"(d[12]), "=f"(d[13]), "=f"(d[14]), "=f"(d[15]), "=f"(d[16]), "=f"(d[17]), "=f"(d[18]), "=f"(d[19]), "=f"(d[20]), "=f"(d[21]), "=f"(d[22]), "=f"(d[23]),
          "=f"(d[24]), "=f"(d[25]), "=f"(d[26]), "=f"(d[27]), "=f"(d[28]), "=f"(d[29]), "=f"(d[30]), "=f"(d[31]), "=f"(d[32]), "=f"(d[33]), "=f"(d[34]), "=f"(d[35]),
          "=f"(d[36]), "=f"(d[37]), "=f"(d[38]), "=f"(d[39]), "=f"(d[40]), "=f"(d[41]), "=f"(d[42]), "=f"(d[43]), "=f"(d[44]), "=f"(d[45]), "=f"(d[46]), "=f"(d[47]),
          "=f"(d[48]), "=f"(d[49]), "=f"(d[50]), "=f"(d[51]), "=f"(d[52]), "=f"(d[53]), "=f"(d[54]), "=f"(d[55]), "=f"(d[56]), "=f"(d[57]), "=f"(d[58]), "=f"(d[59]),
          "=f"(d[60]), "=f"(d[61]), "=f"(d[62]), "=f"(d[63]), "=f"(d[64]), "=f"(d[65]), "=f"(d[66]), "=f"(d[67]), "=f"(d[68]), "=f"(d[69]), "=f"(d[70]), "=f"(d[71]),
          "=f"(d[72]), "=f"(d[73]), "=f"(d[74]), "=f"(d[75]), "=f"(d[76]), "=f"(d[77]), "=f"(d[78]), "=f"(d[79]), "=f"(d[80]), "=f"(d[81]), "=f"(d[82]), "=f"(d[83]),
          "=f"(d[84]), "=f"(d[85]), "=f"(d[86]), "=f"(d[87]), "=f"(d[88]), "=f"(d[89]), "=f"(d[90]), "=f"(d[91]), "=f"(d[92]), "=f"(d[93]), "=f"(d[94]), "=f"(d[95])
        : "l"(desca), "l"(desc));
}
__device__ __forceinline__ void wg_qk_init(uint32_t (&d)[32], uint32_t a0, uint32_t a1, uint32_t a2, uint32_t a3, uint64_t desc) {
    asm volatile("{\n.reg .pred p;\nsetp.ne.b32 p, 0, 0;\n"
        "wgmma.mma_async.sync.aligned.m64n128k16.f16.f16.f16 "
        "{%0,%1,%2,%3,%4,%5,%6,%7,%8,%9,%10,%11,%12,%13,%14,%15,%16,%17,%18,%19,%20,%21,%22,%23,%24,%25,%26,%27,%28,%29,%30,%31}, "
        "{%32,%33,%34,%35}, %36, p, 1, 1, 0;\n}\n"
        : "=r"(d[0]), "=r"(d[1]), "=r"(d[2]), "=r"(d[3]), "=r"(d[4]), "=r"(d[5]), "=r"(d[6]), "=r"(d[7]), "=r"(d[8]), "=r"(d[9]), "=r"(d[10]), "=r"(d[11]),
          "=r"(d[12]), "=r"(d[13]), "=r"(d[14]), "=r"(d[15]), "=r"(d[16]), "=r"(d[17]), "=r"(d[18]), "=r"(d[19]), "=r"(d[20]), "=r"(d[21]), "=r"(d[22]), "=r"(d[23]),
          "=r"(d[24]), "=r"(d[25]), "=r"(d[26]), "=r"(d[27]), "=r"(d[28]), "=r"(d[29]), "=r"(d[30]), "=r"(d[31])
        : "r"(a0), "r"(a1), "r"(a2), "r"(a3), "l"(desc));
}
__device__ __forceinline__ void wg_qk_acc(uint32_t (&d)[32], uint32_t a0, uint32_t a1, uint32_t a2, uint32_t a3, uint64_t desc) {
    asm volatile("{\n.reg .pred p;\nsetp.ne.b32 p, 1, 0;\n"
        "wgmma.mma_async.sync.aligned.m64n128k16.f16.f16.f16 "
        "{%0,%1,%2,%3,%4,%5,%6,%7,%8,%9,%10,%11,%12,%13,%14,%15,%16,%17,%18,%19,%20,%21,%22,%23,%24,%25,%26,%27,%28,%29,%30,%31}, "
        "{%32,%33,%34,%35}, %36, p, 1, 1, 0;\n}\n"
        : "+r"(d[0]), "+r"(d[1]), "+r"(d[2]), "+r"(d[3]), "+r"(d[4]), "+r"(d[5]), "+r"(d[6]), "+r"(d[7]), "+r"(d[8]), "+r"(d[9]), "+r"(d[10]), "+r"(d[11]),
          "+r"(d[12]), "+r"(d[13]), "+r"(d[14]), "+r"(d[15]), "+r"(d[16]), "+r"(d[17]), "+r"(d[18]), "+r"(d[19]), "+r"(d[20]), "+r"(d[21]), "+r"(d[22]), "+r"(d[23]),
          "+r"(d[24]), "+r"(d[25]), "+r"(d[26]), "+r"(d[27]), "+r"(d[28]), "+r"(d[29]), "+r"(d[30]), "+r"(d[31])
        : "r"(a0), "r"(a1), "r"(a2), "r"(a3), "l"(desc));
}
__device__ __forceinline__ void wg_pv_init(uint32_t (&d)[10], uint32_t a0, uint32_t a1, uint32_t a2, uint32_t a3, uint64_t desc) {
    asm volatile("{\n.reg .pred p;\nsetp.ne.b32 p, 0, 0;\n"
        "wgmma.mma_async.sync.aligned.m64n40k16.f16.f16.f16 "
        "{%0,%1,%2,%3,%4,%5,%6,%7,%8,%9}, "
        "{%10,%11,%12,%13}, %14, p, 1, 1, 1;\n}\n"
        : "=r"(d[0]), "=r"(d[1]), "=r"(d[2]), "=r"(d[3]), "=r"(d[4]), "=r"(d[5]), "=r"(d[6]), "=r"(d[7]), "=r"(d[8]), "=r"(d[9])
        : "r"(a0), "r"(a1), "r"(a2), "r"(a3), "l"(desc));
}
__device__ __forceinline__ void wg_pv_acc(uint32_t (&d)[10], uint32_t a0, uint32_t a1, uint32_t a2, uint32_t a3, uint64_t desc) {
    asm volatile("{\n.reg .pred p;\nsetp.ne.b32 p, 1, 0;\n"
        "wgmma.mma_async.sync.aligned.m64n40k16.f16.f16.f16 "
        "{%0,%1,%2,%3,%4,%5,%6,%7,%8,%9}, "
        "{%10,%11,%12,%13}, %14, p, 1, 1, 1;\n}\n"
        : "+r"(d[0]), "+r"(d[1]), "+r"(d[2]), "+r"(d[3]), "+r"(d[4]), "+r"(d[5]), "+r"(d[6]), "+r"(d[7]), "+r"(d[8]), "+r"(d[9])
        : "r"(a0), "r"(a1), "r"(a2), "r"(a3), "l"(desc));
}

constexpr uint32_t SB = SMEM_BASE;
constexpr uint32_t R_SLOT = 18432, A_RING = SB, A_KP = SB + 73728, A_QX = SB + 81920, A_STB = SB + 98304;
constexpr uint32_t F_GU0 = SB + 98304, F_GU1 = SB + 163840, F_WD = F_GU0;
__host__ __device__ constexpr uint32_t o_a(uint32_t s) { return s == 0 ? SB : s == 1 ? A_QX : F_GU0 + (s - 2) * 32768; }
__host__ __device__ constexpr uint32_t o_b(uint32_t s) { return s < 2 ? SB + 16384 + s * 16384 : F_GU0 + 16384 + (s - 2) * 32768; }
constexpr uint32_t XT0 = SB + 49152, XT1 = XT0 + 16384, YT0 = o_a(0), YT1 = o_a(1);
constexpr uint32_t Q_ABYTES = 256 * 64 * 2, Q_STB = Q_ABYTES + 192 * 64 * 2;
constexpr uint32_t Q_CS = SB + 3 * Q_STB, Q_RC = Q_CS + 768, Q_FIX = Q_RC + 2048;
constexpr uint32_t SD_VEC = SB + 176128, SD_W = SB + 180224;
static_assert(Q_FIX + 768 <= SD_VEC, "smem");
constexpr uint32_t M_RED = SB + 229376, M_BAR = M_RED + 2048, BAR_SET = 336, M_HS = M_BAR + 2 * BAR_SET, M_SM = M_HS + 128;
constexpr uint32_t M_IV = M_SM;
constexpr uint32_t M_WS = M_SM + 16;
constexpr uint32_t M_CR = M_SM + 20;
constexpr uint32_t M_SS = M_SM + 24;
constexpr uint32_t M_RT = M_SM + 32;
constexpr uint32_t M_SR = M_SM + 96;
constexpr int K_SMEM = M_SR + 128 - SB;
static_assert(K_SMEM == 232448, "smem");
constexpr uint32_t B_QF = 0, B_AF = 24, B_OF = 56, B_RES = 88, B_GU = 96, B_WD = 104, B_RT = 112, B_SW = 120, B_ONE = 128, B_XD = 136, B_QE = 144, B_OE = 168,
                   B_PX = 200, B_AE = 224, B_OD = 256, B_FG = 288, B_FD = 296, B_XS = 304, B_KS = 312, B_K0 = 320, B_END = 328;
constexpr int NB_ML = 1, NB_CONS = 2, NB_SIDE = 3, NB_EPI = 4;

__device__ __forceinline__ int mt_of(int c) { return (c >> 2) & 7; }
__device__ __forceinline__ int nt_of(int c) { return (c >> 5) * 4 + (c & 3); }
__device__ __forceinline__ int blk_of(int c) { return c >> 3; }
__device__ __forceinline__ int cb_of(int c) { return c & 7; }

struct Maps { CUtensorMap x[2], wqkv, o, wo[2], r, g, u, d; };

template <int N>
__device__ __forceinline__ void halve(float (&v)[8], int lane, int bit) {
    const bool up = lane & bit;
    #pragma unroll
    for (int i = 0; i < N; i++) v[i] = (up ? v[N + i] : v[i]) + __shfl_xor_sync(0xffffffffu, up ? v[i] : v[N + i], bit);
}

__device__ __forceinline__ void reset_exchange(int c, int t) {
    #pragma unroll 1
    for (int i = t; i < FILL; i += 96) g_u.fill[c][i] = make_uint4(EMPTY, EMPTY, EMPTY, EMPTY);
}
__device__ __forceinline__ void prep_work(const bf16* __restrict__ x0, const bf16* __restrict__ w_r, uint32_t lb) {
    const int t = tid_now() - 288, c = cta_now(), lane = t & 31, warp = warp_uniform(t >> 5);
    const uint32_t wb = SD_W + warp * 8192;
    mbar_nap(lb + B_SW, 0);
    {
        float cs[8], cq[8];
        #pragma unroll
        for (int i = 0; i < 8; i++) { cs[i] = 0.f; cq[i] = 0.f; }
        #pragma unroll 1
        for (int h = 0; h < 2; h++) {
            #pragma unroll 2
            for (int r = 0; r < 16; r++) {
                const uint4 u = lds128(wb + h * 24576 + (lane >> 3) * 128 + r * 512 + (((lane & 7) ^ ((r * 4 + (lane >> 3)) & 7)) << 4));
                const uint32_t w[4] = {u.x, u.y, u.z, u.w};
                #pragma unroll
                for (int e = 0; e < 4; e++) {
                    const float a = bf_lo(w[e]), b = bf_hi(w[e]);
                    cs[2*e] += a; cs[2*e+1] += b; cq[2*e] = fmaf(a, a, cq[2*e]); cq[2*e+1] = fmaf(b, b, cq[2*e+1]);
                }
            }
            fence_async_smem();
            __syncwarp();
            if (elect_one()) {
                const uint32_t bytes = h == 0 ? 8192 : warp < 2 ? 4096 : 2048;
                mbar_expect_tx(lb + B_PX + warp * 8, bytes);
                bulk_load(wb + h * 24576, h && warp == 2 ? w_r : x0 + (size_t)(c * 16 + (h ? 12 + warp * 2 : warp * 4)) * D_, bytes, lb + B_PX + warp * 8);
            }
            __syncwarp();
        }
        halve<4>(cs, lane, 16); halve<2>(cs, lane, 8);
        halve<4>(cq, lane, 16); halve<2>(cq, lane, 8);
        *reinterpret_cast<float4*>(&g_cs[mt_of(c)][warp * D_ + nt_of(c) * 64 + (lane & 7) * 8 + (lane >> 3) * 2]) = make_float4(cs[0], cq[0], cs[1], cq[1]);
    }
    TL(288, 22);
    reset_exchange(c, t);
    mbar_nap(lb + B_PX + warp * 8, 0);
    #pragma unroll 1
    for (int i = 0; i < (warp < 2 ? 6 : 5); i++) {
        const int r = i < 4 ? warp * 4 + i : 8 + warp * 2 + i;
        float s0 = 0.f, s1 = 0.f, q0 = 0.f, q1 = 0.f;
        #pragma unroll 2
        for (int j = 0; j < 4; j++) {
            const uint4 u = lds128(wb + (i >> 2) * 16384 + i * 2048 + j * 512 + lane * 16);
            const uint32_t w[4] = {u.x, u.y, u.z, u.w};
            #pragma unroll
            for (int e = 0; e < 4; e++) { const float a = bf_lo(w[e]), b = bf_hi(w[e]); s0 += a; s1 += b; q0 = fmaf(a, a, q0); q1 = fmaf(b, b, q1); }
        }
        s0 += s1; q0 += q1;
        float v = (lane & 16 ? q0 : s0) + __shfl_xor_sync(0xffffffffu, lane & 16 ? s0 : q0, 16);
        #pragma unroll
        for (int o = 8; o > 0; o >>= 1) v += __shfl_xor_sync(0xffffffffu, v, o);
        const float mean = v * (1.f / D_), sq = __shfl_xor_sync(0xffffffffu, mean, 16);
        if (lane == 0) {
            if (r < 16) g_rs0[c * 16 + r] = make_float2(fmaxf(sq - mean * mean, 0.f), mean);
            else stsf(M_WS, v);
        }
    }
    named_sync(NB_SIDE, 96);
    if (t == 0) { TL(288, 23); ctr_arrive(&g_pctr); ctr_wait(&g_pctr, 128); TL(288, 24); }
    named_sync(NB_SIDE, 96);
}

__device__ __forceinline__ int half_exp(uint32_t bits, int off) { return min(max((((int)(bits >> 23) - 125) >> 1) + off, -55), 55); }
__device__ __forceinline__ float pow2(int e) { return __uint_as_float((uint32_t)(127 + e) << 23); }
__device__ __forceinline__ void head_scales(int h) {
    const float fq = ldsf(M_SR + h * 4), fk = ldsf(M_SR + 8 + h * 4);
    const uint32_t vmax = lds32(M_SR + 16 + h * 4), vmin = lds32(M_SR + 24 + h * 4);
    const bool ok = fq <= 16384.f && fk <= 16384.f && fq * fk <= 50000.f && vmax <= vmin + (12u << 23);
    const int a = ok ? 0 : half_exp(__float_as_uint(fq), -8), b = ok ? 0 : half_exp(__float_as_uint(fk), -8), v = half_exp(vmax, ok ? 3 : -10);
    stsf(M_HS + h * 4, QSCALE * pow2(-a)); stsf(M_HS + 8 + h * 4, pow2(-b)); stsf(M_HS + 16 + h * 4, pow2(-v));
    stsf(M_SS + h * 4, ok ? 0.f : pow2(a + b));
    stsf(M_IV + h * 4, pow2(v - 4));
}

__device__ __forceinline__ void epi_inputs(int L, const bf16* __restrict__ w_r) {
    const int t = tid_now() - 288, c = cta_now(), mt = mt_of(c), nt = nt_of(c), lane = t & 31;
    const uint32_t wr = t < 64 ? __ldg(reinterpret_cast<const uint32_t*>(w_r) + cb_of(c) * 64 + t) : 0x3F803F80u;
    #pragma unroll 1
    for (int k = 0; k < 3; k++) {
        const int i = t + 96 * k, col = (i >> 6) * D_ + nt * 64 + (i & 63);
        const float2* rsp = (L ? g_x.rs1 : g_rs0) + mt * 256 + (i & 255);
        uint2 sv = ld_x64(rsp);
        if (k < 2) {
            float2 p[8];
            #pragma unroll
            for (int j = 0; j < 8; j++) p[j] = __ldcg(&g_cs[j][col]);
            stsf(Q_CS + i * 4, ((p[0].x + p[1].x) + (p[2].x + p[3].x)) + ((p[4].x + p[5].x) + (p[6].x + p[7].x)));
            const float zz = ((p[0].y + p[1].y) + (p[2].y + p[3].y)) + ((p[4].y + p[5].y) + (p[6].y + p[7].y));
            const float zs = warp_sum(zz);
            const uint32_t zb = __float_as_uint(zz), zmax = redux_max(zb), zmin = redux_min(zb ? zb : 0x7F800000u);
            if (lane == 0) {
                sts32(M_SR + (i >> 5) * 4, i < 128 ? __float_as_uint(zs) : zmax);
                if (i >= 128) sts32(M_SR + 8 + (i >> 5) * 4, zmin);
            }
        } else {
            named_sync(NB_SIDE, 96);
            if (t < 2) head_scales(t);
            __syncwarp();
        }
        uint32_t n = 0;
        #pragma unroll 1
        while (warp_any(sv.x == EMPTY)) { sv = ld_x64(rsp); poll_tick(n); }
        const float var = __uint_as_float(sv.x), a = L ? 1.f + rsq(var + LN_EPS) : 1.f;
        sts64(Q_RC + (i & 255) * 8, __float_as_uint(a * rsq(a * a * var + LN_EPS)), sv.y ^ 0x80000000u);
    }
    if (t < 68) sts32(M_RED + t * 4, wr);
}

__device__ __forceinline__ void ffn_finish(int L, bf16* __restrict__ out) {
    const int t = tid_now() - 288, c = cta_now(), lane = t & 31, warp = warp_uniform(t >> 5);
    TL(288, L * 32 + 29);
    const uint4 rv = lds128(M_RT + 16 * L);
    const int idx = (int)rv.w;
    const uint32_t* xsrc = &g_x.cand[L][idx >> 7][(c >> 2) * 16 + (t & 3) * 4 + (c & 3)];
    const uint8_t* fsrc = &g_x.x[idx >> 8][((idx >> 7) & 1) * 8 + (c >> 4)];
    uint32_t xw, busy;
    float a[4] = {0.f, 0.f, 0.f, 0.f};
    {
        const float* src = &g_x.ypart[L][c][0][t * 4];
        uint4 v[3];
        uint32_t n = 0;
        #pragma unroll 1
        do {
            v[0] = ld_x128(src); v[1] = ld_x128(src + 384);
            v[2] = make_uint4(0u, 0u, 0u, 0u);
            xw = 0u; busy = 0u;
            if (warp == 0) {
                v[2] = ld_x128(src + 768); xw = ld_x32(xsrc);
                asm volatile("ld.relaxed.gpu.global.u8 %0, [%1];" : "=r"(busy) : "l"(fsrc) : "memory");
            }
            poll_tick(n);
        } while (warp_any(any_empty(v[0]) || any_empty(v[1]) || any_empty(v[2]) || xw == EMPTY || busy != 0));
        TL(288, L * 32 + 30); TL(352, L * 32 + 31);
        #pragma unroll
        for (int i = 0; i < 3; i++) { a[0] += __uint_as_float(v[i].x); a[1] += __uint_as_float(v[i].y); a[2] += __uint_as_float(v[i].z); a[3] += __uint_as_float(v[i].w); }
    }
    #pragma unroll
    for (int o = 2; o < 32; o <<= 1) {
        #pragma unroll
        for (int i = 0; i < 4; i++) a[i] += __shfl_xor_sync(0xffffffffu, a[i], o);
    }
    if (lane < 2) sts128(M_SR + warp * 32 + lane * 16, __float_as_uint(a[0]), __float_as_uint(a[1]), __float_as_uint(a[2]), __float_as_uint(a[3]));
    named_sync(NB_SIDE, 96);
    if (t < 4) {
        const float2 y0 = lds64f(M_SR + t * 8), y1 = lds64f(M_SR + 32 + t * 8), y2 = lds64f(M_SR + 64 + t * 8);
        const uint32_t y = pack_bf16(y0.x + y1.x + y2.x, y0.y + y1.y + y2.y);
        const float rsel = bf_round(rcp(1.f + __expf(-bf_round(__uint_as_float(rv.x)))));
        const uint32_t xn = ln2(xw, ln2_coef(__uint_as_float(rv.y), __uint_as_float(rv.z)));
        const uint32_t res = badd2(xw, badd2(xn, pack_bf16(bf_lo(y) * rsel, bf_hi(y) * rsel)));
        if (L == 0) st_x32(&g_x.x2row[c * 4 + t], res);
        reinterpret_cast<uint32_t*>(L ? out : g_x1)[idx * (D_ / 2) + c * 4 + t] = res;
    }
}

__device__ __forceinline__ void fix_row(uint32_t lb) {
    const int t = tid_now() - 288, c = cta_now(), lane = t & 31, warp = warp_uniform(t >> 5);
    uint4 v[2];
    {
        uint32_t n = 0;
        #pragma unroll 1
        do {
            v[0] = ld_x128(g_x.x2row + t * 4);
            v[1] = make_uint4(0u, 0u, 0u, 0u);
            if (warp == 0) v[1] = ld_x128(g_x.x2row + (96 + t) * 4);
            poll_tick(n);
        } while (warp_any(any_empty(v[0]) || any_empty(v[1])));
    }
    const uint32_t w[8] = {v[0].x, v[0].y, v[0].z, v[0].w, v[1].x, v[1].y, v[1].z, v[1].w};
    float su = 0.f, sq = 0.f;
    #pragma unroll
    for (int i = 0; i < 8; i++) { const float a = bf_lo(w[i]), b = bf_hi(w[i]); su += a + b; sq = fmaf(a, a, fmaf(b, b, sq)); }
    su = warp_sum(su); sq = warp_sum(sq);
    if (lane == 0) sts64(M_SR + 96 + warp * 8, __float_as_uint(su), __float_as_uint(sq));
    named_sync(NB_SIDE, 96);
    const float2 s0 = lds64f(M_SR + 96), s1 = lds64f(M_SR + 104), s2 = lds64f(M_SR + 112);
    const float mean = (s0.x + s1.x + s2.x) * (1.f / D_);
    const float rstd = rsq(fmaxf((s0.y + s1.y + s2.y) * (1.f / D_) - mean * mean, 0.f) + LN_EPS);
    const Ln2 k = ln2_coef(mean, rstd);
    #pragma unroll
    for (int i = 0; i < 2; i++)
        if (i == 0 || warp == 0) sts128(SD_VEC + (t + 96 * i) * 16, ln2(w[4*i], k), ln2(w[4*i+1], k), ln2(w[4*i+2], k), ln2(w[4*i+3], k));
    named_sync(NB_SIDE, 96);
    TL(288, 32 + 22);
    mbar_nap(lb + B_SW, 0);
    float a[8];
    #pragma unroll
    for (int i = 0; i < 8; i++) a[i] = 0.f;
    const uint32_t xa = base32(SD_VEC + lane * 2), wa = base32(SD_W + lane * 48 + warp * 16);
    #pragma unroll 2
    for (int b = 0; b < 32; b++) {
        const float x = bf_lo(lds16(xa + b * 64));
        const uint4 u = lds128(wa + b * 1536);
        a[0] = fmaf(x, bf_lo(u.x), a[0]); a[1] = fmaf(x, bf_hi(u.x), a[1]); a[2] = fmaf(x, bf_lo(u.y), a[2]); a[3] = fmaf(x, bf_hi(u.y), a[3]);
        a[4] = fmaf(x, bf_lo(u.z), a[4]); a[5] = fmaf(x, bf_hi(u.z), a[5]); a[6] = fmaf(x, bf_lo(u.w), a[6]); a[7] = fmaf(x, bf_hi(u.w), a[7]);
    }
    halve<4>(a, lane, 16); halve<2>(a, lane, 8); halve<1>(a, lane, 4);
    a[0] = quad_sum(a[0]);
    if ((lane & 3) == 0) st_x32(&g_x.fix[c * 24 + warp * 8 + (lane >> 2)], __float_as_uint(a[0]));
    TL(288, 32 + 23);
    if (((int)lds32(M_RT + 12) >> 8) == mt_of(c)) {
        const float* src = &g_x.fix[(t >> 5) * D_ + nt_of(c) * 64 + (t & 31) * 2];
        uint2 f;
        uint32_t n = 0;
        #pragma unroll 1
        do { f = ld_x64(src); poll_tick(n); } while (warp_any(f.x == EMPTY || f.y == EMPTY));
        sts64(Q_FIX + t * 8, f.x, f.y);
    }
}

__device__ __forceinline__ void out_piece(bf16* __restrict__ out, int r, int ch, bool on) {
    const uint4 v = lds128(((ch & 8) ? YT1 : YT0) + r * 128 + (((ch ^ r) & 7) << 4)), kk = lds128(XT0 + r * 16);
    const Ln2 k = {kk.x, kk.y, kk.z, kk.w};
    const int c = blockIdx.x;
    stg128_pred(out + (blk_of(c) * 128 + r) * D_ + cb_of(c) * 128 + ch * 8, make_uint4(add_ln2(v.x, k), add_ln2(v.y, k), add_ln2(v.z, k), add_ln2(v.w, k)), on);
}
__device__ __forceinline__ void publish(uint8_t* f) {
    bulk_commit();
    bulk_wait();
    fence_async_global();
    asm volatile("st.release.gpu.global.u8 [%0], 0;" :: "l"(f) : "memory");
}
__device__ __forceinline__ void side_role(const Maps& mp, const bf16* __restrict__ x0, const bf16* __restrict__ wo, const bf16* __restrict__ w_down, const bf16* __restrict__ w_r, bf16* __restrict__ out) {
    #pragma unroll 1
    for (int L = 0; L < 2; L++) {
        const uint32_t lb = M_BAR + L * BAR_SET;
        if (L == 0) prep_work(x0, w_r, lb);
        else fix_row(lb);
        epi_inputs(L, w_r);
        const int t = tid_now() - 288, c = cta_now(), mt = mt_of(c), nt = nt_of(c), warp = warp_uniform(t >> 5);
        TL(288, L * 32 + 4);
        named_arrive(NB_EPI, 224);
        named_arrive(NB_EPI + 1, 224);
        if (warp == 0) {
            named_sync(NB_ML, 288);
            #pragma unroll
            for (int i = 0; i < 16; i++) sts128(base32(A_RING + 16384 + t * 16) + (i >> 2) * R_SLOT + (i & 3) * 512, 0x2C002C00u, 0x2C002C00u, 0x2C002C00u, 0x2C002C00u);
            fence_async_smem();
            __syncwarp();
            mbar_arrive_elect(lb + B_ONE);
        }
        if (elect_one()) {
            #pragma unroll 1
            for (int n = warp - 1; n >= 0 && n < 3 * warp - 2; n++) {
                char* dst = g_kv + (size_t)(nt * 2 + (n >> 1)) * 16 * KV_TILE;
                if (n < 3) mbar_nap(lb + (n == 0 ? B_K0 : n == 1 ? B_KS : B_AE + 16), 0);
                bulk_store(dst + ((2 * mt - 1 + (n & 1)) & 15) * KV_TILE, n == 0 ? A_KP : n == 1 ? A_RING : A_STB + (n - 2) * 8192, 8192 << (n & 1));
                if (n & 1) bulk_store(dst + 2 * mt * KV_TILE + 24576, n == 1 ? A_RING + R_SLOT + 8192 : A_STB + 24576, 8192);
                publish(&g_x.kv[L][nt * 2 + (n >> 1)][2 * mt + (n & 1)]);
                if (n == 1) TL(352, L * 32 + 6);
                if (n == 0) TL(320, L * 32 + 27);
            }
            if (warp == 2) {
                const bool ffn = c < NFC;
                const uint64_t pol = policy_evict_first();
                mbar_expect_tx(lb + B_GU, ffn ? 131072 : 0);
                mbar_expect_tx(lb + B_WD, ffn ? 65536 : 0);
                l2_prefetch(reinterpret_cast<const char*>(wo) + (size_t)c * 16384, 16384);
                if (ffn) {
                    #pragma unroll 1
                    for (int i = 0; i < 12; i++) {
                        if (i < 8) tma_load_s(F_GU0 + i * 16384, (i & 1) ? &mp.u : &mp.g, c * 32, (i >> 1) * 256, lb + B_GU, pol);
                        else l2_prefetch(reinterpret_cast<const char*>(w_down) + (size_t)c * 65536 + (i - 8) * 16384, 16384);
                        __nanosleep(900);
                    }
                }
                mbar_nap(lb + B_OD, 0);
                __nanosleep(1000);
                l2_prefetch(g_u.fill[c], sizeof(g_u.fill[0]));
                if (L == 0) {
                    mbar_nap(lb + B_XS, 0);
                    tma_store(&mp.x[1], YT0, cb_of(c) * 128, blk_of(c) * 128);
                    tma_store(&mp.x[1], YT1, cb_of(c) * 128 + 64, blk_of(c) * 128);
                    publish(&g_x.x[blk_of(c) >> 1][(blk_of(c) & 1) * 8 + cb_of(c)]);
                    mbar_arrive(lb + B_XD);
                    TL(352, 18);
                }
            } else {
                #pragma unroll 1
                for (int p = 0; p < 2; p++) { mbar_sleep(lb + B_OD + (p * 2 + warp) * 8, 0); ctr_arrive(g_x.o[L][mt * 2 + warp][p]); TL(288, L * 32 + 19); }
            }
        }
        __syncwarp();
        if (L) {
            mbar_sleep(lb + B_XS, 0);
            const int cand = (int)lds32(M_CR) & 127;
            #pragma unroll 2
            for (int r = t >> 4; r < 132; r += 6) out_piece(out, r & 127, t & 15, r < 128 && r != cand);
            TL(288, 32 + 18);
            mbar_sleep(lb + B_RT, 0);
            out_piece(out, cand, t & 15, t < 16 && lds32(M_CR) != lds32(M_RT + 28));
        }
        const uint32_t late = mbar_test(lb + B_FD, 0);
        mbar_sleep(lb + B_FD, 0);
        __nanosleep(late ? 50 : 400);
        if (c == 0 && t == 0 && L == 0) g_pctr = 0;
        ffn_finish(L, out);
        TL(288, L * 32 + 20);
    }
}

struct Cols { float2 c[4]; float hs; };
template <int HH>
__device__ __forceinline__ void load_cols(Cols& k, uint32_t cs) {
    #pragma unroll
    for (int jj = 0; jj < 4; jj++) k.c[jj] = lds64f(cs + (HH * 32 + jj * 8) * 4);
    k.hs = ldsf(M_HS + HH * 4);
}
template <int HH>
__device__ __forceinline__ void qkv_epi_head(const float (&acc0)[96], const float (&acc1)[96], const float (&cf)[4], const float (&nm)[4], const Cols& k, uint32_t (&pk)[4][4]) {
    #pragma unroll
    for (int jj = 0; jj < 4; jj++) {
        #pragma unroll
        for (int i = 0; i < 4; i++) {
            const float* a = (i >> 1) ? acc1 : acc0;
            const float sc = cf[i] * k.hs;
            const float x = fmaf(nm[i], k.c[jj].x, a[4 * (4 * HH + jj) + 2 * (i & 1)]) * sc;
            const float y = fmaf(nm[i], k.c[jj].y, a[4 * (4 * HH + jj) + 2 * (i & 1) + 1]) * sc;
            pk[i][jj] = pack_f16(x, y);
        }
    }
}
__device__ __forceinline__ void stage_kv(uint32_t dst, const uint32_t (&pk)[4][4]) {
    #pragma unroll
    for (int i = 0; i < 4; i++) stsm4(dst + (i >> 1) * 1024 + (i & 1) * 128, pk[i][0], pk[i][1], pk[i][2], pk[i][3]);
}
template <int OFF>
__device__ __forceinline__ void patch_row(float (&acc)[96], uint32_t fx) {
    #pragma unroll
    for (int j = 0; j < 24; j++) { const float2 f = lds64f(fx + j * 32); acc[4 * j + OFF] = f.x; acc[4 * j + OFF + 1] = f.y; }
}
template <bool INIT>
__device__ __forceinline__ void qkv_step(float (&acc0)[96], float (&acc1)[96], uint64_t da, uint64_t db) {
    wg_fence();
    #pragma unroll
    for (int kk = 0; kk < 4; kk++) {
        if (INIT && kk == 0) { wg_gemm_n192_init(acc0, da, db); wg_gemm_n192_init(acc1, da + (8192 >> 4), db); }
        else { wg_gemm_n192(acc0, da + kk * 2, db + kk * 128); wg_gemm_n192(acc1, da + (8192 >> 4) + kk * 2, db + kk * 128); }
    }
    wg_commit();
}
__device__ __forceinline__ void qkv_phase(int L, uint32_t lb, int wg, uint32_t (&qa)[8], uint32_t (&qb)[8], uint32_t (&SA)[32], uint32_t (&SB_)[32]) {
    float acc0[96], acc1[96];
    {
        const bool leader = (tid_now() & 127) == 0;
        const uint64_t da0 = opaque(desc_sw128(SB + wg * 16384, 16, 1024)), db0 = opaque(desc_sw128(SB + Q_ABYTES, 8192, 1024));
        mbar_spin(lb + B_QF, 0);
        TL(0, L * 32 + 1); CK(0, L * 32 + 10);
        qkv_step<true>(acc0, acc1, da0, db0);
        uint32_t st = 1, ph = 0;
        #pragma unroll 1
        for (int k = 1; k < 16; k++) {
            mbar_spin(lb + B_QF + 8 * st, ph);
            if (k == 14 && wg) named_sync(NB_CONS, 256);
            qkv_step<false>(acc0, acc1, da0 + st * (Q_STB >> 4), db0 + st * (Q_STB >> 4));
            if (k == 15 && !wg) named_arrive(NB_CONS, 256);
            wg_wait<1>();
            if (leader) mbar_arrive(lb + B_QE + 8 * (st == 0 ? 2 : st - 1));
            if (++st == 3) { st = 0; ph ^= 1; }
        }
    }
    named_sync(NB_EPI + wg, 224);
    const int tid = tid_now(), lane = tid & 31, w = (tid >> 5) & 3, g = lane >> 2, t = lane & 3;
    const int lr0 = wg * 128 + w * 16 + g;
    float cf[4], nm[4];
    #pragma unroll
    for (int i = 0; i < 4; i++) { const float2 r = lds64f(base32(Q_RC + lr0 * 8) + ((i >> 1) * 64 + (i & 1) * 8) * 8); cf[i] = r.x; nm[i] = r.y; }
    const uint32_t cs = base32(Q_CS + t * 8);
    const int d = L ? (int)lds32(M_RT + 12) - (mt_of(cta_now()) * 256 + lr0) : -1;
    const uint32_t ko = base32((lane >> 3) * 2048 + (w * 16 + (lane & 7)) * 16);
    Cols k0, k1;
    load_cols<2>(k0, cs);
    wg_wait<0>();
    pin(acc0); pin(acc1);
    TL(128, L * 32 + 2); CK(128, L * 32 + 11);
    named_arrive(NB_ML, 288);
    if ((tid & 127) == 0) mbar_arrive(lb + B_QE);
    if (__builtin_expect((d & ~72) == 0, 0)) {
        if (d == 0) { patch_row<0>(acc0, cs + (Q_FIX - Q_CS)); cf[0] = 1.f; nm[0] = 0.f; }
        else if (d == 8) { patch_row<2>(acc0, cs + (Q_FIX - Q_CS)); cf[1] = 1.f; nm[1] = 0.f; }
        else if (d == 64) { patch_row<0>(acc1, cs + (Q_FIX - Q_CS)); cf[2] = 1.f; nm[2] = 0.f; }
        else { patch_row<2>(acc1, cs + (Q_FIX - Q_CS)); cf[3] = 1.f; nm[3] = 0.f; }
    }
    __syncwarp();
    uint32_t pk[4][4];
    qkv_epi_head<2>(acc0, acc1, cf, nm, k0, pk);
    load_cols<4>(k1, cs);
    mbar_spin(lb + B_QE + 8 - 8 * wg, wg);
    stage_kv((wg ? A_RING : A_KP) + ko, pk);
    if (!wg) {
        fence_async_smem();
        __syncwarp();
        mbar_arrive_elect(lb + B_K0);
    }
    qkv_epi_head<4>(acc0, acc1, cf, nm, k1, pk);
    load_cols<3>(k0, cs);
    stage_kv(A_RING + wg * R_SLOT + 8192 + ko, pk);
    fence_async_smem();
    __syncwarp();
    mbar_arrive_elect(lb + B_KS);
    qkv_epi_head<3>(acc0, acc1, cf, nm, k0, pk);
    load_cols<0>(k1, cs);
    load_cols<5>(k0, cs);
    stage_kv(A_STB + wg * 8192 + ko, pk);
    qkv_epi_head<0>(acc0, acc1, cf, nm, k1, pk);
    #pragma unroll
    for (int s = 0; s < 2; s++) {
        qa[4*s] = pk[0][2*s]; qa[4*s+1] = pk[1][2*s]; qa[4*s+2] = pk[0][2*s+1]; qa[4*s+3] = pk[1][2*s+1];
        qb[4*s] = pk[2][2*s]; qb[4*s+1] = pk[3][2*s]; qb[4*s+2] = pk[2][2*s+1]; qb[4*s+3] = pk[3][2*s+1];
    }
    mbar_spin(lb + B_K0, 0);
    {
        constexpr uint64_t dk = desc_plain(A_KP, 2048, 128);
        wg_fence();
        wg_qk_init(SA, qa[0], qa[1], qa[2], qa[3], dk);
        wg_qk_acc(SA, qa[4], qa[5], qa[6], qa[7], dk + 256);
        wg_qk_init(SB_, qb[0], qb[1], qb[2], qb[3], dk);
        wg_commit();
    }
    qkv_epi_head<5>(acc0, acc1, cf, nm, k0, pk);
    load_cols<1>(k1, cs);
    stage_kv(A_STB + 16384 + wg * 8192 + ko, pk);
    qkv_epi_head<1>(acc0, acc1, cf, nm, k1, pk);
    #pragma unroll
    for (int u = 0; u < 2; u++)
        #pragma unroll
        for (int s = 0; s < 2; s++) sts128(A_QX + (u * 2 + s) * 4096 + tid * 16, pk[2*u][2*s], pk[2*u+1][2*s], pk[2*u][2*s+1], pk[2*u+1][2*s+1]);
    fence_async_smem();
    wg_wait<0>();
    pin(SA); pin(SB_);
    TL(128, L * 32 + 5); CK(128, L * 32 + 12);
}

#define PMASK 0x0000AAAAu
#define IMASK 0x10101010u
__host__ __device__ constexpr bool is_poly(int j) { return !((PMASK >> j) & 1); }
struct Shift { uint32_t f0, f1, n0, n1, bad; };

__device__ __forceinline__ uint32_t exp2_mufu(uint32_t s, uint32_t nm) {
    uint32_t r;
    asm("ex2.approx.f16x2 %0, %1;" : "=r"(r) : "r"(hadd2(s, nm)));
    return r;
}
__device__ __forceinline__ uint32_t exp2_fix(uint32_t s, uint32_t fm, uint32_t ca, uint32_t& U, bool mul, uint32_t sixteen) {
    uint32_t G, D;
    asm("fma.rn.relu.f16x2 %0, %1, %2, %3;" : "=r"(U) : "r"(s), "r"(0x00400040u), "r"(fm));
    asm("fma.rn.f16x2 %0, %1, %2, %3;" : "=r"(G) : "r"(U & 0x003F003Fu), "r"(ca), "r"(0x98B898B8u));
    asm("{.reg .b32 n; neg.f16x2 n, %1; fma.rn.relu.f16x2 %0, %1, n, %2;}" : "=r"(D) : "r"(G), "r"(0x00570057u));
    if (mul) return U * sixteen - D;
    return (U << 4) - D;
}
__device__ __forceinline__ uint32_t or3(uint32_t a, uint32_t b, uint32_t c) { uint32_t r; asm("lop3.b32 %0, %1, %2, %3, 0xFE;" : "=r"(r) : "r"(a), "r"(b), "r"(c)); return r; }
__device__ __forceinline__ void exp_tile(const uint32_t (&S)[32], uint32_t (&P)[32], Shift& h, uint32_t ca, uint32_t sixteen) {
    uint32_t U[33];
    int n = 0;
    #pragma unroll
    for (int i = 0; i < 32; i++) {
        if (is_poly(i)) P[i] = exp2_fix(S[i], (i & 1) ? h.f1 : h.f0, ca, U[n++], (IMASK >> i) & 1, sixteen);
        else P[i] = exp2_mufu(S[i], (i & 1) ? h.n1 : h.n0);
    }
    U[n] = 0u;
    #pragma unroll
    for (int i = 0; i < 32; i += 6) {
        if (i + 5 <= n) h.bad = or3(h.bad, or3(U[i], U[i + 1], U[i + 2]), or3(U[i + 3], U[i + 4], U[i + 5]));
        else {
            #pragma unroll
            for (int j = i; j < i + 6; j += 2) if (j < n) h.bad = or3(h.bad, U[j], U[j + 1]);
        }
    }
    pin(P);
}
__device__ __forceinline__ uint32_t hfma2(uint32_t a, uint32_t b, uint32_t c) { uint32_t r; asm("fma.rn.f16x2 %0, %1, %2, %3;" : "=r"(r) : "r"(a), "r"(b), "r"(c)); return r; }
__device__ __forceinline__ void unit_start(const uint32_t (&S)[32], Shift& h, uint32_t (&o2)[10]) {
    uint32_t m[4] = {S[0], S[1], S[2], S[3]};
    #pragma unroll
    for (int i = 1; i < 8; i++)
        #pragma unroll
        for (int e = 0; e < 4; e++) m[e] = hmax2(m[e], S[4 * i + e]);
    const uint32_t a = hadd2(m[0], m[2]), c = hadd2(m[1], m[3]);
    uint32_t x = hadd2(__byte_perm(a, c, 0x5410), __byte_perm(a, c, 0x7632));
    x = hadd2(x, __shfl_xor_sync(0xffffffffu, x, 1));
    x = hadd2(x, __shfl_xor_sync(0xffffffffu, x, 2));
    const uint32_t T = hfma2(x, 0xAC00AC00u, 0x5DEB5DEBu);
    const uint32_t n = hadd2(T, 0xDE00DE00u), f = hfma2(n, 0x00400040u, 0x03C003C0u);
    h.n0 = __byte_perm(n, 0, 0x1010); h.n1 = __byte_perm(n, 0, 0x3232);
    h.f0 = __byte_perm(f, 0, 0x1010); h.f1 = __byte_perm(f, 0, 0x3232);
    h.bad = T ^ 0x58005800u;
    #pragma unroll
    for (int i = 0; i < 10; i++) o2[i] = 0u;
}
__device__ __forceinline__ uint32_t o_offset() {
    const int c = cta_now(), tid = tid_now();
    return (mt_of(c) * 256 + (tid & 128) + ((tid >> 1) & 48) + ((tid >> 2) & 7)) * (D_ * 2) + nt_of(c) * 64 + (tid & 3) * 16;
}
template <int PASS, int UNIT>
__device__ __forceinline__ void unit_end(const uint32_t (&o)[10], uint32_t bad, uint32_t lb, uint32_t oo, uint32_t& fail, float iv) {
    float v[20];
    #pragma unroll
    for (int i = 0; i < 10; i++) h2_unpack(o[i], v[2 * i], v[2 * i + 1]);
    const float i0 = rcp(v[16]) * iv, i1 = rcp(v[18]) * iv;
    uint32_t r[8], z = 0;
    #pragma unroll
    for (int j = 0; j < 4; j++) {
        r[j] = pack_bf16(v[4*j] * i0, v[4*j+1] * i0); r[4 + j] = pack_bf16(v[4*j+2] * i1, v[4*j+3] * i1);
        z = bfma2(r[j], r[4 + j], z);
    }
    const bool good = o[8] - 0x34003400u < 0x48000000u && o[9] - 0x34003400u < 0x48000000u &&
                      ((bad & 0xF800F800u) | (bmul2(z, 0u) & 0x7FFF7FFFu) | (fail & (1u << (2 * PASS + UNIT)))) == 0;
    const bool all = __all_sync(0xffffffffu, good);
    char* dst = reinterpret_cast<char*>(g_o) + oo + (UNIT * 64 * D_ + PASS * 512) * 2;
    stg128_pred(dst, make_uint4(r[0], r[1], r[2], r[3]), all);
    stg128_pred(dst + 16 * D_, make_uint4(r[4], r[5], r[6], r[7]), all);
    if (__builtin_expect(!all, 0)) {
        fail |= 1u << (2 * PASS + UNIT);
        if (PASS == 0) {
            #pragma unroll
            for (int s = 0; s < 2; s++) g_qsave[cta_now()][UNIT * 2 + s][tid_now()] = lds128(A_KP + (UNIT * 2 + s) * 4096 + tid_now() * 16);
        }
    }
    __syncwarp();
    mbar_arrive_elect_p(lb + PASS * 16, all);
}
__device__ __forceinline__ void swap_q(uint32_t (&q)[8], uint32_t a) {
    asm volatile("{\n.reg .pred p;\nsetp.ne.u32 p, %8, 0;\n"
                 "@p st.shared.v4.b32 [%8 + -8192], {%0, %1, %2, %3};\n@p st.shared.v4.b32 [%8 + -4096], {%4, %5, %6, %7};\n"
                 "@p ld.shared.v4.b32 {%0, %1, %2, %3}, [%8];\n@p ld.shared.v4.b32 {%4, %5, %6, %7}, [%8 + 4096];\n}"
                 : "+r"(q[0]), "+r"(q[1]), "+r"(q[2]), "+r"(q[3]), "+r"(q[4]), "+r"(q[5]), "+r"(q[6]), "+r"(q[7]) : "r"(a) : "memory");
}
static_assert(A_QX == A_KP + 8192, "parking places");
template <bool INIT>
__device__ __forceinline__ void issue_pv(uint32_t (&o)[10], const uint32_t (&P)[32], uint64_t dv) {
    if (INIT) wg_pv_init(o, P[0], P[1], P[2], P[3], dv); else wg_pv_acc(o, P[0], P[1], P[2], P[3], dv);
    #pragma unroll
    for (int k = 1; k < 8; k++) wg_pv_acc(o, P[4*k], P[4*k+1], P[4*k+2], P[4*k+3], dv + k * 16);
}

__device__ __forceinline__ uint4 quad_transpose(uint32_t x0, uint32_t x1, uint32_t x2, uint32_t x3, int t) {
    const bool b0 = t & 1, b1 = t & 2;
    uint32_t s0 = b0 ? x0 : x1, s1 = b0 ? x2 : x3;
    s0 = __shfl_xor_sync(0xffffffffu, s0, 1); s1 = __shfl_xor_sync(0xffffffffu, s1, 1);
    const uint32_t y0 = b0 ? s0 : x0, y1 = b0 ? x1 : s0, y2 = b0 ? s1 : x2, y3 = b0 ? x3 : s1;
    uint32_t u0 = b1 ? y0 : y2, u1 = b1 ? y1 : y3;
    u0 = __shfl_xor_sync(0xffffffffu, u0, 2); u1 = __shfl_xor_sync(0xffffffffu, u1, 2);
    return b1 ? make_uint4(u0, u1, y2, y3) : make_uint4(y0, y1, u0, u1);
}
__device__ __forceinline__ uint32_t movm(uint32_t v) { uint32_t r; asm volatile("movmatrix.sync.aligned.m8n8.trans.b16 %0, %1;" : "=r"(r) : "r"(v)); return r; }
__device__ __forceinline__ void attn_repair(const uint4 qx, const uint4 qy, uint32_t lb, int pass, int unit) {
    const int tid = tid_now(), g = (tid & 31) >> 2, t = tid & 3;
    float ss = ldsf(M_SS + pass * 4);
    if (ss == 0.f) ss = 1.f;
    const uint4 q0 = quad_transpose(qx.x, qx.z, qy.x, qy.z, t), q1 = quad_transpose(qx.y, qx.w, qy.y, qy.w, t);
    const char* kv = g_kv + (size_t)(nt_of(cta_now()) * 2 + pass) * 16 * KV_TILE + t * 2048 + g * 16;
    float o[4][4], m0 = -INFINITY, m1 = -INFINITY, l0 = 0.f, l1 = 0.f;
    #pragma unroll
    for (int j = 0; j < 4; j++) { o[j][0] = 0.f; o[j][1] = 0.f; o[j][2] = 0.f; o[j][3] = 0.f; }
    uint4 kf[8];
    #pragma unroll
    for (int i = 0; i < 8; i++) kf[i] = __ldcg(reinterpret_cast<const uint4*>(kv + 15 * KV_TILE + i * 128));
    #pragma unroll 1
    for (int b = 0; b < 32; b++) {
        uint4 vf[8];
        #pragma unroll
        for (int i = 0; i < 8; i++) vf[i] = __ldcg(reinterpret_cast<const uint4*>(kv + (b >> 1) * KV_TILE + (b & 1) * 1024 + 8192 + i * 128));
        float s[8][4];
        #pragma unroll
        for (int i = 0; i < 8; i++) {
            s[i][0] = 0.f; s[i][1] = 0.f; s[i][2] = 0.f; s[i][3] = 0.f;
            mma_f16(s[i], q0.x, q1.x, q0.y, q1.y, kf[i].x, kf[i].y); mma_f16(s[i], q0.z, q1.z, q0.w, q1.w, kf[i].z, kf[i].w);
        }
        #pragma unroll
        for (int i = 0; i < 8; i++) kf[i] = __ldcg(reinterpret_cast<const uint4*>(kv + (((b - 1) >> 1) & 15) * KV_TILE + (~b & 1) * 1024 + i * 128));
        float t0 = m0, t1 = m1;
        #pragma unroll
        for (int i = 0; i < 8; i++) { t0 = fmaxf(t0, fmaxf(s[i][0], s[i][1])); t1 = fmaxf(t1, fmaxf(s[i][2], s[i][3])); }
        t0 = quad_max(t0); t1 = quad_max(t1);
        const float a0 = ex2((m0 - t0) * ss), a1 = ex2((m1 - t1) * ss);
        m0 = t0; m1 = t1;
        l0 *= a0; l1 *= a1;
        #pragma unroll
        for (int j = 0; j < 4; j++) { o[j][0] *= a0; o[j][1] *= a0; o[j][2] *= a1; o[j][3] *= a1; }
        #pragma unroll
        for (int k = 0; k < 4; k++) {
            uint32_t pf[4];
            #pragma unroll
            for (int e = 0; e < 2; e++) {
                const float p0 = ex2((s[2*k+e][0] - m0) * ss), p1 = ex2((s[2*k+e][1] - m0) * ss), p2 = ex2((s[2*k+e][2] - m1) * ss), p3 = ex2((s[2*k+e][3] - m1) * ss);
                l0 += p0 + p1; l1 += p2 + p3;
                pf[2*e] = pack_f16(p0, p1); pf[2*e+1] = pack_f16(p2, p3);
            }
            mma_f16(o[0], pf[0], pf[1], pf[2], pf[3], movm(vf[2*k].x), movm(vf[2*k+1].x));
            mma_f16(o[1], pf[0], pf[1], pf[2], pf[3], movm(vf[2*k].y), movm(vf[2*k+1].y));
            mma_f16(o[2], pf[0], pf[1], pf[2], pf[3], movm(vf[2*k].z), movm(vf[2*k+1].z));
            mma_f16(o[3], pf[0], pf[1], pf[2], pf[3], movm(vf[2*k].w), movm(vf[2*k+1].w));
        }
    }
    const float iv = 16.f * ldsf(M_IV + pass * 4), i0 = iv * rcp(quad_sum(l0)), i1 = iv * rcp(quad_sum(l1));
    uint32_t* dst = reinterpret_cast<uint32_t*>(reinterpret_cast<char*>(g_o) + (o_offset() & ~48u) + (unit * 64 * D_ + pass * 512) * 2) + t;
    #pragma unroll
    for (int j = 0; j < 4; j++) {
        dst[j * 4] = pack_bf16(o[j][0] * i0, o[j][1] * i0);
        dst[j * 4 + 4 * D_] = pack_bf16(o[j][2] * i1, o[j][3] * i1);
    }
    __syncwarp();
    mbar_arrive_elect(lb + B_OD + (pass * 2 + (tid >> 7)) * 8);
}

__device__ __forceinline__ void load_gu(uint32_t (&f)[64], uint32_t src, int warp, int lane) {
    const uint32_t row = (warp & 3) * 64 + (lane >> 4) * 8 + (lane & 7), ch = (lane >> 3) & 1, sw = (lane >> 1) & 3;
    const uint32_t a0 = base32(src + (warp >> 2) * 32768 + row * 64 + ((ch ^ sw) << 4)), a1 = base32(a0 ^ 32);
    #pragma unroll
    for (int i = 0; i < 16; i++) ldsm4t(f[4*i], f[4*i+1], f[4*i+2], f[4*i+3], ((i & 1) ? a1 : a0) + ((i >> 1) & 1) * 16384 + (i >> 2) * 1024);
}

__device__ __forceinline__ void arrive_loaded(uint32_t bar, const uint32_t (&f)[64], uint32_t zero) {
    uint32_t x = 0;
    #pragma unroll
    for (int i = 0; i < 16; i++) x |= f[4 * i];
    mbar_arrive_elect(bar + (x & zero));
}
__device__ __forceinline__ void flush(uint32_t (&o2)[10], const uint32_t (&o)[10]) {
    #pragma unroll
    for (int i = 0; i < 10; i++) o2[i] = hadd2(o2[i], o[i]);
}
__device__ __forceinline__ void attention_phase(int L, uint32_t lb, int wg, uint32_t (&qa)[8], uint32_t (&qb)[8], uint32_t (&SA)[32], uint32_t (&SB_)[32], uint64_t dk0, uint64_t dv0, uint32_t ca, uint32_t (&wa)[64], uint32_t zero, uint32_t sixteen) {
    uint32_t PA[32], PB[32], oa[10], ob[10], oa2[10], ob2[10];
    Shift ha, hb;
    uint32_t fail = (lds32(M_SS) ? 3u : 0u) | (lds32(M_SS + 4) ? 12u : 0u);
    ca += base32(fail) >> 4;
    const uint32_t oo = o_offset(), odb = lb + B_OD + wg * 8;
    constexpr uint64_t SL = R_SLOT >> 4, KH = 4096 >> 4;
    uint64_t dkd = dk0 + ((A_KP - A_RING) >> 4);
    unit_start(SA, ha, oa2);
    exp_tile(SA, PA, ha, ca, sixteen);
    #pragma unroll
    for (int i = 0; i < 10; i++) { ob[i] = 0u; ob2[i] = 0u; }
    hb = ha;
    mbar_spin(lb + B_KS, 0);
    mbar_spin(lb + B_ONE, 0);
    #pragma unroll 1
    for (int it = 0; ; it++) {
        const uint32_t ph = it & 1;
        uint32_t qsw = 0;
        #pragma unroll
        for (int u = 0; u < 4; u++) {
            const uint64_t dk = opaque(dk0) + u * SL, dv = opaque(dv0) + u * SL;
            wg_fence();
            if (u == 0) { wg_qk_acc(SB_, qb[4], qb[5], qb[6], qb[7], dkd + KH); wg_commit(); }
            if (u == 0) issue_pv<true>(oa, PA, dv); else issue_pv<false>(oa, PA, dv);
            wg_qk_init(SA, qa[0], qa[1], qa[2], qa[3], dk);
            wg_qk_acc(SA, qa[4], qa[5], qa[6], qa[7], dk + KH);
            wg_commit();
            wg_wait<1>();
            pin(SB_); pin(ob);
            if (u == 0) {
                mbar_arrive_elect_p(lb + B_AE + 24, it);
                flush(ob2, ob);
                if (__builtin_expect((it & 3) == 0, 0)) {
                    if (it) unit_end<0, 1>(ob2, hb.bad, odb, oo, fail, ldsf(M_IV));
                    unit_start(SB_, hb, ob2);
                }
            } else mbar_arrive_elect(lb + B_AE + 8 * (u - 1));
            if (u == 3) swap_q(qb, qsw ? qsw + 8192 : 0u);
            exp_tile(SB_, PB, hb, ca, sixteen);
            wg_fence();
            if (u == 0) issue_pv<true>(ob, PB, dv); else issue_pv<false>(ob, PB, dv);
            wg_qk_init(SB_, qb[0], qb[1], qb[2], qb[3], dk);
            if (u < 3) wg_qk_acc(SB_, qb[4], qb[5], qb[6], qb[7], dk + KH);
            wg_commit();
            wg_wait<1>();
            pin(SA); pin(oa);
            if (u == 2) { qsw = it == 3 ? A_QX + tid_now() * 16 : 0u; swap_q(qa, qsw); }
            if (u == 3) {
                flush(oa2, oa);
                if (__builtin_expect((it & 3) == 3, 0)) {
                    TL(0, L * 32 + 7 + (it >> 2)); CK(0, L * 32 + 1 + (it >> 2));
                    if (it == 7) goto done;
                    unit_end<0, 0>(oa2, ha.bad, odb, oo, fail, ldsf(M_IV));
                    unit_start(SA, ha, oa2);
                }
            }
            exp_tile(SA, PA, ha, ca, sixteen);
            mbar_spin(lb + B_AF + 8 * ((u + 1) & 3), u < 3 ? ph : ph ^ 1);
        }
        wg_wait<0>();
        dkd = dk0 + 3 * SL;
    }
done:
    const float iv = ldsf(M_IV + 4);
    mbar_spin(lb + B_GU, 0);
    load_gu(wa, F_GU0, tid_now() >> 5, tid_now() & 31);
    unit_end<1, 0>(oa2, ha.bad, odb, oo, fail, iv);
    wg_wait<0>();
    pin(ob);
    mbar_arrive_elect(lb + B_AE + 24);
    flush(ob2, ob);
    unit_end<1, 1>(ob2, hb.bad, odb, oo, fail, iv);
    arrive_loaded(lb + B_FG, wa, zero);
    if (__builtin_expect(fail != 0, 0)) {
        uint4* const qs = &g_qsave[cta_now()][0][tid_now()];
        qs[4 * 256] = make_uint4(qa[0], qa[1], qa[2], qa[3]); qs[5 * 256] = make_uint4(qa[4], qa[5], qa[6], qa[7]);
        qs[6 * 256] = make_uint4(qb[0], qb[1], qb[2], qb[3]); qs[7 * 256] = make_uint4(qb[4], qb[5], qb[6], qb[7]);
        #pragma unroll
        for (int i = 0; i < 16; i++) qs[(8 + i) * 256] = make_uint4(wa[4*i], wa[4*i+1], wa[4*i+2], wa[4*i+3]);
        #pragma unroll 1
        for (int r = 0; r < 4; r++)
            if ((fail >> r) & 1) attn_repair(__ldcg(qs + r * 512), __ldcg(qs + r * 512 + 256), lb, r >> 1, r & 1);
        #pragma unroll
        for (int i = 0; i < 16; i++) { const uint4 v = __ldcg(qs + (8 + i) * 256); wa[4*i] = v.x; wa[4*i+1] = v.y; wa[4*i+2] = v.z; wa[4*i+3] = v.w; }
    }
    TL(0, L * 32 + 9); CK(0, L * 32 + 8);
}

__device__ __forceinline__ void oproj_steps(float (&acc)[64], uint32_t lb, int wg, int k0, int k1) {
    const bool leader = (tid_now() & 127) == 0;
    #pragma unroll 1
    for (int k = k0; k < k1; k++) {
        const uint32_t st = k & 3;
        mbar_spin(lb + B_OF + 8 * st, (k >> 2) & 1);
        const uint64_t da = desc_sw128(o_a(st) + wg * 8192, 16, 1024);
        const uint64_t db = desc_sw128(o_b(st), 8192, 1024);
        wg_fence();
        #pragma unroll
        for (int kk = 0; kk < 4; kk++) wg_gemm_n128(acc, da + kk * 2, db + kk * 128);
        wg_commit();
        wg_wait<1>();
        if (leader && k > 0) mbar_arrive(lb + B_OE + 8 * ((k - 1) & 3));
    }
}

__device__ __forceinline__ uint4 best_of(const uint4& e, int sh, int mask) {
    const uint32_t m = redux_max(e.x), row = redux_min(e.x == m ? e.w : 0x7FFFFFFFu), src = (row >> sh) & mask;
    return make_uint4(m, __shfl_sync(0xffffffffu, e.y, src), __shfl_sync(0xffffffffu, e.z, src), row);
}
__device__ __forceinline__ void load_wd(uint32_t (&wd)[64], uint32_t lb, int warp, int lane) {
    mbar_spin(lb + B_WD, 0);
    const uint32_t a0 = F_WD + warp * 8192 + ((lane >> 4) * 8 + (lane & 7)) * 128, ch = ((lane >> 3) & 1) ^ (lane & 7);
    #pragma unroll
    for (int i = 0; i < 16; i++) ldsm4t(wd[4*i], wd[4*i+1], wd[4*i+2], wd[4*i+3], base32(a0 + ((ch ^ (i & 6)) << 4)) + (i >> 3) * 4096 + (i & 1) * 2048);
}
__device__ __forceinline__ void stage_tile(const uint32_t (&xa)[4], const uint32_t (&xv)[32]) {
    #pragma unroll
    for (int m = 0; m < 8; m++) stsm4(xa[m & 3] + (m < 4 ? YT0 - XT0 : YT1 - XT0), xv[4*m], xv[4*m+1], xv[4*m+2], xv[4*m+3]);
    fence_async_smem();
    __syncwarp();
}

__device__ __forceinline__ void tail_phase(int L, uint32_t lb, int wg, const uint32_t (&wa)[64]) {
    const int c = cta_now(), blk = blk_of(c), cb = cb_of(c), tid = tid_now();
    const int lane = tid & 31, w = (tid >> 5) & 3, g = lane >> 2, t = lane & 3;
    const int lr0 = wg * 64 + w * 16 + g;
    uint32_t xa[4];
    #pragma unroll
    for (int m = 0; m < 4; m++) xa[m] = base32(XT0 + (wg * 64 + w * 16 + (lane & 15)) * 128 + (((lane >> 4) ^ (lane & 7) ^ (2 * m)) << 4));
    uint32_t xv[32];
    const bool ffn = c < NFC;
    uint32_t wb[64], wd[64];
    float own[6];
    {
        float acc[64];
        #pragma unroll
        for (int i = 0; i < 64; i++) acc[i] = 0.f;
        pin(acc);
        float2 rs0 = make_float2(0.f, 0.f), rs1 = rs0;
        if (L) { rs0 = __ldcg(&g_x.rs1[blk * 128 + lr0]); rs1 = __ldcg(&g_x.rs1[blk * 128 + lr0 + 8]); }
        oproj_steps(acc, lb, wg, 0, 8);
        mbar_spin(lb + B_RES, 0);
        #pragma unroll
        for (int m = 0; m < 8; m++) ldsm4(xv[4*m], xv[4*m+1], xv[4*m+2], xv[4*m+3], xa[m & 3] + (m < 4 ? 0 : XT1 - XT0));
        if (L) {
            const int d = (int)lds32(M_RT + 12) - (blk * 128 + lr0);
            const Ln2 k0 = ln2_coef(rs0.y, d == 0 ? 0.f : rsq(rs0.x + LN_EPS)), k1 = ln2_coef(rs1.y, d == 8 ? 0.f : rsq(rs1.x + LN_EPS));
            #pragma unroll
            for (int j = 0; j < 16; j++) { xv[2*j] = add_ln2(xv[2*j], k0); xv[2*j+1] = add_ln2(xv[2*j+1], k1); }
        }
        pin(xv);
        oproj_steps(acc, lb, wg, 8, 16);
        uint32_t wv[16];
        #pragma unroll
        for (int i = 0; i < 4; i++) ldsm4(wv[4*i], wv[4*i+1], wv[4*i+2], wv[4*i+3], (lane & 1) ? M_RED + (lane >> 3) * 16 + i * 64 : M_RED + 256);
        wg_wait<0>();
        pin(acc);
        if ((tid & 127) == 0) mbar_arrive(lb + B_OE + 24);
        TL(0, L * 32 + 11); CK(0, L * 32 + 13);
        float sa[4] = {0.f, 0.f, 0.f, 0.f}, sb[4] = {0.f, 0.f, 0.f, 0.f}, sc[4] = {0.f, 0.f, 0.f, 0.f};
        float sd[4] = {0.f, 0.f, 0.f, 0.f}, se[4] = {0.f, 0.f, 0.f, 0.f};
        #pragma unroll
        for (int m = 0; m < 8; m++) {
            #pragma unroll
            for (int i = 0; i < 4; i++) xv[4*m+i] = badd2(xv[4*m+i], pack_bf16(acc[8*m + 2*i], acc[8*m + 2*i + 1]));
            mma_bf16(sa, xv[4*m], xv[4*m+1], xv[4*m+2], xv[4*m+3], wv[2*m], wv[2*m+1]);
            mma_bf16_k8(sb, xv[4*m], xv[4*m+1], xv[4*m]); mma_bf16_k8(sc, xv[4*m], xv[4*m+1], xv[4*m+1]);
            mma_bf16_k8(sd, xv[4*m+2], xv[4*m+3], xv[4*m+2]); mma_bf16_k8(se, xv[4*m+2], xv[4*m+3], xv[4*m+3]);
        }
        const float q0 = (g & 1) ? sb[1] + sd[1] : sb[0] + sd[0], q1 = (g & 1) ? sc[3] + se[3] : sc[2] + se[2];
        if (t == (g >> 1)) {
            st_x128(&g_x.part[L][blk][cb][lr0], __float_as_uint(sa[0]), __float_as_uint(q0), __float_as_uint(sa[1]), 0u);
            st_x128(&g_x.part[L][blk][cb][lr0 + 8], __float_as_uint(sa[2]), __float_as_uint(q1), __float_as_uint(sa[3]), 0u);
        }
        __syncwarp();
        own[0] = sa[0]; own[1] = __shfl_sync(0xffffffffu, q0, (lane & 28) + (g >> 1)); own[2] = sa[1];
        own[3] = sa[2]; own[4] = __shfl_sync(0xffffffffu, q1, (lane & 28) + (g >> 1)); own[5] = sa[3];
    }
    TL(0, L * 32 + 12);
    load_gu(wb, F_GU1, tid >> 5, lane);
    stage_tile(xa, xv);
    float mean[2], rstd[2], score[2];
    {
        const bool o0 = cb == 2 * t, o1 = cb == 2 * t + 1;
        const uint4* const psrc = &g_x.part[L][blk][2 * t][lr0];
        uint4 p[4];
        uint32_t n = 0;
        #pragma unroll 1
        do {
            p[0] = ld_x128(psrc); p[1] = ld_x128(psrc + 128); p[2] = ld_x128(psrc + 8); p[3] = ld_x128(psrc + 136);
            poll_tick(n);
        } while (warp_any((!o0 && (p[0].w | p[2].w) != 0) || (!o1 && (p[1].w | p[3].w) != 0)));
        mbar_arrive_elect_p(lb + B_XS, L == 0);
        const float ws = ldsf(M_WS);
        #pragma unroll
        for (int h = 0; h < 2; h++) {
            const float su = quad_sum((o0 ? own[3*h] : __uint_as_float(p[2*h].x)) + (o1 ? own[3*h] : __uint_as_float(p[2*h+1].x)));
            const float sq = quad_sum((o0 ? own[3*h+1] : __uint_as_float(p[2*h].y)) + (o1 ? own[3*h+1] : __uint_as_float(p[2*h+1].y)));
            const float sd = quad_sum((o0 ? own[3*h+2] : __uint_as_float(p[2*h].z)) + (o1 ? own[3*h+2] : __uint_as_float(p[2*h+1].z)));
            mean[h] = su * (1.f / D_);
            const float var = fmaxf(sq * (1.f / D_) - mean[h] * mean[h], 0.f);
            rstd[h] = rsq(var + LN_EPS);
            score[h] = rstd[h] * (sd - mean[h] * ws);
            if (L && t == h) { const Ln2 k = ln2_coef(mean[h], rstd[h]); sts128(XT0 + (lr0 + 8 * h) * 16, k.nm, k.rh, k.rl, k.c); }
            if (L == 0 && cb == 0 && t == h) st_x64(&g_x.rs1[blk * 128 + lr0 + 8 * h], __float_as_uint(var), __float_as_uint(mean[h]));
        }
    }
    TL(0, L * 32 + 13);
    uint4 f;
    {
        const uint32_t k0 = order_bits(score[0]), k1 = order_bits(score[1]);
        const bool up = k1 > k0;
        const uint32_t kb = max(k0, k1), row = blk * 128 + lr0 + (up ? 8 : 0), m = redux_max(kb);
        if (redux_min(kb == m ? row : 0x7FFFFFFFu) == row && t == 0) sts128(M_SR + (tid >> 5) * 16, kb, __float_as_uint(up ? mean[1] : mean[0]), __float_as_uint(up ? rstd[1] : rstd[0]), row);
        named_sync(NB_CONS, 256);
        f = best_of(lds128(M_SR + (lane & 7) * 16), 4, 7);
        if (tid < 16) st_x128(&g_x.hdr[L][tid * 8 + cb][blk], f.x, f.y, f.z, f.w);
        const int d = (int)f.w - (blk * 128 + lr0);
        if ((d & ~8) == 0) {
            #pragma unroll
            for (int b = 0; b < 4; b++)
                st_x128(&g_x.cand[L][blk][cb * 64 + b * 16 + t * 4], d ? xv[8*b+1] : xv[8*b], d ? xv[8*b+3] : xv[8*b+2], d ? xv[8*b+5] : xv[8*b+4], d ? xv[8*b+7] : xv[8*b+6]);
        }
        __syncwarp();
    }
    TL(0, L * 32 + 28);
    if (tid == 0) sts32(M_CR, f.w);
    __syncwarp();
    mbar_arrive_elect_p(lb + B_XS, L);
    load_wd(wd, lb, tid >> 5, lane);
    TL(0, L * 32 + 25);
    uint4 e;
    {
        uint32_t n = 0;
        #pragma unroll 1
        do { e = ld_x128(&g_x.hdr[L][blk * 8 + cb][lane & 15]); poll_tick(n); } while (warp_any(e.w == EMPTY && (lane & 15) != blk));
        if ((lane & 15) == blk) e = f;
        e = best_of(e, 7, 15);
    }
    TL(0, L * 32 + 14);
    if (tid == 0) sts128(M_RT + 16 * L, (e.x & 0x80000000u) ? e.x ^ 0x80000000u : ~e.x, e.y, e.z, e.w);
    if (tid == 0) mbar_arrive(lb + B_RT);
    if (ffn) {
        const uint32_t* src = &g_x.cand[L][e.w >> 7][(tid >> 5) * 32 + t * 4];
        const Ln2 kx = ln2_coef(__uint_as_float(e.y), __uint_as_float(e.z));
        uint4 x[4];
        uint32_t n = 0;
        #pragma unroll 1
        do {
            x[0] = ld_x128(src); x[1] = ld_x128(src + 16); x[2] = ld_x128(src + 256); x[3] = ld_x128(src + 272);
            poll_tick(n);
        } while (warp_any(x[0].x == EMPTY || x[1].x == EMPTY || x[2].x == EMPTY || x[3].x == EMPTY));
        TL(0, L * 32 + 15);
        float d[4][4];
        #pragma unroll
        for (int i = 0; i < 4; i++) { d[i][0] = 0.f; d[i][1] = 0.f; d[i][2] = 0.f; d[i][3] = 0.f; }
        #pragma unroll
        for (int k = 0; k < 8; k++) {
            const uint32_t b0 = ln2((k & 1) ? x[k >> 1].z : x[k >> 1].x, kx), b1 = ln2((k & 1) ? x[k >> 1].w : x[k >> 1].y, kx);
            const uint32_t* f = (k < 4 ? wa : wb) + (k & 3) * 16;
            #pragma unroll
            for (int i = 0; i < 4; i++) mma_bf16(d[i], f[4*i], f[4*i+1], f[4*i+2], f[4*i+3], b0, b1);
        }
        #pragma unroll
        for (int h = 0; h < 2; h++) {
            const float a = (t & 1) ? d[1][2*h] : d[0][2*h], b = (t & 1) ? d[3][2*h] : d[2][2*h];
            stsf(M_RED + ((tid >> 5) * 64 + t * 16 + h * 8 + g) * 4, (t & 2) ? b : a);
        }
        named_sync(NB_CONS, 256);
        TL(0, L * 32 + 16);
        float s0 = 0.f, s1 = 0.f;
        #pragma unroll
        for (int i = 0; i < 8; i++) { const float2 v = lds64f(base32(M_RED + lane * 8) + i * 256); s0 += v.x; s1 += v.y; }
        const uint32_t mine = pack_bf16(s0, s1), other = __shfl_xor_sync(0xffffffffu, mine, 16);
        const uint32_t gv = lane < 16 ? mine : other, uv = lane < 16 ? other : mine;
        const float g0 = bf_lo(gv), g1 = bf_hi(gv);
        const uint32_t hv = bmul2(pack_bf16(g0 * rcp(1.f + __expf(-g0)), g1 * rcp(1.f + __expf(-g1))), uv);
        uint32_t hb[4];
        #pragma unroll
        for (int i = 0; i < 4; i++) hb[i] = __shfl_sync(0xffffffffu, hv, 4 * i + t);
        float y[8][4];
        #pragma unroll
        for (int i = 0; i < 8; i++) {
            y[i][0] = 0.f; y[i][1] = 0.f; y[i][2] = 0.f; y[i][3] = 0.f;
            mma_bf16(y[i], wd[8*i], wd[8*i+1], wd[8*i+2], wd[8*i+3], hb[0], hb[1]);
            mma_bf16(y[i], wd[8*i+4], wd[8*i+5], wd[8*i+6], wd[8*i+7], hb[2], hb[3]);
        }
        float* dst = &g_x.ypart[L][(tid >> 5) * 16 + t * 4][c][g];
        #pragma unroll
        for (int i = 0; i < 2; i++)
            #pragma unroll
            for (int h = 0; h < 2; h++) {
                const float a = (t & 1) ? y[2 + i][2*h] : y[i][2*h], b = (t & 1) ? y[6 + i][2*h] : y[4 + i][2*h];
                st_x32(dst + (i * 2 + h) * (NFC * 8), __float_as_uint((t & 2) ? b : a));
            }
    }
    __syncwarp();
    mbar_arrive_elect(lb + B_FD);
    TL(0, L * 32 + 17);
}

__device__ __forceinline__ void qkv_load_w(const Maps& mp, uint32_t dst, int k, uint32_t fb) { tma_load3(dst, &mp.wqkv, nt_of(blockIdx.x) * 64, k * 64, 0, fb); }
__device__ __forceinline__ void qkv_load_x(const CUtensorMap* tx, uint32_t sa, int k, uint32_t fb) {
    #pragma unroll
    for (int a = 0; a < 2; a++) tma_load(sa + a * 16384, tx, k * 64, mt_of(blockIdx.x) * 256 + a * 128, fb);
}
__device__ __forceinline__ void producer_role(const Maps& mp) {
    const int c = blockIdx.x, mt = mt_of(c), nt = nt_of(c), blk = blk_of(c), cb = cb_of(c);
    const uint64_t pol = policy_evict_first();
    #pragma unroll 1
    for (int L = 0; L < 2; L++) {
        const uint32_t lb = M_BAR + L * BAR_SET;
        const CUtensorMap* tx = &mp.x[L];
        mbar_expect_tx(lb + B_SW, 49152);
        if (L == 0) {
            mbar_nap(lb + B_QF, 0);
            qkv_load_w(mp, SD_W, mt * 2, lb + B_SW);
            qkv_load_w(mp, SD_W + 24576, mt * 2 + 1, lb + B_SW);
        }
        {
            uint32_t st = 0, ph = L;
            #pragma unroll 1
            for (int k = L ? 0 : 3; k < 16; k++) {
                mbar_sleep(k < 2 ? M_BAR + (k ? B_FD : B_XS) : lb + B_QE + 8 * st, k < 2 ? 0 : ph);
                const uint32_t fb = lb + B_QF + 8 * st, sa = SB + st * Q_STB;
                mbar_expect_tx(fb, Q_STB);
                qkv_load_w(mp, sa + Q_ABYTES, k, fb);
                if (k == 0) {
                    mbar_nap(M_BAR + B_XD, 0);
                    flags16_wait(g_x.x[mt]);
                    fence_async_global();
                    mbar_nap(M_BAR + B_RT, 0);
                    TL(256, 32);
                }
                qkv_load_x(tx, sa, k, fb);
                if (L && k >= 3 && k < 7) tma_load(SD_W + (k - 3) * 12288, &mp.r, c * 24, (k - 3) * 256, lb + B_SW);
                if (++st == 3) { st = 0; ph ^= 1; }
            }
        }
        mbar_sleep(lb + B_QE, 1);
        TL(256, L * 32 + 26);
        mbar_arrive(lb + B_AF);
        {
            const char* kv = g_kv + (size_t)nt * 32 * KV_TILE;
            const uint8_t* fl = g_x.kv[L][nt * 2];
            __nanosleep(200);
            #pragma unroll 1
            for (int j = 1; j < 4; j++) {
                flag_wait(fl + ((2 * mt + j + 1) & 15));
                fence_async_global();
                const uint32_t bytes = j == 1 ? 8192 : 16384;
                mbar_expect_tx(lb + B_AF + 8 * j, bytes);
                bulk_load(A_RING + j * R_SLOT, kv + ((2 * mt + j) & 15) * KV_TILE, bytes, lb + B_AF + 8 * j);
                if (j == 1) TL(256, L * 32 + 21);
            }
            flags16_wait(fl);
            fence_async_global();
            int t0 = 2 * mt;
            #pragma unroll 1
            for (int it = 1; it < 8; it++) {
                #pragma unroll
                for (int u = 0; u < 4; u++) {
                    const char* src = kv + ((t0 + 4 * it + u) & 15) * KV_TILE;
                    const uint32_t fb = lb + B_AF + 8 * u, dst = A_RING + u * R_SLOT;
                    mbar_nap(lb + B_AE + 8 * u, (it - 1) & 1);
                    mbar_expect_tx(fb, 16384);
                    if (u < 3) bulk_load(dst, src, 16384, fb);
                    else {
                        bulk_load(dst + 8192, src + 8192, 8192, fb);
                        if (it == 3) {
                            flags16_wait(fl + 128);
                            fence_async_global();
                            kv += 16 * KV_TILE; src = kv + 15 * KV_TILE; t0 = 0;
                        }
                        bulk_load(dst, src, 8192, fb);
                    }
                }
            }
        }
        #pragma unroll 1
        for (int it = 0; it < 4; it++) {
            #pragma unroll
            for (int s = 0; s < 4; s++) {
                mbar_spin(lb + (it ? B_OE + 8 * s : s < 2 ? B_AE + 8 + 8 * s : B_FG), it ? (it - 1) & 1 : s < 2);
                const uint32_t fb = lb + B_OF + 8 * s;
                mbar_expect_tx(fb, 32768);
                #pragma unroll
                for (int b = 0; b < 2; b++)
                    tma_load5(o_b(s) + b * 8192, &mp.wo[it >> 1], cb * 128 + b * 64, (it & 1) * 8 + s * 2, fb);
                if (s == 0 && !(it & 1)) {
                    ctr_wait(g_x.o[L][blk][it >> 1], 15);
                    fence_async_global();
                    TL(256, L * 32 + 10);
                }
                tma_load(o_a(s), &mp.o, it * 256 + s * 64, blk * 128, fb);
            }
            if (it == 0) {
                mbar_spin(lb + B_AE + 24, 1);
                mbar_expect_tx(lb + B_RES, 32768);
                tma_load_s(XT0, tx, cb * 128, blk * 128, lb + B_RES, pol);
                tma_load_s(XT1, tx, cb * 128 + 64, blk * 128, lb + B_RES, pol);
            }
        }
        if (c < NFC) {
            #pragma unroll 1
            for (int i = 0; i < 4; i++) {
                mbar_spin(lb + B_OE + 16 + 8 * (i >> 1), 1);
                tma_load3_s(F_WD + i * 16384, &mp.d, 0, c * 32, i * 4, lb + B_WD, pol);
            }
        }
    }
}

__global__ void __launch_bounds__(384, 1) k_all(const __grid_constant__ Maps mp, const bf16* __restrict__ x0, const bf16* __restrict__ wo, const bf16* __restrict__ w_down,
                                                const bf16* __restrict__ w_r, bf16* __restrict__ out, const uint64_t dk0, const uint64_t dv0, const uint32_t ca, const uint32_t zero, const uint32_t sixteen) {
    extern __shared__ __align__(1024) char smem[];
    if (smem_u32(smem) != SB) __trap();
    const int warp = warp_uniform(threadIdx.x >> 5), wg = warp >> 2;
    TL(0, 0);
    if (warp == 8) {
      if (elect_one()) {
        tm_prefetch(&mp.x[0]); tm_prefetch(&mp.wqkv);
        #pragma unroll
        for (int s = 0; s < 3; s++) { mbar_init(M_BAR + B_QF + 8 * s, 1); mbar_init(M_BAR + BAR_SET + B_QF + 8 * s, 1); }
        fence_mbar_init();
        #pragma unroll 1
        for (int s = 0; s < 3; s++) {
            const uint32_t sa = SB + s * Q_STB, fb = M_BAR + B_QF + 8 * s;
            mbar_expect_tx(fb, Q_STB);
            qkv_load_x(&mp.x[0], sa, s, fb);
            qkv_load_w(mp, sa + Q_ABYTES, s, fb);
        }
      }
      __syncwarp();
    } else if (warp > 8) {
        if (elect_one()) {
            const uint32_t o0 = warp == 9 ? B_AF : warp == 10 ? B_QE : B_AE, o1 = warp == 9 ? B_QE : warp == 10 ? B_AE : B_END, cnt = warp == 9 ? 1 : warp == 10 ? 2 : 8;
            #pragma unroll 1
            for (uint32_t o = o0; o < o1; o += 8) { const uint32_t n = o == B_K0 ? 4 : cnt; mbar_init(M_BAR + o, n); mbar_init(M_BAR + BAR_SET + o, n); }
            fence_mbar_init();
        }
        __syncwarp();
    }
    __syncthreads();
    if (wg == 2) {
        reg_dec<40>();
        if (warp > 8) side_role(mp, x0, wo, w_down, w_r, out);
        else if (elect_one()) producer_role(mp);
    } else {
        reg_inc<232>();
        #pragma unroll 1
        for (int L = 0; L < 2; L++) {
            const uint32_t lb = M_BAR + L * BAR_SET;
            uint32_t qa[8], qb[8], sa[32], sb[32], wa[64];
            qkv_phase(L, lb, wg, qa, qb, sa, sb);
            attention_phase(L, lb, wg, qa, qb, sa, sb, dk0, dv0, ca, wa, zero, sixteen);
            tail_phase(L, lb, wg, wa);
        }
    }
}

typedef CUresult (*EncodeFn)(CUtensorMap*, CUtensorMapDataType, cuuint32_t, void*, const cuuint64_t*, const cuuint64_t*, const cuuint32_t*,
                             const cuuint32_t*, CUtensorMapInterleave, CUtensorMapSwizzle, CUtensorMapL2promotion, CUtensorMapFloatOOBfill);

void make_map(EncodeFn enc, CUtensorMap* tm, const void* ptr, int rank, const cuuint64_t* dims, const cuuint64_t* strides, const cuuint32_t* box, CUtensorMapSwizzle sw) {
    const cuuint32_t es[5] = {1, 1, 1, 1, 1};
    enc(tm, CU_TENSOR_MAP_DATA_TYPE_BFLOAT16, rank, const_cast<void*>(ptr), dims, strides, box, es, CU_TENSOR_MAP_INTERLEAVE_NONE, sw,
        box[0] == 64 ? CU_TENSOR_MAP_L2_PROMOTION_L2_128B : CU_TENSOR_MAP_L2_PROMOTION_NONE, CU_TENSOR_MAP_FLOAT_OOB_FILL_NONE);
}
void make_map2(EncodeFn enc, CUtensorMap* tm, const void* ptr, uint64_t cols, uint64_t rows, uint32_t bc, uint32_t br, CUtensorMapSwizzle sw) {
    const cuuint64_t dims[2] = {cols, rows}, strides[1] = {cols * 2};
    const cuuint32_t box[2] = {bc, br};
    make_map(enc, tm, ptr, 2, dims, strides, box, sw);
}

}

extern "C" void kernel_launch(void* const* d_in, const int* in_sizes, int n_in, void* d_out, int out_size) {
    const bf16* x0 = (const bf16*)d_in[0];
    const bf16* wqkv = (const bf16*)d_in[1];
    const bf16* wo = (const bf16*)d_in[2];
    const bf16* w_r = (const bf16*)d_in[4];
    const bf16* w_gate = (const bf16*)d_in[5];
    const bf16* w_up = (const bf16*)d_in[6];
    const bf16* w_down = (const bf16*)d_in[7];

    EncodeFn enc = nullptr;
    cudaDriverEntryPointQueryResult qr;
    cudaGetDriverEntryPoint("cuTensorMapEncodeTiled", (void**)&enc, cudaEnableDefault, &qr);
    void *p_o, *p_x1;
    cudaGetSymbolAddress(&p_o, g_o); cudaGetSymbolAddress(&p_x1, g_x1);
    const CUtensorMapSwizzle S128 = CU_TENSOR_MAP_SWIZZLE_128B, S64 = CU_TENSOR_MAP_SWIZZLE_64B, S0 = CU_TENSOR_MAP_SWIZZLE_NONE;
    Maps mp;
    make_map2(enc, &mp.x[0], x0, D_, S_, 64, 128, S128); make_map2(enc, &mp.x[1], p_x1, D_, S_, 64, 128, S128);
    make_map2(enc, &mp.o, p_o, D_, S_, 64, 128, S128);
    {
        const cuuint64_t dims[3] = {D_, D_, 3}, strides[2] = {3 * D_ * 2, D_ * 2};
        const cuuint32_t box[3] = {64, 64, 3};
        make_map(enc, &mp.wqkv, wqkv, 3, dims, strides, box, S128);
    }
    make_map2(enc, &mp.r, wqkv, 3 * D_, D_, 24, 256, S0);
    make_map2(enc, &mp.g, w_gate, FF, D_, 32, 256, S64); make_map2(enc, &mp.u, w_up, FF, D_, 32, 256, S64);
    for (int p = 0; p < 2; p++) {
        const cuuint64_t dims[5] = {D_, 2, 4, 4, 16}, strides[4] = {D_ * 2, 8 * D_ * 2, 2 * D_ * 2, 64 * D_ * 2};
        const cuuint32_t box[5] = {64, 2, 4, 4, 2};
        make_map(enc, &mp.wo[p], wo + (size_t)p * 32 * D_, 5, dims, strides, box, S128);
    }
    {
        const cuuint64_t dims[3] = {64, FF, 16}, strides[2] = {D_ * 2, 128};
        const cuuint32_t box[3] = {64, 32, 4};
        make_map(enc, &mp.d, w_down, 3, dims, strides, box, S128);
    }
    cudaFuncSetAttribute(k_all, cudaFuncAttributeMaxDynamicSharedMemorySize, K_SMEM);
    k_all<<<128, 384, K_SMEM, cudaStreamPerThread>>>(mp, x0, wo, w_down, w_r, (bf16*)d_out, desc_plain(A_RING, 2048, 128), desc_plain(A_RING + 8192, 128, 2048), 0x64A264A2u, 0u, 16u);
}
```

```cpp
#include <cuda_runtime.h>
#include <cuda_bf16.h>
#include <cuda_fp16.h>
#include <cuda.h>
#include <cudaTypedefs.h>
#include <stdint.h>

namespace {

typedef __nv_bfloat16 bf16;

constexpr int S_ = 2048, D_ = 1024, NH = 32, FF = 3584, NFC = FF / 32;
constexpr float LN_EPS = 1e-5f;
constexpr float QSCALE = 0.17677669529663687f * 1.4426950408889634f;
constexpr uint32_t EMPTY = 0xFFFFFFFFu;

constexpr int KV_TILE = 16384;
__device__ __align__(1024) char g_kv[NH * 16 * KV_TILE];
__device__ __align__(1024) bf16 g_o[S_ * D_];
__device__ __align__(1024) bf16 g_x1[S_ * D_];
__device__ __align__(16) float2 g_cs[8][3 * D_];
__device__ __align__(16) float2 g_rs0[S_];
__device__ uint4 g_qsave[128][29][256];
struct Xchg {
    uint4 part[2][16][8][128];
    float ypart[2][128][NFC][8];
    uint32_t cand[2][16][D_ / 2];
    uint4 hdr[2][128][16];
    float2 rs1[S_];
    float fix[3 * D_];
    uint32_t x2row[D_ / 2];
    uint8_t kv[2][NH][128];
    int o[2][16][2][32];
    uint8_t x[8][128];
};
constexpr int FILL = (sizeof(Xchg) / 128 + 127) / 128 * 8;
union XchgFill { Xchg x; uint4 fill[128][FILL]; };
static_assert(FILL > 768 && FILL <= 1024, "exchange area");
__device__ __align__(128) XchgFill g_u;
#define g_x g_u.x
__device__ int g_pctr;

constexpr uint32_t SMEM_BASE = 1024;

__device__ __forceinline__ int tid_now() { int v; asm volatile("mov.u32 %0, %%tid.x;" : "=r"(v)); return v; }
__device__ __forceinline__ int cta_now() { int v; asm volatile("mov.u32 %0, %%ctaid.x;" : "=r"(v)); return v; }
__device__ __forceinline__ uint64_t opaque(uint64_t v) { uint64_t r; asm volatile("mov.b64 %0, %1;" : "=l"(r) : "l"(v)); return r; }
__device__ __forceinline__ uint32_t base32(uint32_t v) { uint32_t r; asm("mov.b32 %0, %1;" : "=r"(r) : "r"(v)); return r; }
__device__ __forceinline__ uint32_t smem_u32(const void* p) { return (uint32_t)__cvta_generic_to_shared(p); }
__device__ __forceinline__ void mbar_init(uint32_t bar, int cnt) { asm volatile("mbarrier.init.shared::cta.b64 [%0], %1;" :: "r"(bar), "r"(cnt) : "memory"); }
__device__ __forceinline__ void mbar_expect_tx(uint32_t bar, uint32_t bytes) { asm volatile("mbarrier.arrive.expect_tx.shared::cta.b64 _, [%0], %1;" :: "r"(bar), "r"(bytes) : "memory"); }
__device__ __forceinline__ void mbar_arrive(uint32_t bar) { asm volatile("mbarrier.arrive.shared::cta.b64 _, [%0];" :: "r"(bar) : "memory"); }
__device__ __forceinline__ void mbar_sleep(uint32_t bar, uint32_t parity) {
    asm volatile("{\n.reg .pred p;\n.reg .u32 n;\nmov.u32 n, 0;\n"
                 "LAB_WAIT:\nmbarrier.try_wait.parity.shared::cta.b64 p, [%0], %1, 0x10000;\n@p bra LAB_DONE;\n"
                 "add.u32 n, n, 1;\nsetp.lt.u32 p, n, 0x10000;\n@p bra LAB_WAIT;\ntrap;\nLAB_DONE:\n}" :: "r"(bar), "r"(parity) : "memory");
}
__device__ __forceinline__ void mbar_nap(uint32_t bar, uint32_t parity) {
    asm volatile("{\n.reg .pred p;\nLAB_WAIT:\nmbarrier.try_wait.parity.shared::cta.b64 p, [%0], %1, 0x10000;\n@!p bra LAB_WAIT;\n}" :: "r"(bar), "r"(parity) : "memory");
}
__device__ __forceinline__ void mbar_spin(uint32_t bar, uint32_t parity) {
    asm volatile("{\n.reg .pred p;\nLAB_WAIT:\nmbarrier.try_wait.parity.shared::cta.b64 p, [%0], %1;\n@!p bra LAB_WAIT;\n}" :: "r"(bar), "r"(parity) : "memory");
}
__device__ __forceinline__ uint32_t mbar_test(uint32_t bar, uint32_t parity) {
    uint32_t ok;
    asm volatile("{\n.reg .pred p;\nmbarrier.test_wait.parity.shared::cta.b64 p, [%1], %2;\nselp.u32 %0, 1, 0, p;\n}" : "=r"(ok) : "r"(bar), "r"(parity) : "memory");
    return ok;
}
__device__ __forceinline__ bool elect_one() {
    uint32_t r;
    asm volatile("{\n.reg .pred p;\nelect.sync _|p, 0xffffffff;\nselp.u32 %0, 1, 0, p;\n}" : "=r"(r));
    return r != 0;
}
__device__ __forceinline__ void mbar_arrive_elect(uint32_t bar) {
    asm volatile("{\n.reg .pred p;\nelect.sync _|p, 0xffffffff;\n@p mbarrier.arrive.shared::cta.b64 _, [%0];\n}" :: "r"(bar) : "memory");
}
__device__ __forceinline__ void mbar_arrive_elect_p(uint32_t bar, uint32_t on) {
    asm volatile("{\n.reg .pred p, q;\nelect.sync _|p, 0xffffffff;\nsetp.ne.and.u32 q, %1, 0, p;\n@q mbarrier.arrive.shared::cta.b64 _, [%0];\n}" :: "r"(bar), "r"(on) : "memory");
}
__device__ __forceinline__ int warp_uniform(int v) { return __shfl_sync(0xffffffffu, v, 0); }
__device__ __forceinline__ void fence_mbar_init() { asm volatile("fence.mbarrier_init.release.cluster;" ::: "memory"); }
__device__ __forceinline__ void fence_async_smem() { asm volatile("fence.proxy.async.shared::cta;" ::: "memory"); }
__device__ __forceinline__ void fence_async_global() { asm volatile("fence.proxy.async.global;" ::: "memory"); }
__device__ __forceinline__ void named_sync(int id, int n) { asm volatile("bar.sync %0, %1;" :: "r"(id), "r"(n) : "memory"); }
__device__ __forceinline__ void named_arrive(int id, int n) { asm volatile("bar.arrive %0, %1;" :: "r"(id), "r"(n) : "memory"); }
__device__ __forceinline__ void bulk_load(uint32_t dst, const void* src, uint32_t bytes, uint32_t bar) {
    asm volatile("cp.async.bulk.shared::cluster.global.mbarrier::complete_tx::bytes [%0], [%1], %2, [%3];" :: "r"(dst), "l"(src), "r"(bytes), "r"(bar) : "memory");
}
__device__ __forceinline__ void bulk_store(void* dst, uint32_t src, uint32_t bytes) {
    asm volatile("cp.async.bulk.global.shared::cta.bulk_group [%0], [%1], %2;" :: "l"(dst), "r"(src), "r"(bytes) : "memory");
}
__device__ __forceinline__ void bulk_commit() { asm volatile("cp.async.bulk.commit_group;" ::: "memory"); }
__device__ __forceinline__ void bulk_wait() { asm volatile("cp.async.bulk.wait_group 0;" ::: "memory"); }
__device__ __forceinline__ void l2_prefetch(const void* src, uint32_t bytes) {
    asm volatile("cp.async.bulk.prefetch.L2.global [%0], %1;" :: "l"(src), "r"(bytes) : "memory");
}
__device__ __forceinline__ void tma_load(uint32_t dst, const CUtensorMap* tm, int c0, int c1, uint32_t bar) {
    asm volatile("cp.async.bulk.tensor.2d.shared::cluster.global.mbarrier::complete_tx::bytes [%0], [%1, {%3, %4}], [%2];"
                 :: "r"(dst), "l"(tm), "r"(bar), "r"(c0), "r"(c1) : "memory");
}
__device__ __forceinline__ void tma_load3(uint32_t dst, const CUtensorMap* tm, int c0, int c1, int c2, uint32_t bar) {
    asm volatile("cp.async.bulk.tensor.3d.shared::cluster.global.mbarrier::complete_tx::bytes [%0], [%1, {%3, %4, %5}], [%2];"
                 :: "r"(dst), "l"(tm), "r"(bar), "r"(c0), "r"(c1), "r"(c2) : "memory");
}
__device__ __forceinline__ void tma_load5(uint32_t dst, const CUtensorMap* tm, int c0, int c4, uint32_t bar) {
    asm volatile("cp.async.bulk.tensor.5d.shared::cluster.global.mbarrier::complete_tx::bytes [%0], [%1, {%3, %5, %5, %5, %4}], [%2];"
                 :: "r"(dst), "l"(tm), "r"(bar), "r"(c0), "r"(c4), "r"(0) : "memory");
}
__device__ __forceinline__ uint64_t policy_evict_first() { uint64_t p; asm volatile("createpolicy.fractional.L2::evict_first.b64 %0, 1.0;" : "=l"(p)); return p; }
__device__ __forceinline__ void tma_load_s(uint32_t dst, const CUtensorMap* tm, int c0, int c1, uint32_t bar, uint64_t pol) {
    asm volatile("cp.async.bulk.tensor.2d.shared::cluster.global.mbarrier::complete_tx::bytes.L2::cache_hint [%0], [%1, {%3, %4}], [%2], %5;"
                 :: "r"(dst), "l"(tm), "r"(bar), "r"(c0), "r"(c1), "l"(pol) : "memory");
}
__device__ __forceinline__ void tma_load3_s(uint32_t dst, const CUtensorMap* tm, int c0, int c1, int c2, uint32_t bar, uint64_t pol) {
    asm volatile("cp.async.bulk.tensor.3d.shared::cluster.global.mbarrier::complete_tx::bytes.L2::cache_hint [%0], [%1, {%3, %4, %5}], [%2], %6;"
                 :: "r"(dst), "l"(tm), "r"(bar), "r"(c0), "r"(c1), "r"(c2), "l"(pol) : "memory");
}
__device__ __forceinline__ void tma_store(const CUtensorMap* tm, uint32_t src, int c0, int c1) {
    asm volatile("cp.async.bulk.tensor.2d.global.shared::cta.bulk_group [%0, {%2, %3}], [%1];" :: "l"(tm), "r"(src), "r"(c0), "r"(c1) : "memory");
}
__device__ __forceinline__ void tma_prefetch(const CUtensorMap* tm, int c0, int c1) {
    asm volatile("cp.async.bulk.prefetch.tensor.2d.L2.global [%0, {%1, %2}];" :: "l"(tm), "r"(c0), "r"(c1) : "memory");
}
__device__ __forceinline__ void tm_prefetch(const CUtensorMap* tm) { asm volatile("prefetch.tensormap [%0];" :: "l"(tm) : "memory"); }
__device__ __forceinline__ void wg_fence() { asm volatile("wgmma.fence.sync.aligned;" ::: "memory"); }
__device__ __forceinline__ void wg_commit() { asm volatile("wgmma.commit_group.sync.aligned;" ::: "memory"); }
template <int N> __device__ __forceinline__ void wg_wait() { asm volatile("wgmma.wait_group.sync.aligned %0;" :: "n"(N) : "memory"); }
template <int N> __device__ __forceinline__ void pin(uint32_t (&r)[N]) {
    #pragma unroll
    for (int i = 0; i < N; i++) asm volatile("" : "+r"(r[i]) :: "memory");
}
template <int N> __device__ __forceinline__ void pin(float (&r)[N]) {
    #pragma unroll
    for (int i = 0; i < N; i++) asm volatile("" : "+f"(r[i]) :: "memory");
}
template <int N> __device__ __forceinline__ void reg_inc() { asm volatile("setmaxnreg.inc.sync.aligned.u32 %0;" :: "n"(N)); }
template <int N> __device__ __forceinline__ void reg_dec() { asm volatile("setmaxnreg.dec.sync.aligned.u32 %0;" :: "n"(N)); }
__host__ __device__ constexpr uint64_t desc_plain(uint32_t addr, uint32_t lbo, uint32_t sbo) {
    return (uint64_t)((addr & 0x3FFFF) >> 4) | ((uint64_t)(lbo >> 4) << 16) | ((uint64_t)(sbo >> 4) << 32);
}
__host__ __device__ constexpr uint64_t desc_sw128(uint32_t addr, uint32_t lbo, uint32_t sbo) { return desc_plain(addr, lbo, sbo) | (1ull << 62); }
__host__ __device__ constexpr uint64_t desc_sw64(uint32_t addr, uint32_t lbo, uint32_t sbo) { return desc_plain(addr, lbo, sbo) | (2ull << 62); }

__device__ __forceinline__ uint32_t lds32(uint32_t a) { uint32_t v; asm volatile("ld.shared.b32 %0, [%1];" : "=r"(v) : "r"(a) : "memory"); return v; }
__device__ __forceinline__ uint32_t lds16(uint32_t a) { uint32_t v; asm volatile("ld.shared.u16 %0, [%1];" : "=r"(v) : "r"(a) : "memory"); return v; }
__device__ __forceinline__ float ldsf(uint32_t a) { return __uint_as_float(lds32(a)); }
__device__ __forceinline__ float2 lds64f(uint32_t a) { float2 v; asm volatile("ld.shared.v2.f32 {%0, %1}, [%2];" : "=f"(v.x), "=f"(v.y) : "r"(a) : "memory"); return v; }
__device__ __forceinline__ uint4 lds128(uint32_t a) { uint4 v; asm volatile("ld.shared.v4.b32 {%0, %1, %2, %3}, [%4];" : "=r"(v.x), "=r"(v.y), "=r"(v.z), "=r"(v.w) : "r"(a) : "memory"); return v; }
__device__ __forceinline__ void sts16(uint32_t a, uint32_t v) { asm volatile("st.shared.b16 [%0], %1;" :: "r"(a), "h"((uint16_t)v) : "memory"); }
__device__ __forceinline__ void sts32(uint32_t a, uint32_t v) { asm volatile("st.shared.b32 [%0], %1;" :: "r"(a), "r"(v) : "memory"); }
__device__ __forceinline__ void stsf(uint32_t a, float v) { sts32(a, __float_as_uint(v)); }
__device__ __forceinline__ void sts64(uint32_t a, uint32_t x, uint32_t y) { asm volatile("st.shared.v2.b32 [%0], {%1, %2};" :: "r"(a), "r"(x), "r"(y) : "memory"); }
__device__ __forceinline__ void sts128(uint32_t a, uint32_t x, uint32_t y, uint32_t z, uint32_t w) { asm volatile("st.shared.v4.b32 [%0], {%1, %2, %3, %4};" :: "r"(a), "r"(x), "r"(y), "r"(z), "r"(w) : "memory"); }
__device__ __forceinline__ void stsm4(uint32_t a, uint32_t x, uint32_t y, uint32_t z, uint32_t w) {
    asm volatile("stmatrix.sync.aligned.m8n8.x4.shared.b16 [%0], {%1, %2, %3, %4};" :: "r"(a), "r"(x), "r"(y), "r"(z), "r"(w) : "memory");
}
__device__ __forceinline__ void ldsm4(uint32_t& a0, uint32_t& a1, uint32_t& a2, uint32_t& a3, uint32_t addr) {
    asm volatile("ldmatrix.sync.aligned.m8n8.x4.shared.b16 {%0,%1,%2,%3}, [%4];" : "=r"(a0), "=r"(a1), "=r"(a2), "=r"(a3) : "r"(addr) : "memory");
}
__device__ __forceinline__ void ldsm4t(uint32_t& a0, uint32_t& a1, uint32_t& a2, uint32_t& a3, uint32_t addr) {
    asm volatile("ldmatrix.sync.aligned.m8n8.x4.trans.shared.b16 {%0,%1,%2,%3}, [%4];" : "=r"(a0), "=r"(a1), "=r"(a2), "=r"(a3) : "r"(addr) : "memory");
}
__device__ __forceinline__ void mma_bf16(float (&d)[4], uint32_t a0, uint32_t a1, uint32_t a2, uint32_t a3, uint32_t b0, uint32_t b1) {
    asm("mma.sync.aligned.m16n8k16.row.col.f32.bf16.bf16.f32 {%0,%1,%2,%3}, {%4,%5,%6,%7}, {%8,%9}, {%0,%1,%2,%3};"
        : "+f"(d[0]), "+f"(d[1]), "+f"(d[2]), "+f"(d[3]) : "r"(a0), "r"(a1), "r"(a2), "r"(a3), "r"(b0), "r"(b1));
}
__device__ __forceinline__ void mma_bf16_k8(float (&d)[4], uint32_t a0, uint32_t a1, uint32_t b0) {
    asm("mma.sync.aligned.m16n8k8.row.col.f32.bf16.bf16.f32 {%0,%1,%2,%3}, {%4,%5}, {%6}, {%0,%1,%2,%3};"
        : "+f"(d[0]), "+f"(d[1]), "+f"(d[2]), "+f"(d[3]) : "r"(a0), "r"(a1), "r"(b0));
}
__device__ __forceinline__ void mma_f16(float (&d)[4], uint32_t a0, uint32_t a1, uint32_t a2, uint32_t a3, uint32_t b0, uint32_t b1) {
    asm("mma.sync.aligned.m16n8k16.row.col.f32.f16.f16.f32 {%0,%1,%2,%3}, {%4,%5,%6,%7}, {%8,%9}, {%0,%1,%2,%3};"
        : "+f"(d[0]), "+f"(d[1]), "+f"(d[2]), "+f"(d[3]) : "r"(a0), "r"(a1), "r"(a2), "r"(a3), "r"(b0), "r"(b1));
}
__device__ __forceinline__ void stg128_pred(void* p, const uint4& v, bool on) {
    asm volatile("{\n.reg .pred q;\nsetp.ne.u32 q, %5, 0;\n@q st.global.v4.b32 [%0], {%1, %2, %3, %4};\n}"
                 :: "l"(p), "r"(v.x), "r"(v.y), "r"(v.z), "r"(v.w), "r"((uint32_t)on) : "memory");
}
__device__ __forceinline__ void st_x32(void* p, uint32_t v) { asm volatile("st.relaxed.gpu.global.u32 [%0], %1;" :: "l"(p), "r"(v) : "memory"); }
__device__ __forceinline__ void st_x64(void* p, uint32_t x, uint32_t y) {
    asm volatile("{\n.reg .b64 v;\nmov.b64 v, {%1, %2};\nst.relaxed.gpu.global.b64 [%0], v;\n}" :: "l"(p), "r"(x), "r"(y) : "memory");
}
__device__ __forceinline__ void st_x128(void* p, uint32_t x, uint32_t y, uint32_t z, uint32_t w) {
    asm volatile("{\n.reg .b64 a, b;\n.reg .b128 v;\nmov.b64 a, {%1, %2};\nmov.b64 b, {%3, %4};\nmov.b128 v, {a, b};\nst.relaxed.gpu.global.b128 [%0], v;\n}"
                 :: "l"(p), "r"(x), "r"(y), "r"(z), "r"(w) : "memory");
}
__device__ __forceinline__ uint32_t ld_x32(const void* p) { uint32_t v; asm volatile("ld.relaxed.gpu.global.u32 %0, [%1];" : "=r"(v) : "l"(p) : "memory"); return v; }
__device__ __forceinline__ uint2 ld_x64(const void* p) {
    uint2 v; asm volatile("{\n.reg .b64 a;\nld.relaxed.gpu.global.b64 a, [%2];\nmov.b64 {%0, %1}, a;\n}" : "=r"(v.x), "=r"(v.y) : "l"(p) : "memory"); return v;
}
__device__ __forceinline__ uint4 ld_x128(const void* p) {
    uint4 v;
    asm volatile("{\n.reg .b64 a, b;\n.reg .b128 v;\nld.relaxed.gpu.global.b128 v, [%4];\nmov.b128 {a, b}, v;\nmov.b64 {%0, %1}, a;\nmov.b64 {%2, %3}, b;\n}"
                 : "=r"(v.x), "=r"(v.y), "=r"(v.z), "=r"(v.w) : "l"(p) : "memory");
    return v;
}
__device__ __forceinline__ void poll_tick(uint32_t& n) { asm volatile("{\n.reg .pred p;\nadd.u32 %0, %0, 1;\nsetp.ge.u32 p, %0, 0x800000;\n@p st.global.u32 [%1], %0;\n}" : "+r"(n) : "l"(0ull)); }
__device__ __forceinline__ void ctr_arrive(int* c) { asm volatile("red.release.gpu.global.add.s32 [%0], 1;" :: "l"(c) : "memory"); }
__device__ __forceinline__ void ctr_wait(const int* c, int target) {
    int v;
    uint32_t n = 0;
    #pragma unroll 1
    do {
        asm volatile("ld.acquire.gpu.global.s32 %0, [%1];" : "=r"(v) : "l"(c) : "memory");
        poll_tick(n);
    } while (v < target);
}
__device__ __forceinline__ void flag_wait(const uint8_t* f) {
    uint32_t n = 0, v;
    #pragma unroll 1
    do { asm volatile("ld.acquire.gpu.global.u8 %0, [%1];" : "=r"(v) : "l"(f) : "memory"); poll_tick(n); } while (v);
}
__device__ __forceinline__ void flags16_wait(const uint8_t* f) {
    uint32_t n = 0;
    uint64_t v;
    #pragma unroll 1
    do {
        asm volatile("{\n.reg .b64 a, b;\n.reg .b128 v;\nld.acquire.gpu.global.b128 v, [%1];\nmov.b128 {a, b}, v;\nor.b64 %0, a, b;\n}" : "=l"(v) : "l"(f) : "memory");
        poll_tick(n);
    } while (v != 0);
}
__device__ __forceinline__ bool any_empty(const uint4& v) { return v.x == EMPTY || v.y == EMPTY || v.z == EMPTY || v.w == EMPTY; }
__device__ __forceinline__ bool warp_any(bool p) { return __any_sync(0xffffffffu, p); }

__device__ __forceinline__ float ex2(float x) { float y; asm("ex2.approx.ftz.f32 %0, %1;" : "=f"(y) : "f"(x)); return y; }
__device__ __forceinline__ float rsq(float x) { float y; asm("rsqrt.approx.ftz.f32 %0, %1;" : "=f"(y) : "f"(x)); return y; }
__device__ __forceinline__ float rcp(float x) { float y; asm("rcp.approx.ftz.f32 %0, %1;" : "=f"(y) : "f"(x)); return y; }
__device__ __forceinline__ uint32_t pack_bf16(float lo, float hi) { uint32_t r; asm("cvt.rn.bf16x2.f32 %0, %1, %2;" : "=r"(r) : "f"(hi), "f"(lo)); return r; }
__device__ __forceinline__ uint32_t pack_f16(float lo, float hi) { uint32_t r; asm("cvt.rn.f16x2.f32 %0, %1, %2;" : "=r"(r) : "f"(hi), "f"(lo)); return r; }
__device__ __forceinline__ float bf_lo(uint32_t v) { return __uint_as_float(v << 16); }
__device__ __forceinline__ float bf_hi(uint32_t v) { return __uint_as_float(v & 0xFFFF0000u); }
__device__ __forceinline__ float bf_round(float x) { return __uint_as_float(pack_bf16(0.f, x)); }
__device__ __forceinline__ void h2_unpack(uint32_t v, float& lo, float& hi) {
    asm("{.reg .f16 l, h; mov.b32 {l, h}, %2; cvt.f32.f16 %0, l; cvt.f32.f16 %1, h;}" : "=f"(lo), "=f"(hi) : "r"(v));
}
__device__ __forceinline__ uint32_t hadd2(uint32_t a, uint32_t b) { uint32_t r; asm("add.rn.f16x2 %0, %1, %2;" : "=r"(r) : "r"(a), "r"(b)); return r; }
__device__ __forceinline__ uint32_t hmax2(uint32_t a, uint32_t b) { uint32_t r; asm("max.f16x2 %0, %1, %2;" : "=r"(r) : "r"(a), "r"(b)); return r; }
__device__ __forceinline__ uint32_t badd2(uint32_t a, uint32_t b) { uint32_t r; asm("add.rn.bf16x2 %0, %1, %2;" : "=r"(r) : "r"(a), "r"(b)); return r; }
__device__ __forceinline__ uint32_t bmul2(uint32_t a, uint32_t b) { uint32_t r; asm("mul.rn.bf16x2 %0, %1, %2;" : "=r"(r) : "r"(a), "r"(b)); return r; }
__device__ __forceinline__ float warp_sum(float v) {
    #pragma unroll
    for (int o = 16; o > 0; o >>= 1) v += __shfl_xor_sync(0xffffffffu, v, o);
    return v;
}
__device__ __forceinline__ float quad_sum(float v) { v += __shfl_xor_sync(0xffffffffu, v, 1); return v + __shfl_xor_sync(0xffffffffu, v, 2); }
__device__ __forceinline__ float quad_max(float v) { v = fmaxf(v, __shfl_xor_sync(0xffffffffu, v, 1)); return fmaxf(v, __shfl_xor_sync(0xffffffffu, v, 2)); }
__device__ __forceinline__ uint32_t redux_max(uint32_t v) { uint32_t r; asm volatile("redux.sync.max.u32 %0, %1, 0xffffffff;" : "=r"(r) : "r"(v)); return r; }
__device__ __forceinline__ uint32_t redux_min(uint32_t v) { uint32_t r; asm volatile("redux.sync.min.u32 %0, %1, 0xffffffff;" : "=r"(r) : "r"(v)); return r; }
__device__ __forceinline__ uint32_t order_bits(float r) { const uint32_t u = __float_as_uint(r); return (u & 0x80000000u) ? ~u : (u | 0x80000000u); }
struct Ln2 { uint32_t nm, rh, rl, c; };
__device__ __forceinline__ Ln2 ln2_coef(float mean, float rstd) {
    const uint32_t a = pack_bf16(-mean, rstd), b = pack_bf16((-mean - bf_lo(a)) * rstd, rstd - bf_hi(a));
    return {__byte_perm(a, 0, 0x1010), __byte_perm(a, 0, 0x3232), __byte_perm(b, 0, 0x3232), __byte_perm(b, 0, 0x1010)};
}
__device__ __forceinline__ uint32_t bfma2(uint32_t a, uint32_t b, uint32_t c) { uint32_t r; asm("fma.rn.bf16x2 %0, %1, %2, %3;" : "=r"(r) : "r"(a), "r"(b), "r"(c)); return r; }
__device__ __forceinline__ uint32_t ln2(uint32_t v, const Ln2& k) { const uint32_t d = badd2(v, k.nm); return bfma2(d, k.rh, bfma2(d, k.rl, k.c)); }
__device__ __forceinline__ uint32_t add_ln2(uint32_t v, const Ln2& k) { return badd2(v, ln2(v, k)); }

#define TL(TID, i)
#define CK(TID, i)

__device__ __forceinline__ void wg_gemm_n128(float (&d)[64], uint64_t desca, uint64_t desc) {
    asm volatile("{\n.reg .pred p;\nsetp.ne.b32 p, 1, 0;\n"
        "wgmma.mma_async.sync.aligned.m64n128k16.f32.bf16.bf16 "
        "{%0,%1,%2,%3,%4,%5,%6,%7,%8,%9,%10,%11,%12,%13,%14,%15,%16,%17,%18,%19,%20,%21,%22,%23,%24,%25,%26,%27,%28,%29,%30,%31,%32,%33,%34,%35,%36,%37,%38,%39,%40,%41,%42,%43,%44,%45,%46,%47,%48,%49,%50,%51,%52,%53,%54,%55,%56,%57,%58,%59,%60,%61,%62,%63}, "
        "%64, %65, p, 1, 1, 0, 1;\n}\n"
        : "+f"(d[0]), "+f"(d[1]), "+f"(d[2]), "+f"(d[3]), "+f"(d[4]), "+f"(d[5]), "+f"(d[6]), "+f"(d[7]), "+f"(d[8]), "+f"(d[9]), "+f"(d[10]), "+f"(d[11]),
          "+f"(d[12]), "+f"(d[13]), "+f"(d[14]), "+f"(d[15]), "+f"(d[16]), "+f"(d[17]), "+f"(d[18]), "+f"(d[19]), "+f"(d[20]), "+f"(d[21]), "+f"(d[22]), "+f"(d[23]),
          "+f"(d[24]), "+f"(d[25]), "+f"(d[26]), "+f"(d[27]), "+f"(d[28]), "+f"(d[29]), "+f"(d[30]), "+f"(d[31]), "+f"(d[32]), "+f"(d[33]), "+f"(d[34]), "+f"(d[35]),
          "+f"(d[36]), "+f"(d[37]), "+f"(d[38]), "+f"(d[39]), "+f"(d[40]), "+f"(d[41]), "+f"(d[42]), "+f"(d[43]), "+f"(d[44]), "+f"(d[45]), "+f"(d[46]), "+f"(d[47]),
          "+f"(d[48]), "+f"(d[49]), "+f"(d[50]), "+f"(d[51]), "+f"(d[52]), "+f"(d[53]), "+f"(d[54]), "+f"(d[55]), "+f"(d[56]), "+f"(d[57]), "+f"(d[58]), "+f"(d[59]),
          "+f"(d[60]), "+f"(d[61]), "+f"(d[62]), "+f"(d[63])
        : "l"(desca), "l"(desc));
}
__device__ __forceinline__ void wg_gemm_n192(float (&d)[96], uint64_t desca, uint64_t desc) {
    asm volatile("{\n.reg .pred p;\nsetp.ne.b32 p, 1, 0;\n"
        "wgmma.mma_async.sync.aligned.m64n192k16.f32.bf16.bf16 "
        "{%0,%1,%2,%3,%4,%5,%6,%7,%8,%9,%10,%11,%12,%13,%14,%15,%16,%17,%18,%19,%20,%21,%22,%23,%24,%25,%26,%27,%28,%29,%30,%31,%32,%33,%34,%35,%36,%37,%38,%39,%40,%41,%42,%43,%44,%45,%46,%47,%48,%49,%50,%51,%52,%53,%54,%55,%56,%57,%58,%59,%60,%61,%62,%63,%64,%65,%66,%67,%68,%69,%70,%71,%72,%73,%74,%75,%76,%77,%78,%79,%80,%81,%82,%83,%84,%85,%86,%87,%88,%89,%90,%91,%92,%93,%94,%95}, "
        "%96, %97, p, 1, 1, 0, 1;\n}\n"
        : "+f"(d[0]), "+f"(d[1]), "+f"(d[2]), "+f"(d[3]), "+f"(d[4]), "+f"(d[5]), "+f"(d[6]), "+f"(d[7]), "+f"(d[8]), "+f"(d[9]), "+f"(d[10]), "+f"(d[11]),
          "+f"(d[12]), "+f"(d[13]), "+f"(d[14]), "+f"(d[15]), "+f"(d[16]), "+f"(d[17]), "+f"(d[18]), "+f"(d[19]), "+f"(d[20]), "+f"(d[21]), "+f"(d[22]), "+f"(d[23]),
          "+f"(d[24]), "+f"(d[25]), "+f"(d[26]), "+f"(d[27]), "+f"(d[28]), "+f"(d[29]), "+f"(d[30]), "+f"(d[31]), "+f"(d[32]), "+f"(d[33]), "+f"(d[34]), "+f"(d[35]),
          "+f"(d[36]), "+f"(d[37]), "+f"(d[38]), "+f"(d[39]), "+f"(d[40]), "+f"(d[41]), "+f"(d[42]), "+f"(d[43]), "+f"(d[44]), "+f"(d[45]), "+f"(d[46]), "+f"(d[47]),
          "+f"(d[48]), "+f"(d[49]), "+f"(d[50]), "+f"(d[51]), "+f"(d[52]), "+f"(d[53]), "+f"(d[54]), "+f"(d[55]), "+f"(d[56]), "+f"(d[57]), "+f"(d[58]), "+f"(d[59]),
          "+f"(d[60]), "+f"(d[61]), "+f"(d[62]), "+f"(d[63]), "+f"(d[64]), "+f"(d[65]), "+f"(d[66]), "+f"(d[67]), "+f"(d[68]), "+f"(d[69]), "+f"(d[70]), "+f"(d[71]),
          "+f"(d[72]), "+f"(d[73]), "+f"(d[74]), "+f"(d[75]), "+f"(d[76]), "+f"(d[77]), "+f"(d[78]), "+f"(d[79]), "+f"(d[80]), "+f"(d[81]), "+f"(d[82]), "+f"(d[83]),
          "+f"(d[84]), "+f"(d[85]), "+f"(d[86]), "+f"(d[87]), "+f"(d[88]), "+f"(d[89]), "+f"(d[90]), "+f"(d[91]), "+f"(d[92]), "+f"(d[93]), "+f"(d[94]), "+f"(d[95])
        : "l"(desca), "l"(desc));
}
__device__ __forceinline__ void wg_gemm_n192_init(float (&d)[96], uint64_t desca, uint64_t desc) {
    asm volatile("{\n.reg .pred p;\nsetp.ne.b32 p, 0, 0;\n"
        "wgmma.mma_async.sync.aligned.m64n192k16.f32.bf16.bf16 "
        "{%0,%1,%2,%3,%4,%5,%6,%7,%8,%9,%10,%11,%12,%13,%14,%15,%16,%17,%18,%19,%20,%21,%22,%23,%24,%25,%26,%27,%28,%29,%30,%31,%32,%33,%34,%35,%36,%37,%38,%39,%40,%41,%42,%43,%44,%45,%46,%47,%48,%49,%50,%51,%52,%53,%54,%55,%56,%57,%58,%59,%60,%61,%62,%63,%64,%65,%66,%67,%68,%69,%70,%71,%72,%73,%74,%75,%76,%77,%78,%79,%80,%81,%82,%83,%84,%85,%86,%87,%88,%89,%90,%91,%92,%93,%94,%95}, "
        "%96, %97, p, 1, 1, 0, 1;\n}\n"
        : "=f"(d[0]), "=f"(d[1]), "=f"(d[2]), "=f"(d[3]), "=f"(d[4]), "=f"(d[5]), "=f"(d[6]), "=f"(d[7]), "=f"(d[8]), "=f"(d[9]), "=f"(d[10]), "=f"(d[11]),
          "=f"(d[12]), "=f"(d[13]), "=f"(d[14]), "=f"(d[15]), "=f"(d[16]), "=f"(d[17]), "=f"(d[18]), "=f"(d[19]), "=f"(d[20]), "=f"(d[21]), "=f"(d[22]), "=f"(d[23]),
          "=f"(d[24]), "=f"(d[25]), "=f"(d[26]), "=f"(d[27]), "=f"(d[28]), "=f"(d[29]), "=f"(d[30]), "=f"(d[31]), "=f"(d[32]), "=f"(d[33]), "=f"(d[34]), "=f"(d[35]),
          "=f"(d[36]), "=f"(d[37]), "=f"(d[38]), "=f"(d[39]), "=f"(d[40]), "=f"(d[41]), "=f"(d[42]), "=f"(d[43]), "=f"(d[44]), "=f"(d[45]), "=f"(d[46]), "=f"(d[47]),
          "=f"(d[48]), "=f"(d[49]), "=f"(d[50]), "=f"(d[51]), "=f"(d[52]), "=f"(d[53]), "=f"(d[54]), "=f"(d[55]), "=f"(d[56]), "=f"(d[57]), "=f"(d[58]), "=f"(d[59]),
          "=f"(d[60]), "=f"(d[61]), "=f"(d[62]), "=f"(d[63]), "=f"(d[64]), "=f"(d[65]), "=f"(d[66]), "=f"(d[67]), "=f"(d[68]), "=f"(d[69]), "=f"(d[70]), "=f"(d[71]),
          "=f"(d[72]), "=f"(d[73]), "=f"(d[74]), "=f"(d[75]), "=f"(d[76]), "=f"(d[77]), "=f"(d[78]), "=f"(d[79]), "=f"(d[80]), "=f"(d[81]), "=f"(d[82]), "=f"(d[83]),
          "=f"(d[84]), "=f"(d[85]), "=f"(d[86]), "=f"(d[87]), "=f"(d[88]), "=f"(d[89]), "=f"(d[90]), "=f"(d[91]), "=f"(d[92]), "=f"(d[93]), "=f"(d[94]), "=f"(d[95])
        : "l"(desca), "l"(desc));
}
__device__ __forceinline__ void wg_qk_init(uint32_t (&d)[32], uint32_t a0, uint32_t a1, uint32_t a2, uint32_t a3, uint64_t desc) {
    asm volatile("{\n.reg .pred p;\nsetp.ne.b32 p, 0, 0;\n"
        "wgmma.mma_async.sync.aligned.m64n128k16.f16.f16.f16 "
        "{%0,%1,%2,%3,%4,%5,%6,%7,%8,%9,%10,%11,%12,%13,%14,%15,%16,%17,%18,%19,%20,%21,%22,%23,%24,%25,%26,%27,%28,%29,%30,%31}, "
        "{%32,%33,%34,%35}, %36, p, 1, 1, 0;\n}\n"
        : "=r"(d[0]), "=r"(d[1]), "=r"(d[2]), "=r"(d[3]), "=r"(d[4]), "=r"(d[5]), "=r"(d[6]), "=r"(d[7]), "=r"(d[8]), "=r"(d[9]), "=r"(d[10]), "=r"(d[11]),
          "=r"(d[12]), "=r"(d[13]), "=r"(d[14]), "=r"(d[15]), "=r"(d[16]), "=r"(d[17]), "=r"(d[18]), "=r"(d[19]), "=r"(d[20]), "=r"(d[21]), "=r"(d[22]), "=r"(d[23]),
          "=r"(d[24]), "=r"(d[25]), "=r"(d[26]), "=r"(d[27]), "=r"(d[28]), "=r"(d[29]), "=r"(d[30]), "=r"(d[31])
        : "r"(a0), "r"(a1), "r"(a2), "r"(a3), "l"(desc));
}
__device__ __forceinline__ void wg_qk_acc(uint32_t (&d)[32], uint32_t a0, uint32_t a1, uint32_t a2, uint32_t a3, uint64_t desc) {
    asm volatile("{\n.reg .pred p;\nsetp.ne.b32 p, 1, 0;\n"
        "wgmma.mma_async.sync.aligned.m64n128k16.f16.f16.f16 "
        "{%0,%1,%2,%3,%4,%5,%6,%7,%8,%9,%10,%11,%12,%13,%14,%15,%16,%17,%18,%19,%20,%21,%22,%23,%24,%25,%26,%27,%28,%29,%30,%31}, "
        "{%32,%33,%34,%35}, %36, p, 1, 1, 0;\n}\n"
        : "+r"(d[0]), "+r"(d[1]), "+r"(d[2]), "+r"(d[3]), "+r"(d[4]), "+r"(d[5]), "+r"(d[6]), "+r"(d[7]), "+r"(d[8]), "+r"(d[9]), "+r"(d[10]), "+r"(d[11]),
          "+r"(d[12]), "+r"(d[13]), "+r"(d[14]), "+r"(d[15]), "+r"(d[16]), "+r"(d[17]), "+r"(d[18]), "+r"(d[19]), "+r"(d[20]), "+r"(d[21]), "+r"(d[22]), "+r"(d[23]),
          "+r"(d[24]), "+r"(d[25]), "+r"(d[26]), "+r"(d[27]), "+r"(d[28]), "+r"(d[29]), "+r"(d[30]), "+r"(d[31])
        : "r"(a0), "r"(a1), "r"(a2), "r"(a3), "l"(desc));
}
__device__ __forceinline__ void wg_pv_init(uint32_t (&d)[10], uint32_t a0, uint32_t a1, uint32_t a2, uint32_t a3, uint64_t desc) {
    asm volatile("{\n.reg .pred p;\nsetp.ne.b32 p, 0, 0;\n"
        "wgmma.mma_async.sync.aligned.m64n40k16.f16.f16.f16 "
        "{%0,%1,%2,%3,%4,%5,%6,%7,%8,%9}, "
        "{%10,%11,%12,%13}, %14, p, 1, 1, 1;\n}\n"
        : "=r"(d[0]), "=r"(d[1]), "=r"(d[2]), "=r"(d[3]), "=r"(d[4]), "=r"(d[5]), "=r"(d[6]), "=r"(d[7]), "=r"(d[8]), "=r"(d[9])
        : "r"(a0), "r"(a1), "r"(a2), "r"(a3), "l"(desc));
}
__device__ __forceinline__ void wg_pv_acc(uint32_t (&d)[10], uint32_t a0, uint32_t a1, uint32_t a2, uint32_t a3, uint64_t desc) {
    asm volatile("{\n.reg .pred p;\nsetp.ne.b32 p, 1, 0;\n"
        "wgmma.mma_async.sync.aligned.m64n40k16.f16.f16.f16 "
        "{%0,%1,%2,%3,%4,%5,%6,%7,%8,%9}, "
        "{%10,%11,%12,%13}, %14, p, 1, 1, 1;\n}\n"
        : "+r"(d[0]), "+r"(d[1]), "+r"(d[2]), "+r"(d[3]), "+r"(d[4]), "+r"(d[5]), "+r"(d[6]), "+r"(d[7]), "+r"(d[8]), "+r"(d[9])
        : "r"(a0), "r"(a1), "r"(a2), "r"(a3), "l"(desc));
}

constexpr uint32_t SB = SMEM_BASE;
constexpr uint32_t R_SLOT = 18432, A_RING = SB, A_KP = SB + 73728, A_QX = SB + 81920, A_STB = SB + 98304;
constexpr uint32_t F_GU0 = SB + 98304, F_GU1 = SB + 163840, F_WD = F_GU0;
__host__ __device__ constexpr uint32_t o_a(uint32_t s) { return s == 0 ? SB : s == 1 ? A_QX : F_GU0 + (s - 2) * 32768; }
__host__ __device__ constexpr uint32_t o_b(uint32_t s) { return s < 2 ? SB + 16384 + s * 16384 : F_GU0 + 16384 + (s - 2) * 32768; }
constexpr uint32_t XT0 = SB + 49152, XT1 = XT0 + 16384, YT0 = o_a(0), YT1 = o_a(1);
constexpr uint32_t Q_ABYTES = 256 * 64 * 2, Q_STB = Q_ABYTES + 192 * 64 * 2;
constexpr uint32_t Q_CS = SB + 3 * Q_STB, Q_RC = Q_CS + 768, Q_FIX = Q_RC + 2048;
constexpr uint32_t SD_VEC = SB + 176128, SD_W = SB + 180224;
static_assert(Q_FIX + 768 <= SD_VEC, "smem");
constexpr uint32_t M_RED = SB + 229376, M_BAR = M_RED + 2048, BAR_SET = 336, M_HS = M_BAR + 2 * BAR_SET, M_SM = M_HS + 128;
constexpr uint32_t M_IV = M_SM;
constexpr uint32_t M_WS = M_SM + 16;
constexpr uint32_t M_CR = M_SM + 20;
constexpr uint32_t M_SS = M_SM + 24;
constexpr uint32_t M_RT = M_SM + 32;
constexpr uint32_t M_SR = M_SM + 96;
constexpr int K_SMEM = M_SR + 128 - SB;
static_assert(K_SMEM == 232448, "smem");
constexpr uint32_t B_QF = 0, B_AF = 24, B_OF = 56, B_RES = 88, B_GU = 96, B_WD = 104, B_RT = 112, B_SW = 120, B_ONE = 128, B_XD = 136, B_QE = 144, B_OE = 168,
                   B_PX = 200, B_AE = 224, B_OD = 256, B_FG = 288, B_FD = 296, B_XS = 304, B_KS = 312, B_K0 = 320, B_END = 328;
constexpr int NB_ML = 1, NB_CONS = 2, NB_SIDE = 3, NB_EPI = 4, NB_WG = 6;

__device__ __forceinline__ int mt_of(int c) { return (c >> 2) & 7; }
__device__ __forceinline__ int nt_of(int c) { return (c >> 5) * 4 + (c & 3); }
__device__ __forceinline__ int blk_of(int c) { return c >> 3; }
__device__ __forceinline__ int cb_of(int c) { return c & 7; }

struct Maps { CUtensorMap x[2], wqkv, o, wo[2], r, g, u, d; };

template <int N>
__device__ __forceinline__ void halve(float (&v)[8], int lane, int bit) {
    const bool up = lane & bit;
    #pragma unroll
    for (int i = 0; i < N; i++) v[i] = (up ? v[N + i] : v[i]) + __shfl_xor_sync(0xffffffffu, up ? v[i] : v[N + i], bit);
}

__device__ __forceinline__ void reset_exchange(int c, int t) {
    #pragma unroll 1
    for (int i = t; i < FILL; i += 96) g_u.fill[c][i] = make_uint4(EMPTY, EMPTY, EMPTY, EMPTY);
}
__device__ __forceinline__ void prep_work(const bf16* __restrict__ x0, const bf16* __restrict__ w_r, uint32_t lb) {
    const int t = tid_now() - 288, c = cta_now(), lane = t & 31, warp = warp_uniform(t >> 5);
    const uint32_t wb = SD_W + warp * 8192;
    mbar_nap(lb + B_SW, 0);
    {
        float cs[8], cq[8];
        #pragma unroll
        for (int i = 0; i < 8; i++) { cs[i] = 0.f; cq[i] = 0.f; }
        #pragma unroll 1
        for (int h = 0; h < 2; h++) {
            #pragma unroll 2
            for (int r = 0; r < 16; r++) {
                const uint4 u = lds128(wb + h * 24576 + (lane >> 3) * 128 + r * 512 + (((lane & 7) ^ ((r * 4 + (lane >> 3)) & 7)) << 4));
                const uint32_t w[4] = {u.x, u.y, u.z, u.w};
                #pragma unroll
                for (int e = 0; e < 4; e++) {
                    const float a = bf_lo(w[e]), b = bf_hi(w[e]);
                    cs[2*e] += a; cs[2*e+1] += b; cq[2*e] = fmaf(a, a, cq[2*e]); cq[2*e+1] = fmaf(b, b, cq[2*e+1]);
                }
            }
            fence_async_smem();
            __syncwarp();
            if (elect_one()) {
                const uint32_t bytes = h == 0 ? 8192 : warp < 2 ? 4096 : 2048;
                mbar_expect_tx(lb + B_PX + warp * 8, bytes);
                bulk_load(wb + h * 24576, h && warp == 2 ? w_r : x0 + (size_t)(c * 16 + (h ? 12 + warp * 2 : warp * 4)) * D_, bytes, lb + B_PX + warp * 8);
            }
            __syncwarp();
        }
        halve<4>(cs, lane, 16); halve<2>(cs, lane, 8);
        halve<4>(cq, lane, 16); halve<2>(cq, lane, 8);
        *reinterpret_cast<float4*>(&g_cs[mt_of(c)][warp * D_ + nt_of(c) * 64 + (lane & 7) * 8 + (lane >> 3) * 2]) = make_float4(cs[0], cq[0], cs[1], cq[1]);
    }
    TL(288, 22);
    reset_exchange(c, t);
    mbar_nap(lb + B_PX + warp * 8, 0);
    #pragma unroll 1
    for (int i = 0; i < (warp < 2 ? 6 : 5); i++) {
        const int r = i < 4 ? warp * 4 + i : 8 + warp * 2 + i;
        float s0 = 0.f, s1 = 0.f, q0 = 0.f, q1 = 0.f;
        #pragma unroll 2
        for (int j = 0; j < 4; j++) {
            const uint4 u = lds128(wb + (i >> 2) * 16384 + i * 2048 + j * 512 + lane * 16);
            const uint32_t w[4] = {u.x, u.y, u.z, u.w};
            #pragma unroll
            for (int e = 0; e < 4; e++) { const float a = bf_lo(w[e]), b = bf_hi(w[e]); s0 += a; s1 += b; q0 = fmaf(a, a, q0); q1 = fmaf(b, b, q1); }
        }
        s0 += s1; q0 += q1;
        float v = (lane & 16 ? q0 : s0) + __shfl_xor_sync(0xffffffffu, lane & 16 ? s0 : q0, 16);
        #pragma unroll
        for (int o = 8; o > 0; o >>= 1) v += __shfl_xor_sync(0xffffffffu, v, o);
        const float mean = v * (1.f / D_), sq = __shfl_xor_sync(0xffffffffu, mean, 16);
        if (lane == 0) {
            if (r < 16) g_rs0[c * 16 + r] = make_float2(fmaxf(sq - mean * mean, 0.f), mean);
            else stsf(M_WS, v);
        }
    }
    named_sync(NB_SIDE, 96);
    if (t == 0) { TL(288, 23); ctr_arrive(&g_pctr); ctr_wait(&g_pctr, 128); TL(288, 24); }
    named_sync(NB_SIDE, 96);
}

__device__ __forceinline__ int half_exp(uint32_t bits, int off) { return min(max((((int)(bits >> 23) - 125) >> 1) + off, -55), 55); }
__device__ __forceinline__ float pow2(int e) { return __uint_as_float((uint32_t)(127 + e) << 23); }
__device__ __forceinline__ void head_scales(int h) {
    const float fq = ldsf(M_SR + h * 4), fk = ldsf(M_SR + 8 + h * 4);
    const uint32_t vmax = lds32(M_SR + 16 + h * 4), vmin = lds32(M_SR + 24 + h * 4);
    const bool ok = fq <= 16384.f && fk <= 16384.f && fq * fk <= 50000.f && vmax <= vmin + (12u << 23);
    const int a = ok ? 0 : half_exp(__float_as_uint(fq), -8), b = ok ? 0 : half_exp(__float_as_uint(fk), -8), v = half_exp(vmax, ok ? 3 : -10);
    stsf(M_HS + h * 4, QSCALE * pow2(-a)); stsf(M_HS + 8 + h * 4, pow2(-b)); stsf(M_HS + 16 + h * 4, pow2(-v));
    stsf(M_SS + h * 4, ok ? 0.f : pow2(a + b));
    stsf(M_IV + h * 4, pow2(v - 4));
}

__device__ __forceinline__ void epi_inputs(int L, const bf16* __restrict__ w_r) {
    const int t = tid_now() - 288, c = cta_now(), mt = mt_of(c), nt = nt_of(c), lane = t & 31;
    const uint32_t wr = t < 64 ? __ldg(reinterpret_cast<const uint32_t*>(w_r) + cb_of(c) * 64 + t) : 0x3F803F80u;
    #pragma unroll 1
    for (int k = 0; k < 3; k++) {
        const int i = t + 96 * k, col = (i >> 6) * D_ + nt * 64 + (i & 63);
        const float2* rsp = (L ? g_x.rs1 : g_rs0) + mt * 256 + (i & 255);
        uint2 sv = ld_x64(rsp);
        if (k < 2) {
            float2 p[8];
            #pragma unroll
            for (int j = 0; j < 8; j++) p[j] = __ldcg(&g_cs[j][col]);
            stsf(Q_CS + i * 4, ((p[0].x + p[1].x) + (p[2].x + p[3].x)) + ((p[4].x + p[5].x) + (p[6].x + p[7].x)));
            const float zz = ((p[0].y + p[1].y) + (p[2].y + p[3].y)) + ((p[4].y + p[5].y) + (p[6].y + p[7].y));
            const float zs = warp_sum(zz);
            const uint32_t zb = __float_as_uint(zz), zmax = redux_max(zb), zmin = redux_min(zb ? zb : 0x7F800000u);
            if (lane == 0) {
                sts32(M_SR + (i >> 5) * 4, i < 128 ? __float_as_uint(zs) : zmax);
                if (i >= 128) sts32(M_SR + 8 + (i >> 5) * 4, zmin);
            }
        } else {
            named_sync(NB_SIDE, 96);
            if (t < 2) head_scales(t);
            __syncwarp();
        }
        uint32_t n = 0;
        #pragma unroll 1
        while (warp_any(sv.x == EMPTY)) { sv = ld_x64(rsp); poll_tick(n); }
        const float var = __uint_as_float(sv.x), a = L ? 1.f + rsq(var + LN_EPS) : 1.f;
        sts64(Q_RC + (i & 255) * 8, __float_as_uint(a * rsq(a * a * var + LN_EPS)), sv.y ^ 0x80000000u);
    }
    if (t < 68) sts32(M_RED + t * 4, wr);
}

__device__ __forceinline__ void ffn_finish(int L, bf16* __restrict__ out) {
    const int t = tid_now() - 288, c = cta_now(), lane = t & 31, warp = warp_uniform(t >> 5);
    TL(288, L * 32 + 29);
    const uint4 rv = lds128(M_RT + 16 * L);
    const int idx = (int)rv.w;
    const uint32_t* xsrc = &g_x.cand[L][idx >> 7][(c >> 2) * 16 + (t & 3) * 4 + (c & 3)];
    const uint8_t* fsrc = &g_x.x[idx >> 8][((idx >> 7) & 1) * 8 + (c >> 4)];
    uint32_t xw, busy;
    float a[4] = {0.f, 0.f, 0.f, 0.f};
    {
        const float* src = &g_x.ypart[L][c][0][t * 4];
        uint4 v[3];
        uint32_t n = 0;
        #pragma unroll 1
        do {
            v[0] = ld_x128(src); v[1] = ld_x128(src + 384);
            v[2] = make_uint4(0u, 0u, 0u, 0u);
            xw = 0u; busy = 0u;
            if (warp == 0) {
                v[2] = ld_x128(src + 768); xw = ld_x32(xsrc);
                asm volatile("ld.relaxed.gpu.global.u8 %0, [%1];" : "=r"(busy) : "l"(fsrc) : "memory");
            }
            poll_tick(n);
        } while (warp_any(any_empty(v[0]) || any_empty(v[1]) || any_empty(v[2]) || xw == EMPTY || busy != 0));
        TL(288, L * 32 + 30); TL(352, L * 32 + 31);
        #pragma unroll
        for (int i = 0; i < 3; i++) { a[0] += __uint_as_float(v[i].x); a[1] += __uint_as_float(v[i].y); a[2] += __uint_as_float(v[i].z); a[3] += __uint_as_float(v[i].w); }
    }
    #pragma unroll
    for (int o = 2; o < 32; o <<= 1) {
        #pragma unroll
        for (int i = 0; i < 4; i++) a[i] += __shfl_xor_sync(0xffffffffu, a[i], o);
    }
    if (lane < 2) sts128(M_SR + warp * 32 + lane * 16, __float_as_uint(a[0]), __float_as_uint(a[1]), __float_as_uint(a[2]), __float_as_uint(a[3]));
    named_sync(NB_SIDE, 96);
    if (t < 4) {
        const float2 y0 = lds64f(M_SR + t * 8), y1 = lds64f(M_SR + 32 + t * 8), y2 = lds64f(M_SR + 64 + t * 8);
        const uint32_t y = pack_bf16(y0.x + y1.x + y2.x, y0.y + y1.y + y2.y);
        const float rsel = bf_round(rcp(1.f + __expf(-bf_round(__uint_as_float(rv.x)))));
        const uint32_t xn = ln2(xw, ln2_coef(__uint_as_float(rv.y), __uint_as_float(rv.z)));
        const uint32_t res = badd2(xw, badd2(xn, pack_bf16(bf_lo(y) * rsel, bf_hi(y) * rsel)));
        if (L == 0) st_x32(&g_x.x2row[c * 4 + t], res);
        reinterpret_cast<uint32_t*>(L ? out : g_x1)[idx * (D_ / 2) + c * 4 + t] = res;
    }
}

__device__ __forceinline__ void fix_row(uint32_t lb) {
    const int t = tid_now() - 288, c = cta_now(), lane = t & 31, warp = warp_uniform(t >> 5);
    uint4 v[2];
    {
        uint32_t n = 0;
        #pragma unroll 1
        do {
            v[0] = ld_x128(g_x.x2row + t * 4);
            v[1] = make_uint4(0u, 0u, 0u, 0u);
            if (warp == 0) v[1] = ld_x128(g_x.x2row + (96 + t) * 4);
            poll_tick(n);
        } while (warp_any(any_empty(v[0]) || any_empty(v[1])));
    }
    const uint32_t w[8] = {v[0].x, v[0].y, v[0].z, v[0].w, v[1].x, v[1].y, v[1].z, v[1].w};
    float su = 0.f, sq = 0.f;
    #pragma unroll
    for (int i = 0; i < 8; i++) { const float a = bf_lo(w[i]), b = bf_hi(w[i]); su += a + b; sq = fmaf(a, a, fmaf(b, b, sq)); }
    su = warp_sum(su); sq = warp_sum(sq);
    if (lane == 0) sts64(M_SR + 96 + warp * 8, __float_as_uint(su), __float_as_uint(sq));
    named_sync(NB_SIDE, 96);
    const float2 s0 = lds64f(M_SR + 96), s1 = lds64f(M_SR + 104), s2 = lds64f(M_SR + 112);
    const float mean = (s0.x + s1.x + s2.x) * (1.f / D_);
    const float rstd = rsq(fmaxf((s0.y + s1.y + s2.y) * (1.f / D_) - mean * mean, 0.f) + LN_EPS);
    const Ln2 k = ln2_coef(mean, rstd);
    #pragma unroll
    for (int i = 0; i < 2; i++)
        if (i == 0 || warp == 0) sts128(SD_VEC + (t + 96 * i) * 16, ln2(w[4*i], k), ln2(w[4*i+1], k), ln2(w[4*i+2], k), ln2(w[4*i+3], k));
    named_sync(NB_SIDE, 96);
    TL(288, 32 + 22);
    mbar_nap(lb + B_SW, 0);
    float a[8];
    #pragma unroll
    for (int i = 0; i < 8; i++) a[i] = 0.f;
    const uint32_t xa = base32(SD_VEC + lane * 2), wa = base32(SD_W + lane * 48 + warp * 16);
    #pragma unroll 2
    for (int b = 0; b < 32; b++) {
        const float x = bf_lo(lds16(xa + b * 64));
        const uint4 u = lds128(wa + b * 1536);
        a[0] = fmaf(x, bf_lo(u.x), a[0]); a[1] = fmaf(x, bf_hi(u.x), a[1]); a[2] = fmaf(x, bf_lo(u.y), a[2]); a[3] = fmaf(x, bf_hi(u.y), a[3]);
        a[4] = fmaf(x, bf_lo(u.z), a[4]); a[5] = fmaf(x, bf_hi(u.z), a[5]); a[6] = fmaf(x, bf_lo(u.w), a[6]); a[7] = fmaf(x, bf_hi(u.w), a[7]);
    }
    halve<4>(a, lane, 16); halve<2>(a, lane, 8); halve<1>(a, lane, 4);
    a[0] = quad_sum(a[0]);
    if ((lane & 3) == 0) st_x32(&g_x.fix[c * 24 + warp * 8 + (lane >> 2)], __float_as_uint(a[0]));
    TL(288, 32 + 23);
    if (((int)lds32(M_RT + 12) >> 8) == mt_of(c)) {
        const float* src = &g_x.fix[(t >> 5) * D_ + nt_of(c) * 64 + (t & 31) * 2];
        uint2 f;
        uint32_t n = 0;
        #pragma unroll 1
        do { f = ld_x64(src); poll_tick(n); } while (warp_any(f.x == EMPTY || f.y == EMPTY));
        sts64(Q_FIX + t * 8, f.x, f.y);
    }
}

__device__ __forceinline__ void out_piece(bf16* __restrict__ out, int r, int ch, bool on) {
    const uint4 v = lds128(((ch & 8) ? YT1 : YT0) + r * 128 + (((ch ^ r) & 7) << 4)), kk = lds128(XT0 + r * 16);
    const Ln2 k = {kk.x, kk.y, kk.z, kk.w};
    const int c = blockIdx.x;
    stg128_pred(out + (blk_of(c) * 128 + r) * D_ + cb_of(c) * 128 + ch * 8, make_uint4(add_ln2(v.x, k), add_ln2(v.y, k), add_ln2(v.z, k), add_ln2(v.w, k)), on);
}
__device__ __forceinline__ void publish(uint8_t* f) {
    bulk_commit();
    bulk_wait();
    fence_async_global();
    asm volatile("st.release.gpu.global.u8 [%0], 0;" :: "l"(f) : "memory");
}
__device__ __forceinline__ void side_role(const Maps& mp, const bf16* __restrict__ x0, const bf16* __restrict__ wo, const bf16* __restrict__ w_down, const bf16* __restrict__ w_r, bf16* __restrict__ out) {
    #pragma unroll 1
    for (int L = 0; L < 2; L++) {
        const uint32_t lb = M_BAR + L * BAR_SET;
        if (L == 0) prep_work(x0, w_r, lb);
        else fix_row(lb);
        epi_inputs(L, w_r);
        const int t = tid_now() - 288, c = cta_now(), mt = mt_of(c), nt = nt_of(c), warp = warp_uniform(t >> 5);
        TL(288, L * 32 + 4);
        named_arrive(NB_EPI, 224);
        named_arrive(NB_EPI + 1, 224);
        if (warp == 0) {
            named_sync(NB_ML, 288);
            #pragma unroll
            for (int i = 0; i < 16; i++) sts128(base32(A_RING + 16384 + t * 16) + (i >> 2) * R_SLOT + (i & 3) * 512, 0x2C002C00u, 0x2C002C00u, 0x2C002C00u, 0x2C002C00u);
            fence_async_smem();
            __syncwarp();
            mbar_arrive_elect(lb + B_ONE);
        }
        if (elect_one()) {
            #pragma unroll 1
            for (int n = warp - 1; n >= 0 && n < 3 * warp - 2; n++) {
                char* dst = g_kv + (size_t)(nt * 2 + (n >> 1)) * 16 * KV_TILE;
                if (n < 3) mbar_nap(lb + (n == 0 ? B_K0 : n == 1 ? B_KS : B_AE + 16), 0);
                bulk_store(dst + ((2 * mt - 1 + (n & 1)) & 15) * KV_TILE, n == 0 ? A_KP : n == 1 ? A_RING : A_STB + (n - 2) * 8192, 8192 << (n & 1));
                if (n & 1) bulk_store(dst + 2 * mt * KV_TILE + 24576, n == 1 ? A_RING + R_SLOT + 8192 : A_STB + 24576, 8192);
                publish(&g_x.kv[L][nt * 2 + (n >> 1)][2 * mt + (n & 1)]);
                if (n == 1) TL(352, L * 32 + 6);
                if (n == 0) TL(320, L * 32 + 27);
            }
            if (warp == 2) {
                const bool ffn = c < NFC;
                const uint64_t pol = policy_evict_first();
                mbar_expect_tx(lb + B_GU, ffn ? 131072 : 0);
                mbar_expect_tx(lb + B_WD, ffn ? 65536 : 0);
                l2_prefetch(reinterpret_cast<const char*>(wo) + (size_t)c * 16384, 16384);
                if (ffn) {
                    #pragma unroll 1
                    for (int i = 0; i < 12; i++) {
                        if (i < 8) tma_load_s(F_GU0 + i * 16384, (i & 1) ? &mp.u : &mp.g, c * 32, (i >> 1) * 256, lb + B_GU, pol);
                        else l2_prefetch(reinterpret_cast<const char*>(w_down) + (size_t)c * 65536 + (i - 8) * 16384, 16384);
                        __nanosleep(900);
                    }
                }
                mbar_nap(lb + B_OD, 0);
                __nanosleep(1000);
                l2_prefetch(g_u.fill[c], sizeof(g_u.fill[0]));
                if (L == 0) {
                    mbar_nap(lb + B_XS, 0);
                    tma_store(&mp.x[1], YT0, cb_of(c) * 128, blk_of(c) * 128);
                    tma_store(&mp.x[1], YT1, cb_of(c) * 128 + 64, blk_of(c) * 128);
                    publish(&g_x.x[blk_of(c) >> 1][(blk_of(c) & 1) * 8 + cb_of(c)]);
                    mbar_arrive(lb + B_XD);
                    TL(352, 18);
                }
            } else {
                #pragma unroll 1
                for (int p = 0; p < 2; p++) { mbar_sleep(lb + B_OD + (p * 2 + warp) * 8, 0); ctr_arrive(g_x.o[L][mt * 2 + warp][p]); TL(288, L * 32 + 19); }
            }
        }
        __syncwarp();
        if (L) {
            mbar_sleep(lb + B_XS, 0);
            const int cand = (int)lds32(M_CR) & 127;
            #pragma unroll 2
            for (int r = t >> 4; r < 132; r += 6) out_piece(out, r & 127, t & 15, r < 128 && r != cand);
            TL(288, 32 + 18);
            mbar_sleep(lb + B_RT, 0);
            out_piece(out, cand, t & 15, t < 16 && lds32(M_CR) != lds32(M_RT + 28));
        }
        const uint32_t late = mbar_test(lb + B_FD, 0);
        mbar_sleep(lb + B_FD, 0);
        __nanosleep(late ? 50 : 400);
        if (c == 0 && t == 0 && L == 0) g_pctr = 0;
        ffn_finish(L, out);
        TL(288, L * 32 + 20);
    }
}

struct Cols { float2 c[4]; float hs; };
template <int HH>
__device__ __forceinline__ void load_cols(Cols& k, uint32_t cs) {
    #pragma unroll
    for (int jj = 0; jj < 4; jj++) k.c[jj] = lds64f(cs + (HH * 32 + jj * 8) * 4);
    k.hs = ldsf(M_HS + HH * 4);
}
template <int HH>
__device__ __forceinline__ void qkv_epi_head(const float (&acc0)[96], const float (&acc1)[96], const float (&cf)[4], const float (&nm)[4], const Cols& k, uint32_t (&pk)[4][4]) {
    #pragma unroll
    for (int jj = 0; jj < 4; jj++) {
        #pragma unroll
        for (int i = 0; i < 4; i++) {
            const float* a = (i >> 1) ? acc1 : acc0;
            const float sc = cf[i] * k.hs;
            const float x = fmaf(nm[i], k.c[jj].x, a[4 * (4 * HH + jj) + 2 * (i & 1)]) * sc;
            const float y = fmaf(nm[i], k.c[jj].y, a[4 * (4 * HH + jj) + 2 * (i & 1) + 1]) * sc;
            pk[i][jj] = pack_f16(x, y);
        }
    }
}
__device__ __forceinline__ void stage_kv(uint32_t dst, const uint32_t (&pk)[4][4]) {
    #pragma unroll
    for (int i = 0; i < 4; i++) stsm4(dst + (i >> 1) * 1024 + (i & 1) * 128, pk[i][0], pk[i][1], pk[i][2], pk[i][3]);
}
template <int OFF>
__device__ __forceinline__ void patch_row(float (&acc)[96], uint32_t fx) {
    #pragma unroll
    for (int j = 0; j < 24; j++) { const float2 f = lds64f(fx + j * 32); acc[4 * j + OFF] = f.x; acc[4 * j + OFF + 1] = f.y; }
}
template <bool INIT>
__device__ __forceinline__ void qkv_step(float (&acc0)[96], float (&acc1)[96], uint64_t da, uint64_t db) {
    wg_fence();
    #pragma unroll
    for (int kk = 0; kk < 4; kk++) {
        if (INIT && kk == 0) { wg_gemm_n192_init(acc0, da, db); wg_gemm_n192_init(acc1, da + (8192 >> 4), db); }
        else { wg_gemm_n192(acc0, da + kk * 2, db + kk * 128); wg_gemm_n192(acc1, da + (8192 >> 4) + kk * 2, db + kk * 128); }
    }
    wg_commit();
}
__device__ __forceinline__ void qkv_phase(int L, uint32_t lb, int wg, uint32_t (&qa)[8], uint32_t (&qb)[8], uint32_t (&SA)[32], uint32_t (&SB_)[32]) {
    float acc0[96], acc1[96];
    {
        const bool leader = (tid_now() & 127) == 0;
        const uint64_t da0 = opaque(desc_sw128(SB + wg * 16384, 16, 1024)), db0 = opaque(desc_sw128(SB + Q_ABYTES, 8192, 1024));
        mbar_spin(lb + B_QF, 0);
        TL(0, L * 32 + 1); CK(0, L * 32 + 10);
        qkv_step<true>(acc0, acc1, da0, db0);
        uint32_t st = 1, ph = 0;
        #pragma unroll 1
        for (int k = 1; k < 16; k++) {
            mbar_spin(lb + B_QF + 8 * st, ph);
            if (k == 14 && wg) named_sync(NB_CONS, 256);
            qkv_step<false>(acc0, acc1, da0 + st * (Q_STB >> 4), db0 + st * (Q_STB >> 4));
            if (k == 15 && !wg) named_arrive(NB_CONS, 256);
            wg_wait<1>();
            if (leader) mbar_arrive(lb + B_QE + 8 * (st == 0 ? 2 : st - 1));
            if (++st == 3) { st = 0; ph ^= 1; }
        }
    }
    named_sync(NB_EPI + wg, 224);
    const int tid = tid_now(), lane = tid & 31, w = (tid >> 5) & 3, g = lane >> 2, t = lane & 3;
    const int lr0 = wg * 128 + w * 16 + g;
    float cf[4], nm[4];
    #pragma unroll
    for (int i = 0; i < 4; i++) { const float2 r = lds64f(base32(Q_RC + lr0 * 8) + ((i >> 1) * 64 + (i & 1) * 8) * 8); cf[i] = r.x; nm[i] = r.y; }
    const uint32_t cs = base32(Q_CS + t * 8);
    const int d = L ? (int)lds32(M_RT + 12) - (mt_of(cta_now()) * 256 + lr0) : -1;
    const uint32_t ko = base32((lane >> 3) * 2048 + (w * 16 + (lane & 7)) * 16);
    Cols k0, k1;
    load_cols<2>(k0, cs);
    wg_wait<0>();
    pin(acc0); pin(acc1);
    TL(128, L * 32 + 2); CK(128, L * 32 + 11);
    named_arrive(NB_ML, 288);
    if ((tid & 127) == 0) mbar_arrive(lb + B_QE);
    if (__builtin_expect((d & ~72) == 0, 0)) {
        if (d == 0) { patch_row<0>(acc0, cs + (Q_FIX - Q_CS)); cf[0] = 1.f; nm[0] = 0.f; }
        else if (d == 8) { patch_row<2>(acc0, cs + (Q_FIX - Q_CS)); cf[1] = 1.f; nm[1] = 0.f; }
        else if (d == 64) { patch_row<0>(acc1, cs + (Q_FIX - Q_CS)); cf[2] = 1.f; nm[2] = 0.f; }
        else { patch_row<2>(acc1, cs + (Q_FIX - Q_CS)); cf[3] = 1.f; nm[3] = 0.f; }
    }
    __syncwarp();
    uint32_t pk[4][4];
    qkv_epi_head<2>(acc0, acc1, cf, nm, k0, pk);
    load_cols<4>(k1, cs);
    mbar_spin(lb + B_QE + 8 - 8 * wg, wg);
    stage_kv((wg ? A_RING : A_KP) + ko, pk);
    if (!wg) {
        fence_async_smem();
        __syncwarp();
        mbar_arrive_elect(lb + B_K0);
    }
    qkv_epi_head<4>(acc0, acc1, cf, nm, k1, pk);
    load_cols<3>(k0, cs);
    stage_kv(A_RING + wg * R_SLOT + 8192 + ko, pk);
    fence_async_smem();
    __syncwarp();
    mbar_arrive_elect(lb + B_KS);
    qkv_epi_head<3>(acc0, acc1, cf, nm, k0, pk);
    load_cols<0>(k1, cs);
    load_cols<5>(k0, cs);
    stage_kv(A_STB + wg * 8192 + ko, pk);
    qkv_epi_head<0>(acc0, acc1, cf, nm, k1, pk);
    #pragma unroll
    for (int s = 0; s < 2; s++) {
        qa[4*s] = pk[0][2*s]; qa[4*s+1] = pk[1][2*s]; qa[4*s+2] = pk[0][2*s+1]; qa[4*s+3] = pk[1][2*s+1];
        qb[4*s] = pk[2][2*s]; qb[4*s+1] = pk[3][2*s]; qb[4*s+2] = pk[2][2*s+1]; qb[4*s+3] = pk[3][2*s+1];
    }
    mbar_spin(lb + B_K0, 0);
    {
        constexpr uint64_t dk = desc_plain(A_KP, 2048, 128);
        wg_fence();
        wg_qk_init(SA, qa[0], qa[1], qa[2], qa[3], dk);
        wg_qk_acc(SA, qa[4], qa[5], qa[6], qa[7], dk + 256);
        wg_qk_init(SB_, qb[0], qb[1], qb[2], qb[3], dk);
        wg_commit();
    }
    qkv_epi_head<5>(acc0, acc1, cf, nm, k0, pk);
    load_cols<1>(k1, cs);
    stage_kv(A_STB + 16384 + wg * 8192 + ko, pk);
    qkv_epi_head<1>(acc0, acc1, cf, nm, k1, pk);
    #pragma unroll
    for (int u = 0; u < 2; u++)
        #pragma unroll
        for (int s = 0; s < 2; s++) sts128(A_QX + (u * 2 + s) * 4096 + tid * 16, pk[2*u][2*s], pk[2*u+1][2*s], pk[2*u][2*s+1], pk[2*u+1][2*s+1]);
    fence_async_smem();
    wg_wait<0>();
    pin(SA); pin(SB_);
    TL(128, L * 32 + 5); CK(128, L * 32 + 12);
}

#define PMASK 0x0000AAAAu
#define IMASK 0x10101010u
__host__ __device__ constexpr bool is_poly(int j) { return !((PMASK >> j) & 1); }
#define TBIAS 0x5DEB5DEBu
struct Shift { uint32_t f0, f1, n0, n1, bad; };

__device__ __forceinline__ uint32_t exp2_mufu(uint32_t s, uint32_t nm) {
    uint32_t r;
    asm("ex2.approx.f16x2 %0, %1;" : "=r"(r) : "r"(hadd2(s, nm)));
    return r;
}
__device__ __forceinline__ uint32_t exp2_fix(uint32_t s, uint32_t fm, uint32_t ca, uint32_t& U, bool mul, uint32_t sixteen) {
    uint32_t G, D;
    asm("fma.rn.relu.f16x2 %0, %1, %2, %3;" : "=r"(U) : "r"(s), "r"(0x00400040u), "r"(fm));
    asm("fma.rn.f16x2 %0, %1, %2, %3;" : "=r"(G) : "r"(U & 0x003F003Fu), "r"(ca), "r"(0x98B898B8u));
    asm("{.reg .b32 n; neg.f16x2 n, %1; fma.rn.relu.f16x2 %0, %1, n, %2;}" : "=r"(D) : "r"(G), "r"(0x00570057u));
    if (mul) return U * sixteen - D;
    return (U << 4) - D;
}
__device__ __forceinline__ uint32_t or3(uint32_t a, uint32_t b, uint32_t c) { uint32_t r; asm("lop3.b32 %0, %1, %2, %3, 0xFE;" : "=r"(r) : "r"(a), "r"(b), "r"(c)); return r; }
__device__ __forceinline__ void exp_tile(const uint32_t (&S)[32], uint32_t (&P)[32], Shift& h, uint32_t ca, uint32_t sixteen) {
    uint32_t U[33];
    int n = 0;
    #pragma unroll
    for (int i = 0; i < 32; i++) {
        if (is_poly(i)) P[i] = exp2_fix(S[i], (i & 1) ? h.f1 : h.f0, ca, U[n++], (IMASK >> i) & 1, sixteen);
        else P[i] = exp2_mufu(S[i], (i & 1) ? h.n1 : h.n0);
    }
    U[n] = 0u;
    #pragma unroll
    for (int i = 0; i < 32; i += 6) {
        if (i + 5 <= n) h.bad = or3(h.bad, or3(U[i], U[i + 1], U[i + 2]), or3(U[i + 3], U[i + 4], U[i + 5]));
        else {
            #pragma unroll
            for (int j = i; j < i + 6; j += 2) if (j < n) h.bad = or3(h.bad, U[j], U[j + 1]);
        }
    }
    pin(P);
}
__device__ __forceinline__ uint32_t hfma2(uint32_t a, uint32_t b, uint32_t c) { uint32_t r; asm("fma.rn.f16x2 %0, %1, %2, %3;" : "=r"(r) : "r"(a), "r"(b), "r"(c)); return r; }
__device__ __forceinline__ void unit_start(const uint32_t (&S)[32], Shift& h, uint32_t (&o2)[10]) {
    uint32_t m[4] = {S[0], S[1], S[2], S[3]};
    #pragma unroll
    for (int i = 1; i < 8; i++)
        #pragma unroll
        for (int e = 0; e < 4; e++) m[e] = hmax2(m[e], S[4 * i + e]);
    const uint32_t a = hadd2(m[0], m[2]), c = hadd2(m[1], m[3]);
    uint32_t x = hadd2(__byte_perm(a, c, 0x5410), __byte_perm(a, c, 0x7632));
    x = hadd2(x, __shfl_xor_sync(0xffffffffu, x, 1));
    x = hadd2(x, __shfl_xor_sync(0xffffffffu, x, 2));
    const uint32_t T = hfma2(x, 0xAC00AC00u, TBIAS);
    const uint32_t n = hadd2(T, 0xDE00DE00u), f = hfma2(n, 0x00400040u, 0x03C003C0u);
    h.n0 = __byte_perm(n, 0, 0x1010); h.n1 = __byte_perm(n, 0, 0x3232);
    h.f0 = __byte_perm(f, 0, 0x1010); h.f1 = __byte_perm(f, 0, 0x3232);
    h.bad = T ^ 0x58005800u;
    #pragma unroll
    for (int i = 0; i < 10; i++) o2[i] = 0u;
}
__device__ __forceinline__ uint32_t o_offset() {
    const int c = cta_now(), tid = tid_now();
    return (mt_of(c) * 256 + (tid & 128) + ((tid >> 1) & 48) + ((tid >> 2) & 7)) * (D_ * 2) + nt_of(c) * 64 + (tid & 3) * 16;
}
template <int PASS, int UNIT>
__device__ __forceinline__ void unit_end(const uint32_t (&o)[10], uint32_t bad, uint32_t lb, uint32_t oo, uint32_t& fail, float iv) {
    float v[20];
    #pragma unroll
    for (int i = 0; i < 10; i++) h2_unpack(o[i], v[2 * i], v[2 * i + 1]);
    const float i0 = rcp(v[16]) * iv, i1 = rcp(v[18]) * iv;
    uint32_t r[8], z = 0;
    #pragma unroll
    for (int j = 0; j < 4; j++) {
        r[j] = pack_bf16(v[4*j] * i0, v[4*j+1] * i0); r[4 + j] = pack_bf16(v[4*j+2] * i1, v[4*j+3] * i1);
        z = bfma2(r[j], r[4 + j], z);
    }
    const bool good = o[8] - 0x34003400u < 0x48000000u && o[9] - 0x34003400u < 0x48000000u &&
                      ((bad & 0xF800F800u) | (bmul2(z, 0u) & 0x7FFF7FFFu) | (fail & (1u << (2 * PASS + UNIT)))) == 0;
    const bool all = __all_sync(0xffffffffu, good);
    char* dst = reinterpret_cast<char*>(g_o) + oo + (UNIT * 64 * D_ + PASS * 512) * 2;
    stg128_pred(dst, make_uint4(r[0], r[1], r[2], r[3]), all);
    stg128_pred(dst + 16 * D_, make_uint4(r[4], r[5], r[6], r[7]), all);
    if (__builtin_expect(!all, 0)) {
        fail |= 1u << (2 * PASS + UNIT);
        if (PASS == 0) {
            #pragma unroll
            for (int s = 0; s < 2; s++) g_qsave[cta_now()][UNIT * 2 + s][tid_now()] = lds128(A_KP + (UNIT * 2 + s) * 4096 + tid_now() * 16);
        }
    }
    __syncwarp();
    mbar_arrive_elect_p(lb + PASS * 16, all);
}
__device__ __forceinline__ void swap_q(uint32_t (&q)[8], uint32_t a) {
    asm volatile("{\n.reg .pred p;\nsetp.ne.u32 p, %8, 0;\n"
                 "@p st.shared.v4.b32 [%8 + -8192], {%0, %1, %2, %3};\n@p st.shared.v4.b32 [%8 + -4096], {%4, %5, %6, %7};\n"
                 "@p ld.shared.v4.b32 {%0, %1, %2, %3}, [%8];\n@p ld.shared.v4.b32 {%4, %5, %6, %7}, [%8 + 4096];\n}"
                 : "+r"(q[0]), "+r"(q[1]), "+r"(q[2]), "+r"(q[3]), "+r"(q[4]), "+r"(q[5]), "+r"(q[6]), "+r"(q[7]) : "r"(a) : "memory");
}
static_assert(A_QX == A_KP + 8192, "parking places");
template <bool INIT>
__device__ __forceinline__ void issue_pv(uint32_t (&o)[10], const uint32_t (&P)[32], uint64_t dv) {
    if (INIT) wg_pv_init(o, P[0], P[1], P[2], P[3], dv); else wg_pv_acc(o, P[0], P[1], P[2], P[3], dv);
    #pragma unroll
    for (int k = 1; k < 8; k++) wg_pv_acc(o, P[4*k], P[4*k+1], P[4*k+2], P[4*k+3], dv + k * 16);
}

__device__ __forceinline__ uint4 quad_transpose(uint32_t x0, uint32_t x1, uint32_t x2, uint32_t x3, int t) {
    const bool b0 = t & 1, b1 = t & 2;
    uint32_t s0 = b0 ? x0 : x1, s1 = b0 ? x2 : x3;
    s0 = __shfl_xor_sync(0xffffffffu, s0, 1); s1 = __shfl_xor_sync(0xffffffffu, s1, 1);
    const uint32_t y0 = b0 ? s0 : x0, y1 = b0 ? x1 : s0, y2 = b0 ? s1 : x2, y3 = b0 ? x3 : s1;
    uint32_t u0 = b1 ? y0 : y2, u1 = b1 ? y1 : y3;
    u0 = __shfl_xor_sync(0xffffffffu, u0, 2); u1 = __shfl_xor_sync(0xffffffffu, u1, 2);
    return b1 ? make_uint4(u0, u1, y2, y3) : make_uint4(y0, y1, u0, u1);
}
__device__ __forceinline__ uint32_t movm(uint32_t v) { uint32_t r; asm volatile("movmatrix.sync.aligned.m8n8.trans.b16 %0, %1;" : "=r"(r) : "r"(v)); return r; }
__device__ __forceinline__ void attn_repair(uint32_t lb, int wg, int ow, int pass, int unit) {
    const int tid = tid_now(), w = (tid >> 5) & 3, g = (tid & 31) >> 2, t = tid & 3;
    uint4* const sc = &g_qsave[cta_now()][0][tid & ~96];
    const uint4 qx = __ldcg(sc + (pass * 2 + unit) * 512 + ow * 32), qy = __ldcg(sc + (pass * 2 + unit) * 512 + 256 + ow * 32);
    float ss = ldsf(M_SS + pass * 4);
    if (ss == 0.f) ss = 1.f;
    const uint4 q0 = quad_transpose(qx.x, qx.z, qy.x, qy.z, t), q1 = quad_transpose(qx.y, qx.w, qy.y, qy.w, t);
    const char* kv = g_kv + (size_t)(nt_of(cta_now()) * 2 + pass) * 16 * KV_TILE + t * 2048 + g * 16;
    float o[4][4], m0 = -INFINITY, m1 = -INFINITY, l0 = 0.f, l1 = 0.f;
    #pragma unroll
    for (int j = 0; j < 4; j++) { o[j][0] = 0.f; o[j][1] = 0.f; o[j][2] = 0.f; o[j][3] = 0.f; }
    uint4 kf[8];
    #pragma unroll
    for (int i = 0; i < 8; i++) kf[i] = __ldcg(reinterpret_cast<const uint4*>(kv + ((4 * w - 1) & 15) * KV_TILE + i * 128));
    #pragma unroll 1
    for (int b = 8 * w; b < 8 * w + 8; b++) {
        uint4 vf[8];
        #pragma unroll
        for (int i = 0; i < 8; i++) vf[i] = __ldcg(reinterpret_cast<const uint4*>(kv + (b >> 1) * KV_TILE + (b & 1) * 1024 + 8192 + i * 128));
        float s[8][4];
        #pragma unroll
        for (int i = 0; i < 8; i++) {
            s[i][0] = 0.f; s[i][1] = 0.f; s[i][2] = 0.f; s[i][3] = 0.f;
            mma_f16(s[i], q0.x, q1.x, q0.y, q1.y, kf[i].x, kf[i].y); mma_f16(s[i], q0.z, q1.z, q0.w, q1.w, kf[i].z, kf[i].w);
        }
        #pragma unroll
        for (int i = 0; i < 8; i++) kf[i] = __ldcg(reinterpret_cast<const uint4*>(kv + (((b - 1) >> 1) & 15) * KV_TILE + (~b & 1) * 1024 + i * 128));
        float t0 = m0, t1 = m1;
        #pragma unroll
        for (int i = 0; i < 8; i++) { t0 = fmaxf(t0, fmaxf(s[i][0], s[i][1])); t1 = fmaxf(t1, fmaxf(s[i][2], s[i][3])); }
        t0 = quad_max(t0); t1 = quad_max(t1);
        const float a0 = ex2((m0 - t0) * ss), a1 = ex2((m1 - t1) * ss);
        m0 = t0; m1 = t1;
        l0 *= a0; l1 *= a1;
        #pragma unroll
        for (int j = 0; j < 4; j++) { o[j][0] *= a0; o[j][1] *= a0; o[j][2] *= a1; o[j][3] *= a1; }
        #pragma unroll
        for (int k = 0; k < 4; k++) {
            uint32_t pf[4];
            #pragma unroll
            for (int e = 0; e < 2; e++) {
                const float p0 = ex2((s[2*k+e][0] - m0) * ss), p1 = ex2((s[2*k+e][1] - m0) * ss), p2 = ex2((s[2*k+e][2] - m1) * ss), p3 = ex2((s[2*k+e][3] - m1) * ss);
                l0 += p0 + p1; l1 += p2 + p3;
                pf[2*e] = pack_f16(p0, p1); pf[2*e+1] = pack_f16(p2, p3);
            }
            mma_f16(o[0], pf[0], pf[1], pf[2], pf[3], movm(vf[2*k].x), movm(vf[2*k+1].x));
            mma_f16(o[1], pf[0], pf[1], pf[2], pf[3], movm(vf[2*k].y), movm(vf[2*k+1].y));
            mma_f16(o[2], pf[0], pf[1], pf[2], pf[3], movm(vf[2*k].z), movm(vf[2*k+1].z));
            mma_f16(o[3], pf[0], pf[1], pf[2], pf[3], movm(vf[2*k].w), movm(vf[2*k+1].w));
        }
    }
    sc[24 * 256 + w * 32] = make_uint4(__float_as_uint(m0), __float_as_uint(m1), __float_as_uint(quad_sum(l0)), __float_as_uint(quad_sum(l1)));
    #pragma unroll
    for (int j = 0; j < 4; j++) sc[(25 + j) * 256 + w * 32] = make_uint4(__float_as_uint(o[j][0]), __float_as_uint(o[j][1]), __float_as_uint(o[j][2]), __float_as_uint(o[j][3]));
    named_sync(NB_WG + wg, 128);
    uint4 h[4];
    #pragma unroll
    for (int i = 0; i < 4; i++) { h[i] = __ldcg(sc + 24 * 256 + i * 32); m0 = fmaxf(m0, __uint_as_float(h[i].x)); m1 = fmaxf(m1, __uint_as_float(h[i].y)); }
    float r[4] = {0.f, 0.f, 0.f, 0.f};
    l0 = 0.f; l1 = 0.f;
    #pragma unroll
    for (int i = 0; i < 4; i++) {
        const uint4 v = __ldcg(sc + (25 + w) * 256 + i * 32);
        const float a0 = ex2((__uint_as_float(h[i].x) - m0) * ss), a1 = ex2((__uint_as_float(h[i].y) - m1) * ss);
        l0 = fmaf(a0, __uint_as_float(h[i].z), l0); l1 = fmaf(a1, __uint_as_float(h[i].w), l1);
        r[0] = fmaf(a0, __uint_as_float(v.x), r[0]); r[1] = fmaf(a0, __uint_as_float(v.y), r[1]);
        r[2] = fmaf(a1, __uint_as_float(v.z), r[2]); r[3] = fmaf(a1, __uint_as_float(v.w), r[3]);
    }
    const float iv = 16.f * ldsf(M_IV + pass * 4), i0 = iv * rcp(l0), i1 = iv * rcp(l1);
    uint32_t* dst = reinterpret_cast<uint32_t*>(reinterpret_cast<char*>(g_o) + (o_offset() & ~48u) + ((unit * 64 + (ow - w) * 16) * D_ + pass * 512) * 2) + w * 4 + t;
    dst[0] = pack_bf16(r[0] * i0, r[1] * i0);
    dst[4 * D_] = pack_bf16(r[2] * i1, r[3] * i1);
    named_sync(NB_WG + wg, 128);
    if ((tid & 127) == 0) mbar_arrive(lb + B_OD + (pass * 2 + wg) * 8);
    __syncwarp();
}
__device__ __forceinline__ bool wg_any(bool p, int id) {
    uint32_t r;
    asm volatile("{\n.reg .pred a, b;\nsetp.ne.u32 a, %1, 0;\nbarrier.cta.red.or.aligned.pred b, %2, 128, a;\nselp.u32 %0, 1, 0, b;\n}" : "=r"(r) : "r"((uint32_t)p), "r"(id) : "memory");
    return r != 0;
}

__device__ __forceinline__ void load_gu(uint32_t (&f)[64], uint32_t src, int warp, int lane) {
    const uint32_t row = (warp & 3) * 64 + (lane >> 4) * 8 + (lane & 7), ch = (lane >> 3) & 1, sw = (lane >> 1) & 3;
    const uint32_t a0 = base32(src + (warp >> 2) * 32768 + row * 64 + ((ch ^ sw) << 4)), a1 = base32(a0 ^ 32);
    #pragma unroll
    for (int i = 0; i < 16; i++) ldsm4t(f[4*i], f[4*i+1], f[4*i+2], f[4*i+3], ((i & 1) ? a1 : a0) + ((i >> 1) & 1) * 16384 + (i >> 2) * 1024);
}

__device__ __forceinline__ void arrive_loaded(uint32_t bar, const uint32_t (&f)[64], uint32_t zero) {
    uint32_t x = 0;
    #pragma unroll
    for (int i = 0; i < 16; i++) x |= f[4 * i];
    mbar_arrive_elect(bar + (x & zero));
}
__device__ __forceinline__ void flush(uint32_t (&o2)[10], const uint32_t (&o)[10]) {
    #pragma unroll
    for (int i = 0; i < 10; i++) o2[i] = hadd2(o2[i], o[i]);
}
__device__ __forceinline__ void attention_phase(int L, uint32_t lb, int wg, uint32_t (&qa)[8], uint32_t (&qb)[8], uint32_t (&SA)[32], uint32_t (&SB_)[32], uint64_t dk0, uint64_t dv0, uint32_t ca, uint32_t (&wa)[64], uint32_t zero, uint32_t sixteen) {
    uint32_t PA[32], PB[32], oa[10], ob[10], oa2[10], ob2[10];
    Shift ha, hb;
    uint32_t fail = (lds32(M_SS) ? 3u : 0u) | (lds32(M_SS + 4) ? 12u : 0u);
    ca += base32(fail) >> 4;
    const uint32_t oo = o_offset(), odb = lb + B_OD + wg * 8;
    constexpr uint64_t SL = R_SLOT >> 4, KH = 4096 >> 4;
    uint64_t dkd = dk0 + ((A_KP - A_RING) >> 4);
    unit_start(SA, ha, oa2);
    exp_tile(SA, PA, ha, ca, sixteen);
    #pragma unroll
    for (int i = 0; i < 10; i++) { ob[i] = 0u; ob2[i] = 0u; }
    hb = ha;
    mbar_spin(lb + B_KS, 0);
    mbar_spin(lb + B_ONE, 0);
    #pragma unroll 1
    for (int it = 0; ; it++) {
        const uint32_t ph = it & 1;
        uint32_t qsw = 0;
        #pragma unroll
        for (int u = 0; u < 4; u++) {
            const uint64_t dk = opaque(dk0) + u * SL, dv = opaque(dv0) + u * SL;
            wg_fence();
            if (u == 0) { wg_qk_acc(SB_, qb[4], qb[5], qb[6], qb[7], dkd + KH); wg_commit(); }
            if (u == 0) issue_pv<true>(oa, PA, dv); else issue_pv<false>(oa, PA, dv);
            wg_qk_init(SA, qa[0], qa[1], qa[2], qa[3], dk);
            wg_qk_acc(SA, qa[4], qa[5], qa[6], qa[7], dk + KH);
            wg_commit();
            wg_wait<1>();
            pin(SB_); pin(ob);
            if (u == 0) {
                mbar_arrive_elect_p(lb + B_AE + 24, it);
                flush(ob2, ob);
                if (__builtin_expect((it & 3) == 0, 0)) {
                    if (it) unit_end<0, 1>(ob2, hb.bad, odb, oo, fail, ldsf(M_IV));
                    unit_start(SB_, hb, ob2);
                }
            } else mbar_arrive_elect(lb + B_AE + 8 * (u - 1));
            if (u == 3) swap_q(qb, qsw ? qsw + 8192 : 0u);
            exp_tile(SB_, PB, hb, ca, sixteen);
            wg_fence();
            if (u == 0) issue_pv<true>(ob, PB, dv); else issue_pv<false>(ob, PB, dv);
            wg_qk_init(SB_, qb[0], qb[1], qb[2], qb[3], dk);
            if (u < 3) wg_qk_acc(SB_, qb[4], qb[5], qb[6], qb[7], dk + KH);
            wg_commit();
            wg_wait<1>();
            pin(SA); pin(oa);
            if (u == 2) { qsw = it == 3 ? A_QX + tid_now() * 16 : 0u; swap_q(qa, qsw); }
            if (u == 3) {
                flush(oa2, oa);
                if (__builtin_expect((it & 3) == 3, 0)) {
                    TL(0, L * 32 + 7 + (it >> 2)); CK(0, L * 32 + 1 + (it >> 2));
                    if (it == 7) goto done;
                    unit_end<0, 0>(oa2, ha.bad, odb, oo, fail, ldsf(M_IV));
                    unit_start(SA, ha, oa2);
                }
            }
            exp_tile(SA, PA, ha, ca, sixteen);
            mbar_spin(lb + B_AF + 8 * ((u + 1) & 3), u < 3 ? ph : ph ^ 1);
        }
        wg_wait<0>();
        dkd = dk0 + 3 * SL;
    }
done:
    const float iv = ldsf(M_IV + 4);
    mbar_spin(lb + B_GU, 0);
    load_gu(wa, F_GU0, tid_now() >> 5, tid_now() & 31);
    unit_end<1, 0>(oa2, ha.bad, odb, oo, fail, iv);
    wg_wait<0>();
    pin(ob);
    mbar_arrive_elect(lb + B_AE + 24);
    flush(ob2, ob);
    unit_end<1, 1>(ob2, hb.bad, odb, oo, fail, iv);
    arrive_loaded(lb + B_FG, wa, zero);
    if (__builtin_expect(wg_any(fail != 0, NB_WG + wg), 0)) {
        uint4* const qs = &g_qsave[cta_now()][0][tid_now()];
        qs[4 * 256] = make_uint4(qa[0], qa[1], qa[2], qa[3]); qs[5 * 256] = make_uint4(qa[4], qa[5], qa[6], qa[7]);
        qs[6 * 256] = make_uint4(qb[0], qb[1], qb[2], qb[3]); qs[7 * 256] = make_uint4(qb[4], qb[5], qb[6], qb[7]);
        #pragma unroll
        for (int i = 0; i < 16; i++) qs[(8 + i) * 256] = make_uint4(wa[4*i], wa[4*i+1], wa[4*i+2], wa[4*i+3]);
        sts32(M_SR + (tid_now() >> 5) * 4, fail);
        named_sync(NB_WG + wg, 128);
        #pragma unroll 1
        for (int r = 0; r < 16; r++)
            if ((warp_uniform(lds32(M_SR + wg * 16 + (r & 3) * 4)) >> (r >> 2)) & 1) attn_repair(lb, wg, r & 3, r >> 3, (r >> 2) & 1);
        #pragma unroll
        for (int i = 0; i < 16; i++) { const uint4 v = __ldcg(qs + (8 + i) * 256); wa[4*i] = v.x; wa[4*i+1] = v.y; wa[4*i+2] = v.z; wa[4*i+3] = v.w; }
    }
    TL(0, L * 32 + 9); CK(0, L * 32 + 8);
}

__device__ __forceinline__ void oproj_steps(float (&acc)[64], uint32_t lb, int wg, int k0, int k1) {
    const bool leader = (tid_now() & 127) == 0;
    #pragma unroll 1
    for (int k = k0; k < k1; k++) {
        const uint32_t st = k & 3;
        mbar_spin(lb + B_OF + 8 * st, (k >> 2) & 1);
        const uint64_t da = desc_sw128(o_a(st) + wg * 8192, 16, 1024);
        const uint64_t db = desc_sw128(o_b(st), 8192, 1024);
        wg_fence();
        #pragma unroll
        for (int kk = 0; kk < 4; kk++) wg_gemm_n128(acc, da + kk * 2, db + kk * 128);
        wg_commit();
        wg_wait<1>();
        if (leader && k > 0) mbar_arrive(lb + B_OE + 8 * ((k - 1) & 3));
    }
}

__device__ __forceinline__ uint4 best_of(const uint4& e, int sh, int mask) {
    const uint32_t m = redux_max(e.x), row = redux_min(e.x == m ? e.w : 0x7FFFFFFFu), src = (row >> sh) & mask;
    return make_uint4(m, __shfl_sync(0xffffffffu, e.y, src), __shfl_sync(0xffffffffu, e.z, src), row);
}
__device__ __forceinline__ void load_wd(uint32_t (&wd)[64], uint32_t lb, int warp, int lane) {
    mbar_spin(lb + B_WD, 0);
    const uint32_t a0 = F_WD + warp * 8192 + ((lane >> 4) * 8 + (lane & 7)) * 128, ch = ((lane >> 3) & 1) ^ (lane & 7);
    #pragma unroll
    for (int i = 0; i < 16; i++) ldsm4t(wd[4*i], wd[4*i+1], wd[4*i+2], wd[4*i+3], base32(a0 + ((ch ^ (i & 6)) << 4)) + (i >> 3) * 4096 + (i & 1) * 2048);
}
__device__ __forceinline__ void stage_tile(const uint32_t (&xa)[4], const uint32_t (&xv)[32]) {
    #pragma unroll
    for (int m = 0; m < 8; m++) stsm4(xa[m & 3] + (m < 4 ? YT0 - XT0 : YT1 - XT0), xv[4*m], xv[4*m+1], xv[4*m+2], xv[4*m+3]);
    fence_async_smem();
    __syncwarp();
}

__device__ __forceinline__ void tail_phase(int L, uint32_t lb, int wg, const uint32_t (&wa)[64]) {
    const int c = cta_now(), blk = blk_of(c), cb = cb_of(c), tid = tid_now();
    const int lane = tid & 31, w = (tid >> 5) & 3, g = lane >> 2, t = lane & 3;
    const int lr0 = wg * 64 + w * 16 + g;
    uint32_t xa[4];
    #pragma unroll
    for (int m = 0; m < 4; m++) xa[m] = base32(XT0 + (wg * 64 + w * 16 + (lane & 15)) * 128 + (((lane >> 4) ^ (lane & 7) ^ (2 * m)) << 4));
    uint32_t xv[32];
    const bool ffn = c < NFC;
    uint32_t wb[64], wd[64];
    float own[6];
    {
        float acc[64];
        #pragma unroll
        for (int i = 0; i < 64; i++) acc[i] = 0.f;
        pin(acc);
        float2 rs0 = make_float2(0.f, 0.f), rs1 = rs0;
        if (L) { rs0 = __ldcg(&g_x.rs1[blk * 128 + lr0]); rs1 = __ldcg(&g_x.rs1[blk * 128 + lr0 + 8]); }
        oproj_steps(acc, lb, wg, 0, 8);
        mbar_spin(lb + B_RES, 0);
        #pragma unroll
        for (int m = 0; m < 8; m++) ldsm4(xv[4*m], xv[4*m+1], xv[4*m+2], xv[4*m+3], xa[m & 3] + (m < 4 ? 0 : XT1 - XT0));
        if (L) {
            const int d = (int)lds32(M_RT + 12) - (blk * 128 + lr0);
            const Ln2 k0 = ln2_coef(rs0.y, d == 0 ? 0.f : rsq(rs0.x + LN_EPS)), k1 = ln2_coef(rs1.y, d == 8 ? 0.f : rsq(rs1.x + LN_EPS));
            #pragma unroll
            for (int j = 0; j < 16; j++) { xv[2*j] = add_ln2(xv[2*j], k0); xv[2*j+1] = add_ln2(xv[2*j+1], k1); }
        }
        pin(xv);
        oproj_steps(acc, lb, wg, 8, 16);
        uint32_t wv[16];
        #pragma unroll
        for (int i = 0; i < 4; i++) ldsm4(wv[4*i], wv[4*i+1], wv[4*i+2], wv[4*i+3], (lane & 1) ? M_RED + (lane >> 3) * 16 + i * 64 : M_RED + 256);
        wg_wait<0>();
        pin(acc);
        if ((tid & 127) == 0) mbar_arrive(lb + B_OE + 24);
        TL(0, L * 32 + 11); CK(0, L * 32 + 13);
        float sa[4] = {0.f, 0.f, 0.f, 0.f}, sb[4] = {0.f, 0.f, 0.f, 0.f}, sc[4] = {0.f, 0.f, 0.f, 0.f};
        float sd[4] = {0.f, 0.f, 0.f, 0.f}, se[4] = {0.f, 0.f, 0.f, 0.f};
        #pragma unroll
        for (int m = 0; m < 8; m++) {
            #pragma unroll
            for (int i = 0; i < 4; i++) xv[4*m+i] = badd2(xv[4*m+i], pack_bf16(acc[8*m + 2*i], acc[8*m + 2*i + 1]));
            mma_bf16(sa, xv[4*m], xv[4*m+1], xv[4*m+2], xv[4*m+3], wv[2*m], wv[2*m+1]);
            mma_bf16_k8(sb, xv[4*m], xv[4*m+1], xv[4*m]); mma_bf16_k8(sc, xv[4*m], xv[4*m+1], xv[4*m+1]);
            mma_bf16_k8(sd, xv[4*m+2], xv[4*m+3], xv[4*m+2]); mma_bf16_k8(se, xv[4*m+2], xv[4*m+3], xv[4*m+3]);
        }
        const float q0 = (g & 1) ? sb[1] + sd[1] : sb[0] + sd[0], q1 = (g & 1) ? sc[3] + se[3] : sc[2] + se[2];
        if (t == (g >> 1)) {
            st_x128(&g_x.part[L][blk][cb][lr0], __float_as_uint(sa[0]), __float_as_uint(q0), __float_as_uint(sa[1]), 0u);
            st_x128(&g_x.part[L][blk][cb][lr0 + 8], __float_as_uint(sa[2]), __float_as_uint(q1), __float_as_uint(sa[3]), 0u);
        }
        __syncwarp();
        own[0] = sa[0]; own[1] = __shfl_sync(0xffffffffu, q0, (lane & 28) + (g >> 1)); own[2] = sa[1];
        own[3] = sa[2]; own[4] = __shfl_sync(0xffffffffu, q1, (lane & 28) + (g >> 1)); own[5] = sa[3];
    }
    TL(0, L * 32 + 12);
    load_gu(wb, F_GU1, tid >> 5, lane);
    stage_tile(xa, xv);
    float mean[2], rstd[2], score[2];
    {
        const bool o0 = cb == 2 * t, o1 = cb == 2 * t + 1;
        const uint4* const psrc = &g_x.part[L][blk][2 * t][lr0];
        uint4 p[4];
        uint32_t n = 0;
        #pragma unroll 1
        do {
            p[0] = ld_x128(psrc); p[1] = ld_x128(psrc + 128); p[2] = ld_x128(psrc + 8); p[3] = ld_x128(psrc + 136);
            poll_tick(n);
        } while (warp_any((!o0 && (p[0].w | p[2].w) != 0) || (!o1 && (p[1].w | p[3].w) != 0)));
        mbar_arrive_elect_p(lb + B_XS, L == 0);
        const float ws = ldsf(M_WS);
        #pragma unroll
        for (int h = 0; h < 2; h++) {
            const float su = quad_sum((o0 ? own[3*h] : __uint_as_float(p[2*h].x)) + (o1 ? own[3*h] : __uint_as_float(p[2*h+1].x)));
            const float sq = quad_sum((o0 ? own[3*h+1] : __uint_as_float(p[2*h].y)) + (o1 ? own[3*h+1] : __uint_as_float(p[2*h+1].y)));
            const float sd = quad_sum((o0 ? own[3*h+2] : __uint_as_float(p[2*h].z)) + (o1 ? own[3*h+2] : __uint_as_float(p[2*h+1].z)));
            mean[h] = su * (1.f / D_);
            const float var = fmaxf(sq * (1.f / D_) - mean[h] * mean[h], 0.f);
            rstd[h] = rsq(var + LN_EPS);
            score[h] = rstd[h] * (sd - mean[h] * ws);
            if (L && t == h) { const Ln2 k = ln2_coef(mean[h], rstd[h]); sts128(XT0 + (lr0 + 8 * h) * 16, k.nm, k.rh, k.rl, k.c); }
            if (L == 0 && cb == 0 && t == h) st_x64(&g_x.rs1[blk * 128 + lr0 + 8 * h], __float_as_uint(var), __float_as_uint(mean[h]));
        }
    }
    TL(0, L * 32 + 13);
    uint4 f;
    {
        const uint32_t k0 = order_bits(score[0]), k1 = order_bits(score[1]);
        const bool up = k1 > k0;
        const uint32_t kb = max(k0, k1), row = blk * 128 + lr0 + (up ? 8 : 0), m = redux_max(kb);
        if (redux_min(kb == m ? row : 0x7FFFFFFFu) == row && t == 0) sts128(M_SR + (tid >> 5) * 16, kb, __float_as_uint(up ? mean[1] : mean[0]), __float_as_uint(up ? rstd[1] : rstd[0]), row);
        named_sync(NB_CONS, 256);
        f = best_of(lds128(M_SR + (lane & 7) * 16), 4, 7);
        if (tid < 16) st_x128(&g_x.hdr[L][tid * 8 + cb][blk], f.x, f.y, f.z, f.w);
        const int d = (int)f.w - (blk * 128 + lr0);
        if ((d & ~8) == 0) {
            #pragma unroll
            for (int b = 0; b < 4; b++)
                st_x128(&g_x.cand[L][blk][cb * 64 + b * 16 + t * 4], d ? xv[8*b+1] : xv[8*b], d ? xv[8*b+3] : xv[8*b+2], d ? xv[8*b+5] : xv[8*b+4], d ? xv[8*b+7] : xv[8*b+6]);
        }
        __syncwarp();
    }
    TL(0, L * 32 + 28);
    if (tid == 0) sts32(M_CR, f.w);
    __syncwarp();
    mbar_arrive_elect_p(lb + B_XS, L);
    load_wd(wd, lb, tid >> 5, lane);
    TL(0, L * 32 + 25);
    uint4 e;
    {
        uint32_t n = 0;
        #pragma unroll 1
        do { e = ld_x128(&g_x.hdr[L][blk * 8 + cb][lane & 15]); poll_tick(n); } while (warp_any(e.w == EMPTY && (lane & 15) != blk));
        if ((lane & 15) == blk) e = f;
        e = best_of(e, 7, 15);
    }
    TL(0, L * 32 + 14);
    if (tid == 0) sts128(M_RT + 16 * L, (e.x & 0x80000000u) ? e.x ^ 0x80000000u : ~e.x, e.y, e.z, e.w);
    if (tid == 0) mbar_arrive(lb + B_RT);
    if (ffn) {
        const uint32_t* src = &g_x.cand[L][e.w >> 7][(tid >> 5) * 32 + t * 4];
        const Ln2 kx = ln2_coef(__uint_as_float(e.y), __uint_as_float(e.z));
        uint4 x[4];
        uint32_t n = 0;
        #pragma unroll 1
        do {
            x[0] = ld_x128(src); x[1] = ld_x128(src + 16); x[2] = ld_x128(src + 256); x[3] = ld_x128(src + 272);
            poll_tick(n);
        } while (warp_any(x[0].x == EMPTY || x[1].x == EMPTY || x[2].x == EMPTY || x[3].x == EMPTY));
        TL(0, L * 32 + 15);
        float d[4][4];
        #pragma unroll
        for (int i = 0; i < 4; i++) { d[i][0] = 0.f; d[i][1] = 0.f; d[i][2] = 0.f; d[i][3] = 0.f; }
        #pragma unroll
        for (int k = 0; k < 8; k++) {
            const uint32_t b0 = ln2((k & 1) ? x[k >> 1].z : x[k >> 1].x, kx), b1 = ln2((k & 1) ? x[k >> 1].w : x[k >> 1].y, kx);
            const uint32_t* f = (k < 4 ? wa : wb) + (k & 3) * 16;
            #pragma unroll
            for (int i = 0; i < 4; i++) mma_bf16(d[i], f[4*i], f[4*i+1], f[4*i+2], f[4*i+3], b0, b1);
        }
        #pragma unroll
        for (int h = 0; h < 2; h++) {
            const float a = (t & 1) ? d[1][2*h] : d[0][2*h], b = (t & 1) ? d[3][2*h] : d[2][2*h];
            stsf(M_RED + ((tid >> 5) * 64 + t * 16 + h * 8 + g) * 4, (t & 2) ? b : a);
        }
        named_sync(NB_CONS, 256);
        TL(0, L * 32 + 16);
        float s0 = 0.f, s1 = 0.f;
        #pragma unroll
        for (int i = 0; i < 8; i++) { const float2 v = lds64f(base32(M_RED + lane * 8) + i * 256); s0 += v.x; s1 += v.y; }
        const uint32_t mine = pack_bf16(s0, s1), other = __shfl_xor_sync(0xffffffffu, mine, 16);
        const uint32_t gv = lane < 16 ? mine : other, uv = lane < 16 ? other : mine;
        const float g0 = bf_lo(gv), g1 = bf_hi(gv);
        const uint32_t hv = bmul2(pack_bf16(g0 * rcp(1.f + __expf(-g0)), g1 * rcp(1.f + __expf(-g1))), uv);
        uint32_t hb[4];
        #pragma unroll
        for (int i = 0; i < 4; i++) hb[i] = __shfl_sync(0xffffffffu, hv, 4 * i + t);
        float y[8][4];
        #pragma unroll
        for (int i = 0; i < 8; i++) {
            y[i][0] = 0.f; y[i][1] = 0.f; y[i][2] = 0.f; y[i][3] = 0.f;
            mma_bf16(y[i], wd[8*i], wd[8*i+1], wd[8*i+2], wd[8*i+3], hb[0], hb[1]);
            mma_bf16(y[i], wd[8*i+4], wd[8*i+5], wd[8*i+6], wd[8*i+7], hb[2], hb[3]);
        }
        float* dst = &g_x.ypart[L][(tid >> 5) * 16 + t * 4][c][g];
        #pragma unroll
        for (int i = 0; i < 2; i++)
            #pragma unroll
            for (int h = 0; h < 2; h++) {
                const float a = (t & 1) ? y[2 + i][2*h] : y[i][2*h], b = (t & 1) ? y[6 + i][2*h] : y[4 + i][2*h];
                st_x32(dst + (i * 2 + h) * (NFC * 8), __float_as_uint((t & 2) ? b : a));
            }
    }
    __syncwarp();
    mbar_arrive_elect(lb + B_FD);
    TL(0, L * 32 + 17);
}

__device__ __forceinline__ void qkv_load_w(const Maps& mp, uint32_t dst, int k, uint32_t fb) { tma_load3(dst, &mp.wqkv, nt_of(blockIdx.x) * 64, k * 64, 0, fb); }
__device__ __forceinline__ void qkv_load_x(const CUtensorMap* tx, uint32_t sa, int k, uint32_t fb) {
    #pragma unroll
    for (int a = 0; a < 2; a++) tma_load(sa + a * 16384, tx, k * 64, mt_of(blockIdx.x) * 256 + a * 128, fb);
}
__device__ __forceinline__ void producer_role(const Maps& mp) {
    const int c = blockIdx.x, mt = mt_of(c), nt = nt_of(c), blk = blk_of(c), cb = cb_of(c);
    const uint64_t pol = policy_evict_first();
    #pragma unroll 1
    for (int L = 0; L < 2; L++) {
        const uint32_t lb = M_BAR + L * BAR_SET;
        const CUtensorMap* tx = &mp.x[L];
        mbar_expect_tx(lb + B_SW, 49152);
        if (L == 0) {
            mbar_nap(lb + B_QF, 0);
            qkv_load_w(mp, SD_W, mt * 2, lb + B_SW);
            qkv_load_w(mp, SD_W + 24576, mt * 2 + 1, lb + B_SW);
        }
        {
            uint32_t st = 0, ph = L;
            #pragma unroll 1
            for (int k = L ? 0 : 3; k < 16; k++) {
                mbar_sleep(k < 2 ? M_BAR + (k ? B_FD : B_XS) : lb + B_QE + 8 * st, k < 2 ? 0 : ph);
                const uint32_t fb = lb + B_QF + 8 * st, sa = SB + st * Q_STB;
                mbar_expect_tx(fb, Q_STB);
                qkv_load_w(mp, sa + Q_ABYTES, k, fb);
                if (k == 0) {
                    mbar_nap(M_BAR + B_XD, 0);
                    flags16_wait(g_x.x[mt]);
                    fence_async_global();
                    mbar_nap(M_BAR + B_RT, 0);
                    TL(256, 32);
                }
                qkv_load_x(tx, sa, k, fb);
                if (L && k >= 3 && k < 7) tma_load(SD_W + (k - 3) * 12288, &mp.r, c * 24, (k - 3) * 256, lb + B_SW);
                if (++st == 3) { st = 0; ph ^= 1; }
            }
        }
        mbar_sleep(lb + B_QE, 1);
        TL(256, L * 32 + 26);
        mbar_arrive(lb + B_AF);
        {
            const char* kv = g_kv + (size_t)nt * 32 * KV_TILE;
            const uint8_t* fl = g_x.kv[L][nt * 2];
            __nanosleep(200);
            #pragma unroll 1
            for (int j = 1; j < 4; j++) {
                flag_wait(fl + ((2 * mt + j + 1) & 15));
                fence_async_global();
                const uint32_t bytes = j == 1 ? 8192 : 16384;
                mbar_expect_tx(lb + B_AF + 8 * j, bytes);
                bulk_load(A_RING + j * R_SLOT, kv + ((2 * mt + j) & 15) * KV_TILE, bytes, lb + B_AF + 8 * j);
                if (j == 1) TL(256, L * 32 + 21);
            }
            flags16_wait(fl);
            fence_async_global();
            int t0 = 2 * mt;
            #pragma unroll 1
            for (int it = 1; it < 8; it++) {
                #pragma unroll
                for (int u = 0; u < 4; u++) {
                    const char* src = kv + ((t0 + 4 * it + u) & 15) * KV_TILE;
                    const uint32_t fb = lb + B_AF + 8 * u, dst = A_RING + u * R_SLOT;
                    mbar_nap(lb + B_AE + 8 * u, (it - 1) & 1);
                    mbar_expect_tx(fb, 16384);
                    if (u < 3) bulk_load(dst, src, 16384, fb);
                    else {
                        bulk_load(dst + 8192, src + 8192, 8192, fb);
                        if (it == 3) {
                            flags16_wait(fl + 128);
                            fence_async_global();
                            kv += 16 * KV_TILE; src = kv + 15 * KV_TILE; t0 = 0;
                        }
                        bulk_load(dst, src, 8192, fb);
                    }
                }
            }
        }
        #pragma unroll 1
        for (int it = 0; it < 4; it++) {
            #pragma unroll
            for (int s = 0; s < 4; s++) {
                mbar_spin(lb + (it ? B_OE + 8 * s : s < 2 ? B_AE + 8 + 8 * s : B_FG), it ? (it - 1) & 1 : s < 2);
                const uint32_t fb = lb + B_OF + 8 * s;
                mbar_expect_tx(fb, 32768);
                #pragma unroll
                for (int b = 0; b < 2; b++)
                    tma_load5(o_b(s) + b * 8192, &mp.wo[it >> 1], cb * 128 + b * 64, (it & 1) * 8 + s * 2, fb);
                if (s == 0 && !(it & 1)) {
                    ctr_wait(g_x.o[L][blk][it >> 1], 15);
                    fence_async_global();
                    TL(256, L * 32 + 10);
                }
                tma_load(o_a(s), &mp.o, it * 256 + s * 64, blk * 128, fb);
            }
            if (it == 0) {
                mbar_spin(lb + B_AE + 24, 1);
                mbar_expect_tx(lb + B_RES, 32768);
                tma_load_s(XT0, tx, cb * 128, blk * 128, lb + B_RES, pol);
                tma_load_s(XT1, tx, cb * 128 + 64, blk * 128, lb + B_RES, pol);
            }
        }
        if (c < NFC) {
            #pragma unroll 1
            for (int i = 0; i < 4; i++) {
                mbar_spin(lb + B_OE + 16 + 8 * (i >> 1), 1);
                tma_load3_s(F_WD + i * 16384, &mp.d, 0, c * 32, i * 4, lb + B_WD, pol);
            }
        }
    }
}

__global__ void __launch_bounds__(384, 1) k_all(const __grid_constant__ Maps mp, const bf16* __restrict__ x0, const bf16* __restrict__ wo, const bf16* __restrict__ w_down,
                                                const bf16* __restrict__ w_r, bf16* __restrict__ out, const uint64_t dk0, const uint64_t dv0, const uint32_t ca, const uint32_t zero, const uint32_t sixteen) {
    extern __shared__ __align__(1024) char smem[];
    if (smem_u32(smem) != SB) __trap();
    const int warp = warp_uniform(threadIdx.x >> 5), wg = warp >> 2;
    TL(0, 0);
    if (warp == 8) {
      if (elect_one()) {
        tm_prefetch(&mp.x[0]); tm_prefetch(&mp.wqkv);
        #pragma unroll
        for (int s = 0; s < 3; s++) { mbar_init(M_BAR + B_QF + 8 * s, 1); mbar_init(M_BAR + BAR_SET + B_QF + 8 * s, 1); }
        fence_mbar_init();
        #pragma unroll 1
        for (int s = 0; s < 3; s++) {
            const uint32_t sa = SB + s * Q_STB, fb = M_BAR + B_QF + 8 * s;
            mbar_expect_tx(fb, Q_STB);
            qkv_load_x(&mp.x[0], sa, s, fb);
            qkv_load_w(mp, sa + Q_ABYTES, s, fb);
        }
      }
      __syncwarp();
    } else if (warp > 8) {
        if (elect_one()) {
            const uint32_t o0 = warp == 9 ? B_AF : warp == 10 ? B_QE : B_AE, o1 = warp == 9 ? B_QE : warp == 10 ? B_AE : B_END, cnt = warp == 9 ? 1 : warp == 10 ? 2 : 8;
            #pragma unroll 1
            for (uint32_t o = o0; o < o1; o += 8) { const uint32_t n = o == B_K0 ? 4 : cnt; mbar_init(M_BAR + o, n); mbar_init(M_BAR + BAR_SET + o, n); }
            fence_mbar_init();
        }
        __syncwarp();
    }
    __syncthreads();
    if (wg == 2) {
        reg_dec<40>();
        if (warp > 8) side_role(mp, x0, wo, w_down, w_r, out);
        else if (elect_one()) producer_role(mp);
    } else {
        reg_inc<232>();
        #pragma unroll 1
        for (int L = 0; L < 2; L++) {
            const uint32_t lb = M_BAR + L * BAR_SET;
            uint32_t qa[8], qb[8], sa[32], sb[32], wa[64];
            qkv_phase(L, lb, wg, qa, qb, sa, sb);
            attention_phase(L, lb, wg, qa, qb, sa, sb, dk0, dv0, ca, wa, zero, sixteen);
            tail_phase(L, lb, wg, wa);
        }
    }
}

typedef CUresult (*EncodeFn)(CUtensorMap*, CUtensorMapDataType, cuuint32_t, void*, const cuuint64_t*, const cuuint64_t*, const cuuint32_t*,
                             const cuuint32_t*, CUtensorMapInterleave, CUtensorMapSwizzle, CUtensorMapL2promotion, CUtensorMapFloatOOBfill);

void make_map(EncodeFn enc, CUtensorMap* tm, const void* ptr, int rank, const cuuint64_t* dims, const cuuint64_t* strides, const cuuint32_t* box, CUtensorMapSwizzle sw) {
    const cuuint32_t es[5] = {1, 1, 1, 1, 1};
    enc(tm, CU_TENSOR_MAP_DATA_TYPE_BFLOAT16, rank, const_cast<void*>(ptr), dims, strides, box, es, CU_TENSOR_MAP_INTERLEAVE_NONE, sw,
        box[0] == 64 ? CU_TENSOR_MAP_L2_PROMOTION_L2_128B : CU_TENSOR_MAP_L2_PROMOTION_NONE, CU_TENSOR_MAP_FLOAT_OOB_FILL_NONE);
}
void make_map2(EncodeFn enc, CUtensorMap* tm, const void* ptr, uint64_t cols, uint64_t rows, uint32_t bc, uint32_t br, CUtensorMapSwizzle sw) {
    const cuuint64_t dims[2] = {cols, rows}, strides[1] = {cols * 2};
    const cuuint32_t box[2] = {bc, br};
    make_map(enc, tm, ptr, 2, dims, strides, box, sw);
}

}

extern "C" void kernel_launch(void* const* d_in, const int* in_sizes, int n_in, void* d_out, int out_size) {
    const bf16* x0 = (const bf16*)d_in[0];
    const bf16* wqkv = (const bf16*)d_in[1];
    const bf16* wo = (const bf16*)d_in[2];
    const bf16* w_r = (const bf16*)d_in[4];
    const bf16* w_gate = (const bf16*)d_in[5];
    const bf16* w_up = (const bf16*)d_in[6];
    const bf16* w_down = (const bf16*)d_in[7];

    EncodeFn enc = nullptr;
    cudaDriverEntryPointQueryResult qr;
    cudaGetDriverEntryPoint("cuTensorMapEncodeTiled", (void**)&enc, cudaEnableDefault, &qr);
    void *p_o, *p_x1;
    cudaGetSymbolAddress(&p_o, g_o); cudaGetSymbolAddress(&p_x1, g_x1);
    const CUtensorMapSwizzle S128 = CU_TENSOR_MAP_SWIZZLE_128B, S64 = CU_TENSOR_MAP_SWIZZLE_64B, S0 = CU_TENSOR_MAP_SWIZZLE_NONE;
    Maps mp;
    make_map2(enc, &mp.x[0], x0, D_, S_, 64, 128, S128); make_map2(enc, &mp.x[1], p_x1, D_, S_, 64, 128, S128);
    make_map2(enc, &mp.o, p_o, D_, S_, 64, 128, S128);
    {
        const cuuint64_t dims[3] = {D_, D_, 3}, strides[2] = {3 * D_ * 2, D_ * 2};
        const cuuint32_t box[3] = {64, 64, 3};
        make_map(enc, &mp.wqkv, wqkv, 3, dims, strides, box, S128);
    }
    make_map2(enc, &mp.r, wqkv, 3 * D_, D_, 24, 256, S0);
    make_map2(enc, &mp.g, w_gate, FF, D_, 32, 256, S64); make_map2(enc, &mp.u, w_up, FF, D_, 32, 256, S64);
    for (int p = 0; p < 2; p++) {
        const cuuint64_t dims[5] = {D_, 2, 4, 4, 16}, strides[4] = {D_ * 2, 8 * D_ * 2, 2 * D_ * 2, 64 * D_ * 2};
        const cuuint32_t box[5] = {64, 2, 4, 4, 2};
        make_map(enc, &mp.wo[p], wo + (size_t)p * 32 * D_, 5, dims, strides, box, S128);
    }
    {
        const cuuint64_t dims[3] = {64, FF, 16}, strides[2] = {D_ * 2, 128};
        const cuuint32_t box[3] = {64, 32, 4};
        make_map(enc, &mp.d, w_down, 3, dims, strides, box, S128);
    }
    cudaFuncSetAttribute(k_all, cudaFuncAttributeMaxDynamicSharedMemorySize, K_SMEM);
    k_all<<<128, 384, K_SMEM, cudaStreamPerThread>>>(mp, x0, wo, w_down, w_r, (bf16*)d_out, desc_plain(A_RING, 2048, 128), desc_plain(A_RING + 8192, 128, 2048), 0x64A264A2u, 0u, 16u);
}
```

```cpp
#include <cuda_runtime.h>
#include <cuda_bf16.h>
#include <cuda_fp16.h>
#include <cuda.h>
#include <cudaTypedefs.h>
#include <stdint.h>

namespace {

typedef __nv_bfloat16 bf16;

constexpr int S_ = 2048, D_ = 1024, NH = 32, FF = 3584, NFC = FF / 32;
constexpr float LN_EPS = 1e-5f;
constexpr float QSCALE = 0.17677669529663687f * 1.4426950408889634f;
constexpr uint32_t EMPTY = 0xFFFFFFFFu;

constexpr int KV_TILE = 16384;
__device__ __align__(1024) char g_kv[NH * 16 * KV_TILE];
__device__ __align__(1024) bf16 g_o[S_ * D_];
__device__ __align__(1024) bf16 g_x1[S_ * D_];
__device__ __align__(16) float2 g_cs[8][3 * D_];
__device__ __align__(16) float2 g_rs0[S_];
__device__ uint4 g_qsave[128][29][256];
struct Xchg {
    uint4 part[2][16][8][128];
    float ypart[2][128][NFC][8];
    uint32_t cand[2][16][D_ / 2];
    uint4 hdr[2][128][16];
    float2 rs1[S_];
    float fix[3 * D_];
    uint32_t x2row[D_ / 2];
    uint8_t kv[2][NH][128];
    int o[2][16][2][32];
    uint8_t x[8][128];
};
constexpr int FILL = (sizeof(Xchg) / 128 + 127) / 128 * 8;
union XchgFill { Xchg x; uint4 fill[128][FILL]; };
static_assert(FILL > 768 && FILL <= 1024, "exchange area");
__device__ __align__(128) XchgFill g_u;
#define g_x g_u.x
__device__ int g_pctr;

constexpr uint32_t SMEM_BASE = 1024;

__device__ __forceinline__ int tid_now() { int v; asm volatile("mov.u32 %0, %%tid.x;" : "=r"(v)); return v; }
__device__ __forceinline__ int cta_now() { int v; asm volatile("mov.u32 %0, %%ctaid.x;" : "=r"(v)); return v; }
__device__ __forceinline__ uint64_t opaque(uint64_t v) { uint64_t r; asm volatile("mov.b64 %0, %1;" : "=l"(r) : "l"(v)); return r; }
__device__ __forceinline__ uint32_t base32(uint32_t v) { uint32_t r; asm("mov.b32 %0, %1;" : "=r"(r) : "r"(v)); return r; }
__device__ __forceinline__ uint32_t smem_u32(const void* p) { return (uint32_t)__cvta_generic_to_shared(p); }
__device__ __forceinline__ void mbar_init(uint32_t bar, int cnt) { asm volatile("mbarrier.init.shared::cta.b64 [%0], %1;" :: "r"(bar), "r"(cnt) : "memory"); }
__device__ __forceinline__ void mbar_expect_tx(uint32_t bar, uint32_t bytes) { asm volatile("mbarrier.arrive.expect_tx.shared::cta.b64 _, [%0], %1;" :: "r"(bar), "r"(bytes) : "memory"); }
__device__ __forceinline__ void mbar_arrive(uint32_t bar) { asm volatile("mbarrier.arrive.shared::cta.b64 _, [%0];" :: "r"(bar) : "memory"); }
__device__ __forceinline__ void mbar_sleep(uint32_t bar, uint32_t parity) {
    asm volatile("{\n.reg .pred p;\n.reg .u32 n;\nmov.u32 n, 0;\n"
                 "LAB_WAIT:\nmbarrier.try_wait.parity.shared::cta.b64 p, [%0], %1, 0x10000;\n@p bra LAB_DONE;\n"
                 "add.u32 n, n, 1;\nsetp.lt.u32 p, n, 0x10000;\n@p bra LAB_WAIT;\ntrap;\nLAB_DONE:\n}" :: "r"(bar), "r"(parity) : "memory");
}
__device__ __forceinline__ void mbar_nap(uint32_t bar, uint32_t parity) {
    asm volatile("{\n.reg .pred p;\nLAB_WAIT:\nmbarrier.try_wait.parity.shared::cta.b64 p, [%0], %1, 0x10000;\n@!p bra LAB_WAIT;\n}" :: "r"(bar), "r"(parity) : "memory");
}
__device__ __forceinline__ void mbar_spin(uint32_t bar, uint32_t parity) {
    asm volatile("{\n.reg .pred p;\nLAB_WAIT:\nmbarrier.try_wait.parity.shared::cta.b64 p, [%0], %1;\n@!p bra LAB_WAIT;\n}" :: "r"(bar), "r"(parity) : "memory");
}
__device__ __forceinline__ uint32_t mbar_test(uint32_t bar, uint32_t parity) {
    uint32_t ok;
    asm volatile("{\n.reg .pred p;\nmbarrier.test_wait.parity.shared::cta.b64 p, [%1], %2;\nselp.u32 %0, 1, 0, p;\n}" : "=r"(ok) : "r"(bar), "r"(parity) : "memory");
    return ok;
}
__device__ __forceinline__ bool elect_one() {
    uint32_t r;
    asm volatile("{\n.reg .pred p;\nelect.sync _|p, 0xffffffff;\nselp.u32 %0, 1, 0, p;\n}" : "=r"(r));
    return r != 0;
}
__device__ __forceinline__ void mbar_arrive_elect(uint32_t bar) {
    asm volatile("{\n.reg .pred p;\nelect.sync _|p, 0xffffffff;\n@p mbarrier.arrive.shared::cta.b64 _, [%0];\n}" :: "r"(bar) : "memory");
}
__device__ __forceinline__ void mbar_arrive_elect_p(uint32_t bar, uint32_t on) {
    asm volatile("{\n.reg .pred p, q;\nelect.sync _|p, 0xffffffff;\nsetp.ne.and.u32 q, %1, 0, p;\n@q mbarrier.arrive.shared::cta.b64 _, [%0];\n}" :: "r"(bar), "r"(on) : "memory");
}
__device__ __forceinline__ int warp_uniform(int v) { return __shfl_sync(0xffffffffu, v, 0); }
__device__ __forceinline__ void fence_mbar_init() { asm volatile("fence.mbarrier_init.release.cluster;" ::: "memory"); }
__device__ __forceinline__ void fence_async_smem() { asm volatile("fence.proxy.async.shared::cta;" ::: "memory"); }
__device__ __forceinline__ void fence_async_global() { asm volatile("fence.proxy.async.global;" ::: "memory"); }
__device__ __forceinline__ void named_sync(int id, int n) { asm volatile("bar.sync %0, %1;" :: "r"(id), "r"(n) : "memory"); }
__device__ __forceinline__ void named_arrive(int id, int n) { asm volatile("bar.arrive %0, %1;" :: "r"(id), "r"(n) : "memory"); }
__device__ __forceinline__ void bulk_load(uint32_t dst, const void* src, uint32_t bytes, uint32_t bar) {
    asm volatile("cp.async.bulk.shared::cluster.global.mbarrier::complete_tx::bytes [%0], [%1], %2, [%3];" :: "r"(dst), "l"(src), "r"(bytes), "r"(bar) : "memory");
}
__device__ __forceinline__ void bulk_store(void* dst, uint32_t src, uint32_t bytes) {
    asm volatile("cp.async.bulk.global.shared::cta.bulk_group [%0], [%1], %2;" :: "l"(dst), "r"(src), "r"(bytes) : "memory");
}
__device__ __forceinline__ void bulk_commit() { asm volatile("cp.async.bulk.commit_group;" ::: "memory"); }
__device__ __forceinline__ void bulk_wait() { asm volatile("cp.async.bulk.wait_group 0;" ::: "memory"); }
__device__ __forceinline__ void l2_prefetch(const void* src, uint32_t bytes) {
    asm volatile("cp.async.bulk.prefetch.L2.global [%0], %1;" :: "l"(src), "r"(bytes) : "memory");
}
__device__ __forceinline__ void tma_load(uint32_t dst, const CUtensorMap* tm, int c0, int c1, uint32_t bar) {
    asm volatile("cp.async.bulk.tensor.2d.shared::cluster.global.mbarrier::complete_tx::bytes [%0], [%1, {%3, %4}], [%2];"
                 :: "r"(dst), "l"(tm), "r"(bar), "r"(c0), "r"(c1) : "memory");
}
__device__ __forceinline__ void tma_load3(uint32_t dst, const CUtensorMap* tm, int c0, int c1, int c2, uint32_t bar) {
    asm volatile("cp.async.bulk.tensor.3d.shared::cluster.global.mbarrier::complete_tx::bytes [%0], [%1, {%3, %4, %5}], [%2];"
                 :: "r"(dst), "l"(tm), "r"(bar), "r"(c0), "r"(c1), "r"(c2) : "memory");
}
__device__ __forceinline__ void tma_load5(uint32_t dst, const CUtensorMap* tm, int c0, int c4, uint32_t bar) {
    asm volatile("cp.async.bulk.tensor.5d.shared::cluster.global.mbarrier::complete_tx::bytes [%0], [%1, {%3, %5, %5, %5, %4}], [%2];"
                 :: "r"(dst), "l"(tm), "r"(bar), "r"(c0), "r"(c4), "r"(0) : "memory");
}
__device__ __forceinline__ uint64_t policy_evict_first() { uint64_t p; asm volatile("createpolicy.fractional.L2::evict_first.b64 %0, 1.0;" : "=l"(p)); return p; }
__device__ __forceinline__ void tma_load_s(uint32_t dst, const CUtensorMap* tm, int c0, int c1, uint32_t bar, uint64_t pol) {
    asm volatile("cp.async.bulk.tensor.2d.shared::cluster.global.mbarrier::complete_tx::bytes.L2::cache_hint [%0], [%1, {%3, %4}], [%2], %5;"
                 :: "r"(dst), "l"(tm), "r"(bar), "r"(c0), "r"(c1), "l"(pol) : "memory");
}
__device__ __forceinline__ void tma_load3_s(uint32_t dst, const CUtensorMap* tm, int c0, int c1, int c2, uint32_t bar, uint64_t pol) {
    asm volatile("cp.async.bulk.tensor.3d.shared::cluster.global.mbarrier::complete_tx::bytes.L2::cache_hint [%0], [%1, {%3, %4, %5}], [%2], %6;"
                 :: "r"(dst), "l"(tm), "r"(bar), "r"(c0), "r"(c1), "r"(c2), "l"(pol) : "memory");
}
__device__ __forceinline__ void tma_store(const CUtensorMap* tm, uint32_t src, int c0, int c1) {
    asm volatile("cp.async.bulk.tensor.2d.global.shared::cta.bulk_group [%0, {%2, %3}], [%1];" :: "l"(tm), "r"(src), "r"(c0), "r"(c1) : "memory");
}
__device__ __forceinline__ void tma_prefetch(const CUtensorMap* tm, int c0, int c1) {
    asm volatile("cp.async.bulk.prefetch.tensor.2d.L2.global [%0, {%1, %2}];" :: "l"(tm), "r"(c0), "r"(c1) : "memory");
}
__device__ __forceinline__ void tm_prefetch(const CUtensorMap* tm) { asm volatile("prefetch.tensormap [%0];" :: "l"(tm) : "memory"); }
__device__ __forceinline__ void wg_fence() { asm volatile("wgmma.fence.sync.aligned;" ::: "memory"); }
__device__ __forceinline__ void wg_commit() { asm volatile("wgmma.commit_group.sync.aligned;" ::: "memory"); }
template <int N> __device__ __forceinline__ void wg_wait() { asm volatile("wgmma.wait_group.sync.aligned %0;" :: "n"(N) : "memory"); }
template <int N> __device__ __forceinline__ void pin(uint32_t (&r)[N]) {
    #pragma unroll
    for (int i = 0; i < N; i++) asm volatile("" : "+r"(r[i]) :: "memory");
}
template <int N> __device__ __forceinline__ void pin(float (&r)[N]) {
    #pragma unroll
    for (int i = 0; i < N; i++) asm volatile("" : "+f"(r[i]) :: "memory");
}
template <int N> __device__ __forceinline__ void reg_inc() { asm volatile("setmaxnreg.inc.sync.aligned.u32 %0;" :: "n"(N)); }
template <int N> __device__ __forceinline__ void reg_dec() { asm volatile("setmaxnreg.dec.sync.aligned.u32 %0;" :: "n"(N)); }
__host__ __device__ constexpr uint64_t desc_plain(uint32_t addr, uint32_t lbo, uint32_t sbo) {
    return (uint64_t)((addr & 0x3FFFF) >> 4) | ((uint64_t)(lbo >> 4) << 16) | ((uint64_t)(sbo >> 4) << 32);
}
__host__ __device__ constexpr uint64_t desc_sw128(uint32_t addr, uint32_t lbo, uint32_t sbo) { return desc_plain(addr, lbo, sbo) | (1ull << 62); }
__host__ __device__ constexpr uint64_t desc_sw64(uint32_t addr, uint32_t lbo, uint32_t sbo) { return desc_plain(addr, lbo, sbo) | (2ull << 62); }

__device__ __forceinline__ uint32_t lds32(uint32_t a) { uint32_t v; asm volatile("ld.shared.b32 %0, [%1];" : "=r"(v) : "r"(a) : "memory"); return v; }
__device__ __forceinline__ uint32_t lds16(uint32_t a) { uint32_t v; asm volatile("ld.shared.u16 %0, [%1];" : "=r"(v) : "r"(a) : "memory"); return v; }
__device__ __forceinline__ float ldsf(uint32_t a) { return __uint_as_float(lds32(a)); }
__device__ __forceinline__ float2 lds64f(uint32_t a) { float2 v; asm volatile("ld.shared.v2.f32 {%0, %1}, [%2];" : "=f"(v.x), "=f"(v.y) : "r"(a) : "memory"); return v; }
__device__ __forceinline__ uint4 lds128(uint32_t a) { uint4 v; asm volatile("ld.shared.v4.b32 {%0, %1, %2, %3}, [%4];" : "=r"(v.x), "=r"(v.y), "=r"(v.z), "=r"(v.w) : "r"(a) : "memory"); return v; }
__device__ __forceinline__ void sts16(uint32_t a, uint32_t v) { asm volatile("st.shared.b16 [%0], %1;" :: "r"(a), "h"((uint16_t)v) : "memory"); }
__device__ __forceinline__ void sts32(uint32_t a, uint32_t v) { asm volatile("st.shared.b32 [%0], %1;" :: "r"(a), "r"(v) : "memory"); }
__device__ __forceinline__ void stsf(uint32_t a, float v) { sts32(a, __float_as_uint(v)); }
__device__ __forceinline__ void sts64(uint32_t a, uint32_t x, uint32_t y) { asm volatile("st.shared.v2.b32 [%0], {%1, %2};" :: "r"(a), "r"(x), "r"(y) : "memory"); }
__device__ __forceinline__ void sts128(uint32_t a, uint32_t x, uint32_t y, uint32_t z, uint32_t w) { asm volatile("st.shared.v4.b32 [%0], {%1, %2, %3, %4};" :: "r"(a), "r"(x), "r"(y), "r"(z), "r"(w) : "memory"); }
__device__ __forceinline__ void stsm4(uint32_t a, uint32_t x, uint32_t y, uint32_t z, uint32_t w) {
    asm volatile("stmatrix.sync.aligned.m8n8.x4.shared.b16 [%0], {%1, %2, %3, %4};" :: "r"(a), "r"(x), "r"(y), "r"(z), "r"(w) : "memory");
}
__device__ __forceinline__ void ldsm4(uint32_t& a0, uint32_t& a1, uint32_t& a2, uint32_t& a3, uint32_t addr) {
    asm volatile("ldmatrix.sync.aligned.m8n8.x4.shared.b16 {%0,%1,%2,%3}, [%4];" : "=r"(a0), "=r"(a1), "=r"(a2), "=r"(a3) : "r"(addr) : "memory");
}
__device__ __forceinline__ void ldsm4t(uint32_t& a0, uint32_t& a1, uint32_t& a2, uint32_t& a3, uint32_t addr) {
    asm volatile("ldmatrix.sync.aligned.m8n8.x4.trans.shared.b16 {%0,%1,%2,%3}, [%4];" : "=r"(a0), "=r"(a1), "=r"(a2), "=r"(a3) : "r"(addr) : "memory");
}
__device__ __forceinline__ void mma_bf16(float (&d)[4], uint32_t a0, uint32_t a1, uint32_t a2, uint32_t a3, uint32_t b0, uint32_t b1) {
    asm("mma.sync.aligned.m16n8k16.row.col.f32.bf16.bf16.f32 {%0,%1,%2,%3}, {%4,%5,%6,%7}, {%8,%9}, {%0,%1,%2,%3};"
        : "+f"(d[0]), "+f"(d[1]), "+f"(d[2]), "+f"(d[3]) : "r"(a0), "r"(a1), "r"(a2), "r"(a3), "r"(b0), "r"(b1));
}
__device__ __forceinline__ void mma_bf16_k8(float (&d)[4], uint32_t a0, uint32_t a1, uint32_t b0) {
    asm("mma.sync.aligned.m16n8k8.row.col.f32.bf16.bf16.f32 {%0,%1,%2,%3}, {%4,%5}, {%6}, {%0,%1,%2,%3};"
        : "+f"(d[0]), "+f"(d[1]), "+f"(d[2]), "+f"(d[3]) : "r"(a0), "r"(a1), "r"(b0));
}
__device__ __forceinline__ void mma_f16(float (&d)[4], uint32_t a0, uint32_t a1, uint32_t a2, uint32_t a3, uint32_t b0, uint32_t b1) {
    asm("mma.sync.aligned.m16n8k16.row.col.f32.f16.f16.f32 {%0,%1,%2,%3}, {%4,%5,%6,%7}, {%8,%9}, {%0,%1,%2,%3};"
        : "+f"(d[0]), "+f"(d[1]), "+f"(d[2]), "+f"(d[3]) : "r"(a0), "r"(a1), "r"(a2), "r"(a3), "r"(b0), "r"(b1));
}
__device__ __forceinline__ void stg128_pred(void* p, const uint4& v, bool on) {
    asm volatile("{\n.reg .pred q;\nsetp.ne.u32 q, %5, 0;\n@q st.global.v4.b32 [%0], {%1, %2, %3, %4};\n}"
                 :: "l"(p), "r"(v.x), "r"(v.y), "r"(v.z), "r"(v.w), "r"((uint32_t)on) : "memory");
}
__device__ __forceinline__ void st_x32(void* p, uint32_t v) { asm volatile("st.relaxed.gpu.global.u32 [%0], %1;" :: "l"(p), "r"(v) : "memory"); }
__device__ __forceinline__ void st_x64(void* p, uint32_t x, uint32_t y) {
    asm volatile("{\n.reg .b64 v;\nmov.b64 v, {%1, %2};\nst.relaxed.gpu.global.b64 [%0], v;\n}" :: "l"(p), "r"(x), "r"(y) : "memory");
}
__device__ __forceinline__ void st_x128(void* p, uint32_t x, uint32_t y, uint32_t z, uint32_t w) {
    asm volatile("{\n.reg .b64 a, b;\n.reg .b128 v;\nmov.b64 a, {%1, %2};\nmov.b64 b, {%3, %4};\nmov.b128 v, {a, b};\nst.relaxed.gpu.global.b128 [%0], v;\n}"
                 :: "l"(p), "r"(x), "r"(y), "r"(z), "r"(w) : "memory");
}
__device__ __forceinline__ void st_x128_if(bool on, void* p, uint32_t x, uint32_t y, uint32_t z, uint32_t w) {
    asm volatile("{\n.reg .pred q;\n.reg .b64 a, b;\n.reg .b128 v;\nsetp.ne.u32 q, %5, 0;\nmov.b64 a, {%1, %2};\nmov.b64 b, {%3, %4};\nmov.b128 v, {a, b};\n"
                 "@q st.relaxed.gpu.global.b128 [%0], v;\n}" :: "l"(p), "r"(x), "r"(y), "r"(z), "r"(w), "r"((uint32_t)on) : "memory");
}
__device__ __forceinline__ uint32_t ld_x32(const void* p) { uint32_t v; asm volatile("ld.relaxed.gpu.global.u32 %0, [%1];" : "=r"(v) : "l"(p) : "memory"); return v; }
__device__ __forceinline__ uint2 ld_x64(const void* p) {
    uint2 v; asm volatile("{\n.reg .b64 a;\nld.relaxed.gpu.global.b64 a, [%2];\nmov.b64 {%0, %1}, a;\n}" : "=r"(v.x), "=r"(v.y) : "l"(p) : "memory"); return v;
}
__device__ __forceinline__ uint4 ld_x128(const void* p) {
    uint4 v;
    asm volatile("{\n.reg .b64 a, b;\n.reg .b128 v;\nld.relaxed.gpu.global.b128 v, [%4];\nmov.b128 {a, b}, v;\nmov.b64 {%0, %1}, a;\nmov.b64 {%2, %3}, b;\n}"
                 : "=r"(v.x), "=r"(v.y), "=r"(v.z), "=r"(v.w) : "l"(p) : "memory");
    return v;
}
__device__ __forceinline__ void poll_tick(uint32_t& n) { asm volatile("{\n.reg .pred p;\nadd.u32 %0, %0, 1;\nsetp.ge.u32 p, %0, 0x800000;\n@p st.global.u32 [%1], %0;\n}" : "+r"(n) : "l"(0ull)); }
__device__ __forceinline__ void ctr_arrive(int* c) { asm volatile("red.release.gpu.global.add.s32 [%0], 1;" :: "l"(c) : "memory"); }
__device__ __forceinline__ void ctr_wait(const int* c, int target) {
    int v;
    uint32_t n = 0;
    #pragma unroll 1
    do {
        asm volatile("ld.acquire.gpu.global.s32 %0, [%1];" : "=r"(v) : "l"(c) : "memory");
        poll_tick(n);
    } while (v < target);
}
__device__ __forceinline__ void flag_wait(const uint8_t* f) {
    uint32_t n = 0, v;
    #pragma unroll 1
    do { asm volatile("ld.acquire.gpu.global.u8 %0, [%1];" : "=r"(v) : "l"(f) : "memory"); poll_tick(n); } while (v);
}
__device__ __forceinline__ void flags16_wait(const uint8_t* f) {
    uint32_t n = 0;
    uint64_t v;
    #pragma unroll 1
    do {
        asm volatile("{\n.reg .b64 a, b;\n.reg .b128 v;\nld.acquire.gpu.global.b128 v, [%1];\nmov.b128 {a, b}, v;\nor.b64 %0, a, b;\n}" : "=l"(v) : "l"(f) : "memory");
        poll_tick(n);
    } while (v != 0);
}
__device__ __forceinline__ bool any_empty(const uint4& v) { return v.x == EMPTY || v.y == EMPTY || v.z == EMPTY || v.w == EMPTY; }
__device__ __forceinline__ bool warp_any(bool p) { return __any_sync(0xffffffffu, p); }

__device__ __forceinline__ float ex2(float x) { float y; asm("ex2.approx.ftz.f32 %0, %1;" : "=f"(y) : "f"(x)); return y; }
__device__ __forceinline__ float rsq(float x) { float y; asm("rsqrt.approx.ftz.f32 %0, %1;" : "=f"(y) : "f"(x)); return y; }
__device__ __forceinline__ float rcp(float x) { float y; asm("rcp.approx.ftz.f32 %0, %1;" : "=f"(y) : "f"(x)); return y; }
__device__ __forceinline__ float sigmoid(float x) { return rcp(1.f + ex2(x * -1.4426950408889634f)); }
__device__ __forceinline__ uint32_t pack_bf16(float lo, float hi) { uint32_t r; asm("cvt.rn.bf16x2.f32 %0, %1, %2;" : "=r"(r) : "f"(hi), "f"(lo)); return r; }
__device__ __forceinline__ uint32_t pack_f16(float lo, float hi) { uint32_t r; asm("cvt.rn.f16x2.f32 %0, %1, %2;" : "=r"(r) : "f"(hi), "f"(lo)); return r; }
__device__ __forceinline__ float bf_lo(uint32_t v) { return __uint_as_float(v << 16); }
__device__ __forceinline__ float bf_hi(uint32_t v) { return __uint_as_float(v & 0xFFFF0000u); }
__device__ __forceinline__ float bf_round(float x) { return __uint_as_float(pack_bf16(0.f, x)); }
__device__ __forceinline__ void h2_unpack(uint32_t v, float& lo, float& hi) {
    asm("{.reg .f16 l, h; mov.b32 {l, h}, %2; cvt.f32.f16 %0, l; cvt.f32.f16 %1, h;}" : "=f"(lo), "=f"(hi) : "r"(v));
}
__device__ __forceinline__ uint32_t hadd2(uint32_t a, uint32_t b) { uint32_t r; asm("add.rn.f16x2 %0, %1, %2;" : "=r"(r) : "r"(a), "r"(b)); return r; }
__device__ __forceinline__ uint32_t hmax2(uint32_t a, uint32_t b) { uint32_t r; asm("max.f16x2 %0, %1, %2;" : "=r"(r) : "r"(a), "r"(b)); return r; }
__device__ __forceinline__ uint32_t badd2(uint32_t a, uint32_t b) { uint32_t r; asm("add.rn.bf16x2 %0, %1, %2;" : "=r"(r) : "r"(a), "r"(b)); return r; }
__device__ __forceinline__ uint32_t bmul2(uint32_t a, uint32_t b) { uint32_t r; asm("mul.rn.bf16x2 %0, %1, %2;" : "=r"(r) : "r"(a), "r"(b)); return r; }
__device__ __forceinline__ float warp_sum(float v) {
    #pragma unroll
    for (int o = 16; o > 0; o >>= 1) v += __shfl_xor_sync(0xffffffffu, v, o);
    return v;
}
__device__ __forceinline__ float quad_sum(float v) { v += __shfl_xor_sync(0xffffffffu, v, 1); return v + __shfl_xor_sync(0xffffffffu, v, 2); }
__device__ __forceinline__ float quad_max(float v) { v = fmaxf(v, __shfl_xor_sync(0xffffffffu, v, 1)); return fmaxf(v, __shfl_xor_sync(0xffffffffu, v, 2)); }
__device__ __forceinline__ uint32_t redux_max(uint32_t v) { uint32_t r; asm volatile("redux.sync.max.u32 %0, %1, 0xffffffff;" : "=r"(r) : "r"(v)); return r; }
__device__ __forceinline__ uint32_t redux_min(uint32_t v) { uint32_t r; asm volatile("redux.sync.min.u32 %0, %1, 0xffffffff;" : "=r"(r) : "r"(v)); return r; }
__device__ __forceinline__ uint32_t order_bits(float r) { const uint32_t u = __float_as_uint(r); return (u & 0x80000000u) ? ~u : (u | 0x80000000u); }
struct Ln2 { uint32_t nm, rh, rl, c; };
__device__ __forceinline__ Ln2 ln2_coef(float mean, float rstd) {
    const uint32_t a = pack_bf16(-mean, rstd), b = pack_bf16((-mean - bf_lo(a)) * rstd, rstd - bf_hi(a));
    return {__byte_perm(a, 0, 0x1010), __byte_perm(a, 0, 0x3232), __byte_perm(b, 0, 0x3232), __byte_perm(b, 0, 0x1010)};
}
__device__ __forceinline__ uint32_t bfma2(uint32_t a, uint32_t b, uint32_t c) { uint32_t r; asm("fma.rn.bf16x2 %0, %1, %2, %3;" : "=r"(r) : "r"(a), "r"(b), "r"(c)); return r; }
__device__ __forceinline__ uint32_t ln2(uint32_t v, const Ln2& k) { const uint32_t d = badd2(v, k.nm); return bfma2(d, k.rh, bfma2(d, k.rl, k.c)); }
__device__ __forceinline__ uint32_t add_ln2(uint32_t v, const Ln2& k) { return badd2(v, ln2(v, k)); }

#define TL(TID, i)
#define CK(TID, i)

__device__ __forceinline__ void wg_gemm_n128(float (&d)[64], uint64_t desca, uint64_t desc) {
    asm volatile("{\n.reg .pred p;\nsetp.ne.b32 p, 1, 0;\n"
        "wgmma.mma_async.sync.aligned.m64n128k16.f32.bf16.bf16 "
        "{%0,%1,%2,%3,%4,%5,%6,%7,%8,%9,%10,%11,%12,%13,%14,%15,%16,%17,%18,%19,%20,%21,%22,%23,%24,%25,%26,%27,%28,%29,%30,%31,%32,%33,%34,%35,%36,%37,%38,%39,%40,%41,%42,%43,%44,%45,%46,%47,%48,%49,%50,%51,%52,%53,%54,%55,%56,%57,%58,%59,%60,%61,%62,%63}, "
        "%64, %65, p, 1, 1, 0, 1;\n}\n"
        : "+f"(d[0]), "+f"(d[1]), "+f"(d[2]), "+f"(d[3]), "+f"(d[4]), "+f"(d[5]), "+f"(d[6]), "+f"(d[7]), "+f"(d[8]), "+f"(d[9]), "+f"(d[10]), "+f"(d[11]),
          "+f"(d[12]), "+f"(d[13]), "+f"(d[14]), "+f"(d[15]), "+f"(d[16]), "+f"(d[17]), "+f"(d[18]), "+f"(d[19]), "+f"(d[20]), "+f"(d[21]), "+f"(d[22]), "+f"(d[23]),
          "+f"(d[24]), "+f"(d[25]), "+f"(d[26]), "+f"(d[27]), "+f"(d[28]), "+f"(d[29]), "+f"(d[30]), "+f"(d[31]), "+f"(d[32]), "+f"(d[33]), "+f"(d[34]), "+f"(d[35]),
          "+f"(d[36]), "+f"(d[37]), "+f"(d[38]), "+f"(d[39]), "+f"(d[40]), "+f"(d[41]), "+f"(d[42]), "+f"(d[43]), "+f"(d[44]), "+f"(d[45]), "+f"(d[46]), "+f"(d[47]),
          "+f"(d[48]), "+f"(d[49]), "+f"(d[50]), "+f"(d[51]), "+f"(d[52]), "+f"(d[53]), "+f"(d[54]), "+f"(d[55]), "+f"(d[56]), "+f"(d[57]), "+f"(d[58]), "+f"(d[59]),
          "+f"(d[60]), "+f"(d[61]), "+f"(d[62]), "+f"(d[63])
        : "l"(desca), "l"(desc));
}
__device__ __forceinline__ void wg_gemm_n192(float (&d)[96], uint64_t desca, uint64_t desc) {
    asm volatile("{\n.reg .pred p;\nsetp.ne.b32 p, 1, 0;\n"
        "wgmma.mma_async.sync.aligned.m64n192k16.f32.bf16.bf16 "
        "{%0,%1,%2,%3,%4,%5,%6,%7,%8,%9,%10,%11,%12,%13,%14,%15,%16,%17,%18,%19,%20,%21,%22,%23,%24,%25,%26,%27,%28,%29,%30,%31,%32,%33,%34,%35,%36,%37,%38,%39,%40,%41,%42,%43,%44,%45,%46,%47,%48,%49,%50,%51,%52,%53,%54,%55,%56,%57,%58,%59,%60,%61,%62,%63,%64,%65,%66,%67,%68,%69,%70,%71,%72,%73,%74,%75,%76,%77,%78,%79,%80,%81,%82,%83,%84,%85,%86,%87,%88,%89,%90,%91,%92,%93,%94,%95}, "
        "%96, %97, p, 1, 1, 0, 1;\n}\n"
        : "+f"(d[0]), "+f"(d[1]), "+f"(d[2]), "+f"(d[3]), "+f"(d[4]), "+f"(d[5]), "+f"(d[6]), "+f"(d[7]), "+f"(d[8]), "+f"(d[9]), "+f"(d[10]), "+f"(d[11]),
          "+f"(d[12]), "+f"(d[13]), "+f"(d[14]), "+f"(d[15]), "+f"(d[16]), "+f"(d[17]), "+f"(d[18]), "+f"(d[19]), "+f"(d[20]), "+f"(d[21]), "+f"(d[22]), "+f"(d[23]),
          "+f"(d[24]), "+f"(d[25]), "+f"(d[26]), "+f"(d[27]), "+f"(d[28]), "+f"(d[29]), "+f"(d[30]), "+f"(d[31]), "+f"(d[32]), "+f"(d[33]), "+f"(d[34]), "+f"(d[35]),
          "+f"(d[36]), "+f"(d[37]), "+f"(d[38]), "+f"(d[39]), "+f"(d[40]), "+f"(d[41]), "+f"(d[42]), "+f"(d[43]), "+f"(d[44]), "+f"(d[45]), "+f"(d[46]), "+f"(d[47]),
          "+f"(d[48]), "+f"(d[49]), "+f"(d[50]), "+f"(d[51]), "+f"(d[52]), "+f"(d[53]), "+f"(d[54]), "+f"(d[55]), "+f"(d[56]), "+f"(d[57]), "+f"(d[58]), "+f"(d[59]),
          "+f"(d[60]), "+f"(d[61]), "+f"(d[62]), "+f"(d[63]), "+f"(d[64]), "+f"(d[65]), "+f"(d[66]), "+f"(d[67]), "+f"(d[68]), "+f"(d[69]), "+f"(d[70]), "+f"(d[71]),
          "+f"(d[72]), "+f"(d[73]), "+f"(d[74]), "+f"(d[75]), "+f"(d[76]), "+f"(d[77]), "+f"(d[78]), "+f"(d[79]), "+f"(d[80]), "+f"(d[81]), "+f"(d[82]), "+f"(d[83]),
          "+f"(d[84]), "+f"(d[85]), "+f"(d[86]), "+f"(d[87]), "+f"(d[88]), "+f"(d[89]), "+f"(d[90]), "+f"(d[91]), "+f"(d[92]), "+f"(d[93]), "+f"(d[94]), "+f"(d[95])
        : "l"(desca), "l"(desc));
}
__device__ __forceinline__ void wg_gemm_n192_init(float (&d)[96], uint64_t desca, uint64_t desc) {
    asm volatile("{\n.reg .pred p;\nsetp.ne.b32 p, 0, 0;\n"
        "wgmma.mma_async.sync.aligned.m64n192k16.f32.bf16.bf16 "
        "{%0,%1,%2,%3,%4,%5,%6,%7,%8,%9,%10,%11,%12,%13,%14,%15,%16,%17,%18,%19,%20,%21,%22,%23,%24,%25,%26,%27,%28,%29,%30,%31,%32,%33,%34,%35,%36,%37,%38,%39,%40,%41,%42,%43,%44,%45,%46,%47,%48,%49,%50,%51,%52,%53,%54,%55,%56,%57,%58,%59,%60,%61,%62,%63,%64,%65,%66,%67,%68,%69,%70,%71,%72,%73,%74,%75,%76,%77,%78,%79,%80,%81,%82,%83,%84,%85,%86,%87,%88,%89,%90,%91,%92,%93,%94,%95}, "
        "%96, %97, p, 1, 1, 0, 1;\n}\n"
        : "=f"(d[0]), "=f"(d[1]), "=f"(d[2]), "=f"(d[3]), "=f"(d[4]), "=f"(d[5]), "=f"(d[6]), "=f"(d[7]), "=f"(d[8]), "=f"(d[9]), "=f"(d[10]), "=f"(d[11]),
          "=f"(d[12]), "=f"(d[13]), "=f"(d[14]), "=f"(d[15]), "=f"(d[16]), "=f"(d[17]), "=f"(d[18]), "=f"(d[19]), "=f"(d[20]), "=f"(d[21]), "=f"(d[22]), "=f"(d[23]),
          "=f"(d[24]), "=f"(d[25]), "=f"(d[26]), "=f"(d[27]), "=f"(d[28]), "=f"(d[29]), "=f"(d[30]), "=f"(d[31]), "=f"(d[32]), "=f"(d[33]), "=f"(d[34]), "=f"(d[35]),
          "=f"(d[36]), "=f"(d[37]), "=f"(d[38]), "=f"(d[39]), "=f"(d[40]), "=f"(d[41]), "=f"(d[42]), "=f"(d[43]), "=f"(d[44]), "=f"(d[45]), "=f"(d[46]), "=f"(d[47]),
          "=f"(d[48]), "=f"(d[49]), "=f"(d[50]), "=f"(d[51]), "=f"(d[52]), "=f"(d[53]), "=f"(d[54]), "=f"(d[55]), "=f"(d[56]), "=f"(d[57]), "=f"(d[58]), "=f"(d[59]),
          "=f"(d[60]), "=f"(d[61]), "=f"(d[62]), "=f"(d[63]), "=f"(d[64]), "=f"(d[65]), "=f"(d[66]), "=f"(d[67]), "=f"(d[68]), "=f"(d[69]), "=f"(d[70]), "=f"(d[71]),
          "=f"(d[72]), "=f"(d[73]), "=f"(d[74]), "=f"(d[75]), "=f"(d[76]), "=f"(d[77]), "=f"(d[78]), "=f"(d[79]), "=f"(d[80]), "=f"(d[81]), "=f"(d[82]), "=f"(d[83]),
          "=f"(d[84]), "=f"(d[85]), "=f"(d[86]), "=f"(d[87]), "=f"(d[88]), "=f"(d[89]), "=f"(d[90]), "=f"(d[91]), "=f"(d[92]), "=f"(d[93]), "=f"(d[94]), "=f"(d[95])
        : "l"(desca), "l"(desc));
}
__device__ __forceinline__ void wg_qk_init(uint32_t (&d)[32], uint32_t a0, uint32_t a1, uint32_t a2, uint32_t a3, uint64_t desc) {
    asm volatile("{\n.reg .pred p;\nsetp.ne.b32 p, 0, 0;\n"
        "wgmma.mma_async.sync.aligned.m64n128k16.f16.f16.f16 "
        "{%0,%1,%2,%3,%4,%5,%6,%7,%8,%9,%10,%11,%12,%13,%14,%15,%16,%17,%18,%19,%20,%21,%22,%23,%24,%25,%26,%27,%28,%29,%30,%31}, "
        "{%32,%33,%34,%35}, %36, p, 1, 1, 0;\n}\n"
        : "=r"(d[0]), "=r"(d[1]), "=r"(d[2]), "=r"(d[3]), "=r"(d[4]), "=r"(d[5]), "=r"(d[6]), "=r"(d[7]), "=r"(d[8]), "=r"(d[9]), "=r"(d[10]), "=r"(d[11]),
          "=r"(d[12]), "=r"(d[13]), "=r"(d[14]), "=r"(d[15]), "=r"(d[16]), "=r"(d[17]), "=r"(d[18]), "=r"(d[19]), "=r"(d[20]), "=r"(d[21]), "=r"(d[22]), "=r"(d[23]),
          "=r"(d[24]), "=r"(d[25]), "=r"(d[26]), "=r"(d[27]), "=r"(d[28]), "=r"(d[29]), "=r"(d[30]), "=r"(d[31])
        : "r"(a0), "r"(a1), "r"(a2), "r"(a3), "l"(desc));
}
__device__ __forceinline__ void wg_qk_acc(uint32_t (&d)[32], uint32_t a0, uint32_t a1, uint32_t a2, uint32_t a3, uint64_t desc) {
    asm volatile("{\n.reg .pred p;\nsetp.ne.b32 p, 1, 0;\n"
        "wgmma.mma_async.sync.aligned.m64n128k16.f16.f16.f16 "
        "{%0,%1,%2,%3,%4,%5,%6,%7,%8,%9,%10,%11,%12,%13,%14,%15,%16,%17,%18,%19,%20,%21,%22,%23,%24,%25,%26,%27,%28,%29,%30,%31}, "
        "{%32,%33,%34,%35}, %36, p, 1, 1, 0;\n}\n"
        : "+r"(d[0]), "+r"(d[1]), "+r"(d[2]), "+r"(d[3]), "+r"(d[4]), "+r"(d[5]), "+r"(d[6]), "+r"(d[7]), "+r"(d[8]), "+r"(d[9]), "+r"(d[10]), "+r"(d[11]),
          "+r"(d[12]), "+r"(d[13]), "+r"(d[14]), "+r"(d[15]), "+r"(d[16]), "+r"(d[17]), "+r"(d[18]), "+r"(d[19]), "+r"(d[20]), "+r"(d[21]), "+r"(d[22]), "+r"(d[23]),
          "+r"(d[24]), "+r"(d[25]), "+r"(d[26]), "+r"(d[27]), "+r"(d[28]), "+r"(d[29]), "+r"(d[30]), "+r"(d[31])
        : "r"(a0), "r"(a1), "r"(a2), "r"(a3), "l"(desc));
}
__device__ __forceinline__ void wg_pv_init(uint32_t (&d)[10], uint32_t a0, uint32_t a1, uint32_t a2, uint32_t a3, uint64_t desc) {
    asm volatile("{\n.reg .pred p;\nsetp.ne.b32 p, 0, 0;\n"
        "wgmma.mma_async.sync.aligned.m64n40k16.f16.f16.f16 "
        "{%0,%1,%2,%3,%4,%5,%6,%7,%8,%9}, "
        "{%10,%11,%12,%13}, %14, p, 1, 1, 1;\n}\n"
        : "=r"(d[0]), "=r"(d[1]), "=r"(d[2]), "=r"(d[3]), "=r"(d[4]), "=r"(d[5]), "=r"(d[6]), "=r"(d[7]), "=r"(d[8]), "=r"(d[9])
        : "r"(a0), "r"(a1), "r"(a2), "r"(a3), "l"(desc));
}
__device__ __forceinline__ void wg_pv_acc(uint32_t (&d)[10], uint32_t a0, uint32_t a1, uint32_t a2, uint32_t a3, uint64_t desc) {
    asm volatile("{\n.reg .pred p;\nsetp.ne.b32 p, 1, 0;\n"
        "wgmma.mma_async.sync.aligned.m64n40k16.f16.f16.f16 "
        "{%0,%1,%2,%3,%4,%5,%6,%7,%8,%9}, "
        "{%10,%11,%12,%13}, %14, p, 1, 1, 1;\n}\n"
        : "+r"(d[0]), "+r"(d[1]), "+r"(d[2]), "+r"(d[3]), "+r"(d[4]), "+r"(d[5]), "+r"(d[6]), "+r"(d[7]), "+r"(d[8]), "+r"(d[9])
        : "r"(a0), "r"(a1), "r"(a2), "r"(a3), "l"(desc));
}

constexpr uint32_t SB = SMEM_BASE;
constexpr uint32_t R_SLOT = 18432, A_RING = SB, A_KP = SB + 73728, A_QX = SB + 81920, A_STB = SB + 98304;
constexpr uint32_t F_GU0 = SB + 98304, F_GU1 = SB + 163840, F_WD = F_GU0;
__host__ __device__ constexpr uint32_t o_a(uint32_t s) { return s == 0 ? SB : s == 1 ? A_QX : F_GU0 + (s - 2) * 32768; }
__host__ __device__ constexpr uint32_t o_b(uint32_t s) { return s < 2 ? SB + 16384 + s * 16384 : F_GU0 + 16384 + (s - 2) * 32768; }
constexpr uint32_t XT0 = SB + 49152, XT1 = XT0 + 16384, YT0 = o_a(0), YT1 = o_a(1);
constexpr uint32_t Q_ABYTES = 256 * 64 * 2, Q_STB = Q_ABYTES + 192 * 64 * 2;
constexpr uint32_t Q_CS = SB + 3 * Q_STB, Q_RC = Q_CS + 768, Q_FIX = Q_RC + 2048;
constexpr uint32_t SD_VEC = SB + 176128, SD_W = SB + 180224;
static_assert(Q_FIX + 768 <= SD_VEC, "smem");
constexpr uint32_t M_RED = SB + 229376, M_BAR = M_RED + 2048, BAR_SET = 336, M_HS = M_BAR + 2 * BAR_SET, M_SM = M_HS + 128;
constexpr uint32_t M_IV = M_SM;
constexpr uint32_t M_WS = M_SM + 16;
constexpr uint32_t M_CR = M_SM + 20;
constexpr uint32_t M_SS = M_SM + 24;
constexpr uint32_t M_RT = M_SM + 32;
constexpr uint32_t M_SR = M_SM + 96;
constexpr int K_SMEM = M_SR + 128 - SB;
static_assert(K_SMEM == 232448, "smem");
constexpr uint32_t B_QF = 0, B_AF = 24, B_OF = 56, B_RES = 88, B_GU = 96, B_WD = 104, B_RT = 112, B_SW = 120, B_ONE = 128, B_XD = 136, B_QE = 144, B_OE = 168,
                   B_PX = 200, B_AE = 224, B_OD = 256, B_FG = 288, B_FD = 296, B_XS = 304, B_KS = 312, B_K0 = 320, B_END = 328;
constexpr int NB_ML = 1, NB_CONS = 2, NB_SIDE = 3, NB_EPI = 4, NB_WG = 6;

__device__ __forceinline__ int mt_of(int c) { return (c >> 2) & 7; }
__device__ __forceinline__ int nt_of(int c) { return (c >> 5) * 4 + (c & 3); }
__device__ __forceinline__ int blk_of(int c) { return c >> 3; }
__device__ __forceinline__ int cb_of(int c) { return c & 7; }

struct Maps { CUtensorMap x[2], wqkv, o, wo[2], r, g, u, d; };

template <int N>
__device__ __forceinline__ void halve(float (&v)[8], int lane, int bit) {
    const bool up = lane & bit;
    #pragma unroll
    for (int i = 0; i < N; i++) v[i] = (up ? v[N + i] : v[i]) + __shfl_xor_sync(0xffffffffu, up ? v[i] : v[N + i], bit);
}

__device__ __forceinline__ void reset_exchange(int c, int t) {
    #pragma unroll 1
    for (int i = t; i < FILL; i += 96) g_u.fill[c][i] = make_uint4(EMPTY, EMPTY, EMPTY, EMPTY);
}
__device__ __forceinline__ void prep_work(const bf16* __restrict__ x0, const bf16* __restrict__ w_r, uint32_t lb) {
    const int t = tid_now() - 288, c = cta_now(), lane = t & 31, warp = warp_uniform(t >> 5);
    const uint32_t wb = SD_W + warp * 8192;
    mbar_nap(lb + B_SW, 0);
    {
        float cs[8], cq[8];
        #pragma unroll
        for (int i = 0; i < 8; i++) { cs[i] = 0.f; cq[i] = 0.f; }
        #pragma unroll 1
        for (int h = 0; h < 2; h++) {
            #pragma unroll 2
            for (int r = 0; r < 16; r++) {
                const uint4 u = lds128(wb + h * 24576 + (lane >> 3) * 128 + r * 512 + (((lane & 7) ^ ((r * 4 + (lane >> 3)) & 7)) << 4));
                const uint32_t w[4] = {u.x, u.y, u.z, u.w};
                #pragma unroll
                for (int e = 0; e < 4; e++) {
                    const float a = bf_lo(w[e]), b = bf_hi(w[e]);
                    cs[2*e] += a; cs[2*e+1] += b; cq[2*e] = fmaf(a, a, cq[2*e]); cq[2*e+1] = fmaf(b, b, cq[2*e+1]);
                }
            }
            fence_async_smem();
            __syncwarp();
            if (elect_one()) {
                const uint32_t bytes = h == 0 ? 8192 : warp < 2 ? 4096 : 2048;
                mbar_expect_tx(lb + B_PX + warp * 8, bytes);
                bulk_load(wb + h * 24576, h && warp == 2 ? w_r : x0 + (size_t)(c * 16 + (h ? 12 + warp * 2 : warp * 4)) * D_, bytes, lb + B_PX + warp * 8);
            }
            __syncwarp();
        }
        halve<4>(cs, lane, 16); halve<2>(cs, lane, 8);
        halve<4>(cq, lane, 16); halve<2>(cq, lane, 8);
        *reinterpret_cast<float4*>(&g_cs[mt_of(c)][warp * D_ + nt_of(c) * 64 + (lane & 7) * 8 + (lane >> 3) * 2]) = make_float4(cs[0], cq[0], cs[1], cq[1]);
    }
    TL(288, 22);
    reset_exchange(c, t);
    mbar_nap(lb + B_PX + warp * 8, 0);
    #pragma unroll 1
    for (int i = 0; i < (warp < 2 ? 6 : 5); i++) {
        const int r = i < 4 ? warp * 4 + i : 8 + warp * 2 + i;
        float s0 = 0.f, s1 = 0.f, q0 = 0.f, q1 = 0.f;
        #pragma unroll 2
        for (int j = 0; j < 4; j++) {
            const uint4 u = lds128(wb + (i >> 2) * 16384 + i * 2048 + j * 512 + lane * 16);
            const uint32_t w[4] = {u.x, u.y, u.z, u.w};
            #pragma unroll
            for (int e = 0; e < 4; e++) { const float a = bf_lo(w[e]), b = bf_hi(w[e]); s0 += a; s1 += b; q0 = fmaf(a, a, q0); q1 = fmaf(b, b, q1); }
        }
        s0 += s1; q0 += q1;
        float v = (lane & 16 ? q0 : s0) + __shfl_xor_sync(0xffffffffu, lane & 16 ? s0 : q0, 16);
        #pragma unroll
        for (int o = 8; o > 0; o >>= 1) v += __shfl_xor_sync(0xffffffffu, v, o);
        const float mean = v * (1.f / D_), sq = __shfl_xor_sync(0xffffffffu, mean, 16);
        if (lane == 0) {
            if (r < 16) g_rs0[c * 16 + r] = make_float2(fmaxf(sq - mean * mean, 0.f), mean);
            else stsf(M_WS, v);
        }
    }
    named_sync(NB_SIDE, 96);
    if (t == 0) { TL(288, 23); ctr_arrive(&g_pctr); ctr_wait(&g_pctr, 128); TL(288, 24); }
    named_sync(NB_SIDE, 96);
}

__device__ __forceinline__ int half_exp(uint32_t bits, int off) { return min(max((((int)(bits >> 23) - 125) >> 1) + off, -55), 55); }
__device__ __forceinline__ float pow2(int e) { return __uint_as_float((uint32_t)(127 + e) << 23); }
__device__ __forceinline__ void head_scales(int h) {
    const float fq = ldsf(M_SR + h * 4), fk = ldsf(M_SR + 8 + h * 4);
    const uint32_t vmax = lds32(M_SR + 16 + h * 4), vmin = lds32(M_SR + 24 + h * 4);
    const bool ok = fq <= 16384.f && fk <= 16384.f && fq * fk <= 50000.f && vmax <= vmin + (12u << 23);
    const int a = ok ? 0 : half_exp(__float_as_uint(fq), -8), b = ok ? 0 : half_exp(__float_as_uint(fk), -8), v = half_exp(vmax, ok ? 3 : -10);
    stsf(M_HS + h * 4, QSCALE * pow2(-a)); stsf(M_HS + 8 + h * 4, pow2(-b)); stsf(M_HS + 16 + h * 4, pow2(-v));
    stsf(M_SS + h * 4, ok ? 0.f : pow2(a + b));
    stsf(M_IV + h * 4, pow2(v - 4));
}

__device__ __forceinline__ void epi_inputs(int L, const bf16* __restrict__ w_r) {
    const int t = tid_now() - 288, c = cta_now(), mt = mt_of(c), nt = nt_of(c), lane = t & 31;
    const uint32_t wr = t < 64 ? __ldg(reinterpret_cast<const uint32_t*>(w_r) + cb_of(c) * 64 + t) : 0x3F803F80u;
    #pragma unroll 1
    for (int k = 0; k < 3; k++) {
        const int i = t + 96 * k, col = (i >> 6) * D_ + nt * 64 + (i & 63);
        const float2* rsp = (L ? g_x.rs1 : g_rs0) + mt * 256 + (i & 255);
        uint2 sv = ld_x64(rsp);
        if (k < 2) {
            float2 p[8];
            #pragma unroll
            for (int j = 0; j < 8; j++) p[j] = __ldcg(&g_cs[j][col]);
            stsf(Q_CS + i * 4, ((p[0].x + p[1].x) + (p[2].x + p[3].x)) + ((p[4].x + p[5].x) + (p[6].x + p[7].x)));
            const float zz = ((p[0].y + p[1].y) + (p[2].y + p[3].y)) + ((p[4].y + p[5].y) + (p[6].y + p[7].y));
            const float zs = warp_sum(zz);
            const uint32_t zb = __float_as_uint(zz), zmax = redux_max(zb), zmin = redux_min(zb ? zb : 0x7F800000u);
            if (lane == 0) {
                sts32(M_SR + (i >> 5) * 4, i < 128 ? __float_as_uint(zs) : zmax);
                if (i >= 128) sts32(M_SR + 8 + (i >> 5) * 4, zmin);
            }
        } else {
            named_sync(NB_SIDE, 96);
            if (t < 2) head_scales(t);
            __syncwarp();
        }
        uint32_t n = 0;
        #pragma unroll 1
        while (warp_any(sv.x == EMPTY)) { sv = ld_x64(rsp); poll_tick(n); }
        const float var = __uint_as_float(sv.x), a = L ? 1.f + rsq(var + LN_EPS) : 1.f;
        sts64(Q_RC + (i & 255) * 8, __float_as_uint(a * rsq(a * a * var + LN_EPS)), sv.y ^ 0x80000000u);
    }
    if (t < 68) sts32(M_RED + t * 4, wr);
}

__device__ __forceinline__ void ffn_finish(int L, bf16* __restrict__ out) {
    const int t = tid_now() - 288, c = cta_now(), lane = t & 31, warp = warp_uniform(t >> 5);
    TL(288, L * 32 + 29);
    const uint4 rv = lds128(M_RT + 16 * L);
    const int idx = (int)rv.w;
    const uint32_t* xsrc = &g_x.cand[L][idx >> 7][(c >> 2) * 16 + (t & 3) * 4 + (c & 3)];
    const uint8_t* fsrc = &g_x.x[idx >> 8][((idx >> 7) & 1) * 8 + (c >> 4)];
    uint32_t xw, busy;
    const float sg = sigmoid(bf_round(__uint_as_float(rv.x)));
    uint32_t rsel = pack_bf16(sg, sg);
    Ln2 kx = ln2_coef(__uint_as_float(rv.y), __uint_as_float(rv.z));
    uint32_t* dst = reinterpret_cast<uint32_t*>(L ? out : g_x1) + idx * (D_ / 2) + c * 4 + t;
    asm volatile("" : "+r"(rsel), "+r"(kx.nm), "+r"(kx.rh), "+r"(kx.rl), "+r"(kx.c), "+l"(dst));
    float a[8] = {0.f, 0.f, 0.f, 0.f};
    {
        const float* src = &g_x.ypart[L][c][0][t * 4];
        uint4 v[3];
        uint32_t n = 0;
        #pragma unroll 1
        do {
            v[0] = ld_x128(src); v[1] = ld_x128(src + 384);
            v[2] = make_uint4(0u, 0u, 0u, 0u);
            xw = 0u; busy = 0u;
            if (warp == 0) {
                v[2] = ld_x128(src + 768); xw = ld_x32(xsrc);
                asm volatile("ld.relaxed.gpu.global.u8 %0, [%1];" : "=r"(busy) : "l"(fsrc) : "memory");
            }
            poll_tick(n);
        } while (warp_any(any_empty(v[0]) || any_empty(v[1]) || any_empty(v[2]) || xw == EMPTY || busy != 0));
        TL(288, L * 32 + 30); TL(352, L * 32 + 31);
        #pragma unroll
        for (int i = 0; i < 3; i++) { a[0] += __uint_as_float(v[i].x); a[1] += __uint_as_float(v[i].y); a[2] += __uint_as_float(v[i].z); a[3] += __uint_as_float(v[i].w); }
    }
    halve<2>(a, lane, 2); halve<1>(a, lane, 4);
    a[0] += __shfl_xor_sync(0xffffffffu, a[0], 8); a[0] += __shfl_xor_sync(0xffffffffu, a[0], 16);
    if (lane < 8) stsf(M_SR + warp * 32 + ((lane & 1) * 4 + (lane & 2) + (lane >> 2)) * 4, a[0]);
    const uint32_t xn = ln2(xw, kx);
    named_sync(NB_SIDE, 96);
    if (t < 4) {
        const float2 y0 = lds64f(M_SR + t * 8), y1 = lds64f(M_SR + 32 + t * 8), y2 = lds64f(M_SR + 64 + t * 8);
        const uint32_t y = pack_bf16(y0.x + y1.x + y2.x, y0.y + y1.y + y2.y);
        const uint32_t res = badd2(xw, badd2(xn, bmul2(y, rsel)));
        *dst = res;
        if (L == 0) st_x32(&g_x.x2row[c * 4 + t], res);
    }
}

__device__ __forceinline__ void fix_row(uint32_t lb) {
    const int t = tid_now() - 288, c = cta_now(), lane = t & 31, warp = warp_uniform(t >> 5);
    uint4 v[2];
    {
        uint32_t n = 0;
        #pragma unroll 1
        do {
            v[0] = ld_x128(g_x.x2row + t * 4);
            v[1] = make_uint4(0u, 0u, 0u, 0u);
            if (warp == 0) v[1] = ld_x128(g_x.x2row + (96 + t) * 4);
            poll_tick(n);
        } while (warp_any(any_empty(v[0]) || any_empty(v[1])));
    }
    const uint32_t w[8] = {v[0].x, v[0].y, v[0].z, v[0].w, v[1].x, v[1].y, v[1].z, v[1].w};
    float su = 0.f, sq = 0.f;
    #pragma unroll
    for (int i = 0; i < 8; i++) { const float a = bf_lo(w[i]), b = bf_hi(w[i]); su += a + b; sq = fmaf(a, a, fmaf(b, b, sq)); }
    su = warp_sum(su); sq = warp_sum(sq);
    if (lane == 0) sts64(M_SR + 96 + warp * 8, __float_as_uint(su), __float_as_uint(sq));
    named_sync(NB_SIDE, 96);
    const float2 s0 = lds64f(M_SR + 96), s1 = lds64f(M_SR + 104), s2 = lds64f(M_SR + 112);
    const float mean = (s0.x + s1.x + s2.x) * (1.f / D_);
    const float rstd = rsq(fmaxf((s0.y + s1.y + s2.y) * (1.f / D_) - mean * mean, 0.f) + LN_EPS);
    const Ln2 k = ln2_coef(mean, rstd);
    #pragma unroll
    for (int i = 0; i < 2; i++)
        if (i == 0 || warp == 0) sts128(SD_VEC + (t + 96 * i) * 16, ln2(w[4*i], k), ln2(w[4*i+1], k), ln2(w[4*i+2], k), ln2(w[4*i+3], k));
    named_sync(NB_SIDE, 96);
    TL(288, 32 + 22);
    mbar_nap(lb + B_SW, 0);
    float a[8];
    #pragma unroll
    for (int i = 0; i < 8; i++) a[i] = 0.f;
    const uint32_t xa = base32(SD_VEC + lane * 2), wa = base32(SD_W + lane * 48 + warp * 16);
    #pragma unroll 2
    for (int b = 0; b < 32; b++) {
        const float x = bf_lo(lds16(xa + b * 64));
        const uint4 u = lds128(wa + b * 1536);
        a[0] = fmaf(x, bf_lo(u.x), a[0]); a[1] = fmaf(x, bf_hi(u.x), a[1]); a[2] = fmaf(x, bf_lo(u.y), a[2]); a[3] = fmaf(x, bf_hi(u.y), a[3]);
        a[4] = fmaf(x, bf_lo(u.z), a[4]); a[5] = fmaf(x, bf_hi(u.z), a[5]); a[6] = fmaf(x, bf_lo(u.w), a[6]); a[7] = fmaf(x, bf_hi(u.w), a[7]);
    }
    halve<4>(a, lane, 16); halve<2>(a, lane, 8); halve<1>(a, lane, 4);
    a[0] = quad_sum(a[0]);
    if ((lane & 3) == 0) st_x32(&g_x.fix[c * 24 + warp * 8 + (lane >> 2)], __float_as_uint(a[0]));
    TL(288, 32 + 23);
    if (((int)lds32(M_RT + 12) >> 8) == mt_of(c)) {
        const float* src = &g_x.fix[(t >> 5) * D_ + nt_of(c) * 64 + (t & 31) * 2];
        uint2 f;
        uint32_t n = 0;
        #pragma unroll 1
        do { f = ld_x64(src); poll_tick(n); } while (warp_any(f.x == EMPTY || f.y == EMPTY));
        sts64(Q_FIX + t * 8, f.x, f.y);
    }
}

__device__ __forceinline__ void out_piece(bf16* __restrict__ out, int r, int ch, bool on) {
    const uint4 v = lds128(((ch & 8) ? YT1 : YT0) + r * 128 + (((ch ^ r) & 7) << 4)), kk = lds128(XT0 + r * 16);
    const Ln2 k = {kk.x, kk.y, kk.z, kk.w};
    const int c = blockIdx.x;
    stg128_pred(out + (blk_of(c) * 128 + r) * D_ + cb_of(c) * 128 + ch * 8, make_uint4(add_ln2(v.x, k), add_ln2(v.y, k), add_ln2(v.z, k), add_ln2(v.w, k)), on);
}
__device__ __forceinline__ void publish(uint8_t* f) {
    bulk_commit();
    bulk_wait();
    fence_async_global();
    asm volatile("st.release.gpu.global.u8 [%0], 0;" :: "l"(f) : "memory");
}
__device__ __forceinline__ void side_role(const Maps& mp, const bf16* __restrict__ x0, const bf16* __restrict__ wo, const bf16* __restrict__ w_down, const bf16* __restrict__ w_r, bf16* __restrict__ out) {
    #pragma unroll 1
    for (int L = 0; L < 2; L++) {
        const uint32_t lb = M_BAR + L * BAR_SET;
        if (L == 0) prep_work(x0, w_r, lb);
        else fix_row(lb);
        epi_inputs(L, w_r);
        const int t = tid_now() - 288, c = cta_now(), mt = mt_of(c), nt = nt_of(c), warp = warp_uniform(t >> 5);
        TL(288, L * 32 + 4);
        named_arrive(NB_EPI, 224);
        named_arrive(NB_EPI + 1, 224);
        if (warp == 0) {
            named_sync(NB_ML, 288);
            #pragma unroll
            for (int i = 0; i < 16; i++) sts128(base32(A_RING + 16384 + t * 16) + (i >> 2) * R_SLOT + (i & 3) * 512, 0x2C002C00u, 0x2C002C00u, 0x2C002C00u, 0x2C002C00u);
            fence_async_smem();
            __syncwarp();
            mbar_arrive_elect(lb + B_ONE);
        }
        if (elect_one()) {
            #pragma unroll 1
            for (int n = warp - 1; n >= 0 && n < 3 * warp - 2; n++) {
                char* dst = g_kv + (size_t)(nt * 2 + (n >> 1)) * 16 * KV_TILE;
                if (n < 3) mbar_nap(lb + (n == 0 ? B_K0 : n == 1 ? B_KS : B_AE + 16), 0);
                bulk_store(dst + ((2 * mt - 1 + (n & 1)) & 15) * KV_TILE, n == 0 ? A_KP : n == 1 ? A_RING : A_STB + (n - 2) * 8192, 8192 << (n & 1));
                if (n & 1) bulk_store(dst + 2 * mt * KV_TILE + 24576, n == 1 ? A_RING + R_SLOT + 8192 : A_STB + 24576, 8192);
                publish(&g_x.kv[L][nt * 2 + (n >> 1)][2 * mt + (n & 1)]);
                if (n == 1) TL(352, L * 32 + 6);
                if (n == 0) TL(320, L * 32 + 27);
            }
            if (warp == 2) {
                const bool ffn = c < NFC;
                const uint64_t pol = policy_evict_first();
                mbar_expect_tx(lb + B_GU, ffn ? 131072 : 0);
                mbar_expect_tx(lb + B_WD, ffn ? 65536 : 0);
                l2_prefetch(reinterpret_cast<const char*>(wo) + (size_t)c * 16384, 16384);
                if (ffn) {
                    #pragma unroll 1
                    for (int i = 0; i < 12; i++) {
                        if (i < 8) tma_load_s(F_GU0 + i * 16384, (i & 1) ? &mp.u : &mp.g, c * 32, (i >> 1) * 256, lb + B_GU, pol);
                        else l2_prefetch(reinterpret_cast<const char*>(w_down) + (size_t)c * 65536 + (i - 8) * 16384, 16384);
                        __nanosleep(900);
                    }
                }
                mbar_nap(lb + B_OD, 0);
                __nanosleep(1000);
                l2_prefetch(g_u.fill[c], sizeof(g_u.fill[0]));
                if (L == 0) {
                    mbar_nap(lb + B_XS, 0);
                    tma_store(&mp.x[1], YT0, cb_of(c) * 128, blk_of(c) * 128);
                    tma_store(&mp.x[1], YT1, cb_of(c) * 128 + 64, blk_of(c) * 128);
                    publish(&g_x.x[blk_of(c) >> 1][(blk_of(c) & 1) * 8 + cb_of(c)]);
                    mbar_arrive(lb + B_XD);
                    TL(352, 18);
                }
            } else {
                #pragma unroll 1
                for (int p = 0; p < 2; p++) { mbar_sleep(lb + B_OD + (p * 2 + warp) * 8, 0); ctr_arrive(g_x.o[L][mt * 2 + warp][p]); TL(288, L * 32 + 19); }
            }
        }
        __syncwarp();
        if (L) {
            mbar_sleep(lb + B_XS, 0);
            const int cand = (int)lds32(M_CR) & 127;
            #pragma unroll 2
            for (int r = t >> 4; r < 132; r += 6) out_piece(out, r & 127, t & 15, r < 128 && r != cand);
            TL(288, 32 + 18);
            mbar_sleep(lb + B_RT, 0);
            out_piece(out, cand, t & 15, t < 16 && lds32(M_CR) != lds32(M_RT + 28));
        }
        const uint32_t late = mbar_test(lb + B_FD, 0);
        mbar_sleep(lb + B_FD, 0);
        __nanosleep(late ? 50 : 400);
        if (c == 0 && t == 0 && L == 0) g_pctr = 0;
        ffn_finish(L, out);
        TL(288, L * 32 + 20);
    }
}

struct Cols { float2 c[4]; float hs; };
template <int HH>
__device__ __forceinline__ void load_cols(Cols& k, uint32_t cs) {
    #pragma unroll
    for (int jj = 0; jj < 4; jj++) k.c[jj] = lds64f(cs + (HH * 32 + jj * 8) * 4);
    k.hs = ldsf(M_HS + HH * 4);
}
template <int HH>
__device__ __forceinline__ void qkv_epi_head(const float (&acc0)[96], const float (&acc1)[96], const float (&cf)[4], const float (&nm)[4], const Cols& k, uint32_t (&pk)[4][4]) {
    #pragma unroll
    for (int jj = 0; jj < 4; jj++) {
        #pragma unroll
        for (int i = 0; i < 4; i++) {
            const float* a = (i >> 1) ? acc1 : acc0;
            const float sc = cf[i] * k.hs;
            const float x = fmaf(nm[i], k.c[jj].x, a[4 * (4 * HH + jj) + 2 * (i & 1)]) * sc;
            const float y = fmaf(nm[i], k.c[jj].y, a[4 * (4 * HH + jj) + 2 * (i & 1) + 1]) * sc;
            pk[i][jj] = pack_f16(x, y);
        }
    }
}
__device__ __forceinline__ void stage_kv(uint32_t dst, const uint32_t (&pk)[4][4]) {
    #pragma unroll
    for (int i = 0; i < 4; i++) stsm4(dst + (i >> 1) * 1024 + (i & 1) * 128, pk[i][0], pk[i][1], pk[i][2], pk[i][3]);
}
template <int OFF>
__device__ __forceinline__ void patch_row(float (&acc)[96], uint32_t fx) {
    #pragma unroll
    for (int j = 0; j < 24; j++) { const float2 f = lds64f(fx + j * 32); acc[4 * j + OFF] = f.x; acc[4 * j + OFF + 1] = f.y; }
}
template <bool INIT>
__device__ __forceinline__ void qkv_step(float (&acc0)[96], float (&acc1)[96], uint64_t da, uint64_t db) {
    wg_fence();
    #pragma unroll
    for (int kk = 0; kk < 4; kk++) {
        if (INIT && kk == 0) { wg_gemm_n192_init(acc0, da, db); wg_gemm_n192_init(acc1, da + (8192 >> 4), db); }
        else { wg_gemm_n192(acc0, da + kk * 2, db + kk * 128); wg_gemm_n192(acc1, da + (8192 >> 4) + kk * 2, db + kk * 128); }
    }
    wg_commit();
}
__device__ __forceinline__ void qkv_phase(int L, uint32_t lb, int wg, uint32_t (&qa)[8], uint32_t (&qb)[8], uint32_t (&SA)[32], uint32_t (&SB_)[32]) {
    float acc0[96], acc1[96];
    {
        const bool leader = (tid_now() & 127) == 0;
        const uint64_t da0 = opaque(desc_sw128(SB + wg * 16384, 16, 1024)), db0 = opaque(desc_sw128(SB + Q_ABYTES, 8192, 1024));
        mbar_spin(lb + B_QF, 0);
        TL(0, L * 32 + 1); CK(0, L * 32 + 10);
        qkv_step<true>(acc0, acc1, da0, db0);
        uint32_t st = 1, ph = 0;
        #pragma unroll 1
        for (int k = 1; k < 16; k++) {
            mbar_spin(lb + B_QF + 8 * st, ph);
            if (k == 14 && wg) named_sync(NB_CONS, 256);
            qkv_step<false>(acc0, acc1, da0 + st * (Q_STB >> 4), db0 + st * (Q_STB >> 4));
            if (k == 15 && !wg) named_arrive(NB_CONS, 256);
            wg_wait<1>();
            if (leader) mbar_arrive(lb + B_QE + 8 * (st == 0 ? 2 : st - 1));
            if (++st == 3) { st = 0; ph ^= 1; }
        }
    }
    named_sync(NB_EPI + wg, 224);
    const int tid = tid_now(), lane = tid & 31, w = (tid >> 5) & 3, g = lane >> 2, t = lane & 3;
    const int lr0 = wg * 128 + w * 16 + g;
    float cf[4], nm[4];
    #pragma unroll
    for (int i = 0; i < 4; i++) { const float2 r = lds64f(base32(Q_RC + lr0 * 8) + ((i >> 1) * 64 + (i & 1) * 8) * 8); cf[i] = r.x; nm[i] = r.y; }
    const uint32_t cs = base32(Q_CS + t * 8);
    const int d = L ? (int)lds32(M_RT + 12) - (mt_of(cta_now()) * 256 + lr0) : -1;
    const uint32_t ko = base32((lane >> 3) * 2048 + (w * 16 + (lane & 7)) * 16);
    Cols k0, k1;
    load_cols<2>(k0, cs);
    wg_wait<0>();
    pin(acc0); pin(acc1);
    TL(128, L * 32 + 2); CK(128, L * 32 + 11);
    named_arrive(NB_ML, 288);
    if ((tid & 127) == 0) mbar_arrive(lb + B_QE);
    if (__builtin_expect((d & ~72) == 0, 0)) {
        if (d == 0) { patch_row<0>(acc0, cs + (Q_FIX - Q_CS)); cf[0] = 1.f; nm[0] = 0.f; }
        else if (d == 8) { patch_row<2>(acc0, cs + (Q_FIX - Q_CS)); cf[1] = 1.f; nm[1] = 0.f; }
        else if (d == 64) { patch_row<0>(acc1, cs + (Q_FIX - Q_CS)); cf[2] = 1.f; nm[2] = 0.f; }
        else { patch_row<2>(acc1, cs + (Q_FIX - Q_CS)); cf[3] = 1.f; nm[3] = 0.f; }
    }
    __syncwarp();
    uint32_t pk[4][4];
    qkv_epi_head<2>(acc0, acc1, cf, nm, k0, pk);
    load_cols<4>(k1, cs);
    mbar_spin(lb + B_QE + 8 - 8 * wg, wg);
    stage_kv((wg ? A_RING : A_KP) + ko, pk);
    if (!wg) {
        fence_async_smem();
        __syncwarp();
        mbar_arrive_elect(lb + B_K0);
    }
    qkv_epi_head<4>(acc0, acc1, cf, nm, k1, pk);
    load_cols<3>(k0, cs);
    stage_kv(A_RING + wg * R_SLOT + 8192 + ko, pk);
    fence_async_smem();
    __syncwarp();
    mbar_arrive_elect(lb + B_KS);
    qkv_epi_head<3>(acc0, acc1, cf, nm, k0, pk);
    load_cols<0>(k1, cs);
    load_cols<5>(k0, cs);
    stage_kv(A_STB + wg * 8192 + ko, pk);
    qkv_epi_head<0>(acc0, acc1, cf, nm, k1, pk);
    #pragma unroll
    for (int s = 0; s < 2; s++) {
        qa[4*s] = pk[0][2*s]; qa[4*s+1] = pk[1][2*s]; qa[4*s+2] = pk[0][2*s+1]; qa[4*s+3] = pk[1][2*s+1];
        qb[4*s] = pk[2][2*s]; qb[4*s+1] = pk[3][2*s]; qb[4*s+2] = pk[2][2*s+1]; qb[4*s+3] = pk[3][2*s+1];
    }
    mbar_spin(lb + B_K0, 0);
    {
        constexpr uint64_t dk = desc_plain(A_KP, 2048, 128);
        wg_fence();
        wg_qk_init(SA, qa[0], qa[1], qa[2], qa[3], dk);
        wg_qk_acc(SA, qa[4], qa[5], qa[6], qa[7], dk + 256);
        wg_qk_init(SB_, qb[0], qb[1], qb[2], qb[3], dk);
        wg_qk_acc(SB_, qb[4], qb[5], qb[6], qb[7], dk + 256);
        wg_commit();
    }
    qkv_epi_head<5>(acc0, acc1, cf, nm, k0, pk);
    load_cols<1>(k1, cs);
    stage_kv(A_STB + 16384 + wg * 8192 + ko, pk);
    qkv_epi_head<1>(acc0, acc1, cf, nm, k1, pk);
    #pragma unroll
    for (int u = 0; u < 2; u++)
        #pragma unroll
        for (int s = 0; s < 2; s++) sts128(A_QX + (u * 2 + s) * 4096 + tid * 16, pk[2*u][2*s], pk[2*u+1][2*s], pk[2*u][2*s+1], pk[2*u+1][2*s+1]);
    fence_async_smem();
    wg_wait<0>();
    pin(SA); pin(SB_);
    TL(128, L * 32 + 5); CK(128, L * 32 + 12);
}

#define PMASK 0x00005555u
#define IMASK 0x20202020u
__host__ __device__ constexpr bool is_poly(int j) { return !((PMASK >> j) & 1); }
#define TBIAS 0x5DEB5DEBu
struct Shift { uint32_t f0, f1, n0, n1, bad; };

__device__ __forceinline__ uint32_t exp2_mufu(uint32_t s, uint32_t nm) {
    uint32_t r;
    asm("ex2.approx.f16x2 %0, %1;" : "=r"(r) : "r"(hadd2(s, nm)));
    return r;
}
__device__ __forceinline__ uint32_t exp2_fix(uint32_t s, uint32_t fm, uint32_t ca, uint32_t& U, bool mul, uint32_t sixteen) {
    uint32_t G, D;
    asm("fma.rn.relu.f16x2 %0, %1, %2, %3;" : "=r"(U) : "r"(s), "r"(0x00400040u), "r"(fm));
    asm("fma.rn.f16x2 %0, %1, %2, %3;" : "=r"(G) : "r"(U & 0x003F003Fu), "r"(ca), "r"(0x98B898B8u));
    asm("{.reg .b32 n; neg.f16x2 n, %1; fma.rn.relu.f16x2 %0, %1, n, %2;}" : "=r"(D) : "r"(G), "r"(0x00570057u));
    if (mul) return U * sixteen - D;
    return (U << 4) - D;
}
__device__ __forceinline__ uint32_t or3(uint32_t a, uint32_t b, uint32_t c) { uint32_t r; asm("lop3.b32 %0, %1, %2, %3, 0xFE;" : "=r"(r) : "r"(a), "r"(b), "r"(c)); return r; }
__device__ __forceinline__ void exp_tile(const uint32_t (&S)[32], uint32_t (&P)[32], Shift& h, uint32_t ca, uint32_t sixteen) {
    uint32_t U[33];
    int n = 0;
    #pragma unroll
    for (int i = 0; i < 32; i++) {
        if (is_poly(i)) P[i] = exp2_fix(S[i], (i & 1) ? h.f1 : h.f0, ca, U[n++], (IMASK >> i) & 1, sixteen);
        else P[i] = exp2_mufu(S[i], (i & 1) ? h.n1 : h.n0);
    }
    U[n] = 0u;
    #pragma unroll
    for (int i = 0; i < 32; i += 6) {
        if (i + 5 <= n) h.bad = or3(h.bad, or3(U[i], U[i + 1], U[i + 2]), or3(U[i + 3], U[i + 4], U[i + 5]));
        else {
            #pragma unroll
            for (int j = i; j < i + 6; j += 2) if (j < n) h.bad = or3(h.bad, U[j], U[j + 1]);
        }
    }
    pin(P);
}
__device__ __forceinline__ uint32_t hfma2(uint32_t a, uint32_t b, uint32_t c) { uint32_t r; asm("fma.rn.f16x2 %0, %1, %2, %3;" : "=r"(r) : "r"(a), "r"(b), "r"(c)); return r; }
__device__ __forceinline__ void unit_start(const uint32_t (&S)[32], Shift& h, uint32_t (&o2)[10]) {
    uint32_t m[4] = {S[0], S[1], S[2], S[3]};
    #pragma unroll
    for (int i = 1; i < 8; i++)
        #pragma unroll
        for (int e = 0; e < 4; e++) m[e] = hmax2(m[e], S[4 * i + e]);
    const uint32_t a = hadd2(m[0], m[2]), c = hadd2(m[1], m[3]);
    uint32_t x = hadd2(__byte_perm(a, c, 0x5410), __byte_perm(a, c, 0x7632));
    x = hadd2(x, __shfl_xor_sync(0xffffffffu, x, 1));
    x = hadd2(x, __shfl_xor_sync(0xffffffffu, x, 2));
    const uint32_t T = hfma2(x, 0xAC00AC00u, TBIAS);
    const uint32_t n = hadd2(T, 0xDE00DE00u), f = hfma2(n, 0x00400040u, 0x03C003C0u);
    h.n0 = __byte_perm(n, 0, 0x1010); h.n1 = __byte_perm(n, 0, 0x3232);
    h.f0 = __byte_perm(f, 0, 0x1010); h.f1 = __byte_perm(f, 0, 0x3232);
    h.bad = T ^ 0x58005800u;
    #pragma unroll
    for (int i = 0; i < 10; i++) o2[i] = 0u;
}
__device__ __forceinline__ uint32_t o_offset() {
    const int c = cta_now(), tid = tid_now();
    return (mt_of(c) * 256 + (tid & 128) + ((tid >> 1) & 48) + ((tid >> 2) & 7)) * (D_ * 2) + nt_of(c) * 64 + (tid & 3) * 16;
}
template <int PASS, int UNIT>
__device__ __forceinline__ void unit_end(const uint32_t (&o)[10], uint32_t bad, uint32_t lb, uint32_t oo, uint32_t& fail, float iv) {
    float v[20];
    #pragma unroll
    for (int i = 0; i < 10; i++) h2_unpack(o[i], v[2 * i], v[2 * i + 1]);
    const float i0 = rcp(v[16]) * iv, i1 = rcp(v[18]) * iv;
    uint32_t r[8], z = 0;
    #pragma unroll
    for (int j = 0; j < 4; j++) {
        r[j] = pack_bf16(v[4*j] * i0, v[4*j+1] * i0); r[4 + j] = pack_bf16(v[4*j+2] * i1, v[4*j+3] * i1);
        z = bfma2(r[j], r[4 + j], z);
    }
    const bool good = o[8] - 0x34003400u < 0x48000000u && o[9] - 0x34003400u < 0x48000000u &&
                      ((bad & 0xF800F800u) | (bmul2(z, 0u) & 0x7FFF7FFFu) | (fail & (1u << (2 * PASS + UNIT)))) == 0;
    const bool all = __all_sync(0xffffffffu, good);
    char* dst = reinterpret_cast<char*>(g_o) + oo + (UNIT * 64 * D_ + PASS * 512) * 2;
    stg128_pred(dst, make_uint4(r[0], r[1], r[2], r[3]), all);
    stg128_pred(dst + 16 * D_, make_uint4(r[4], r[5], r[6], r[7]), all);
    if (__builtin_expect(!all, 0)) {
        fail |= 1u << (2 * PASS + UNIT);
        if (PASS == 0) {
            #pragma unroll
            for (int s = 0; s < 2; s++) g_qsave[cta_now()][UNIT * 2 + s][tid_now()] = lds128(A_KP + (UNIT * 2 + s) * 4096 + tid_now() * 16);
        }
    }
    __syncwarp();
    mbar_arrive_elect_p(lb + PASS * 16, all);
}
__device__ __forceinline__ void swap_q(uint32_t (&q)[8], uint32_t a) {
    asm volatile("{\n.reg .pred p;\nsetp.ne.u32 p, %8, 0;\n"
                 "@p st.shared.v4.b32 [%8 + -8192], {%0, %1, %2, %3};\n@p st.shared.v4.b32 [%8 + -4096], {%4, %5, %6, %7};\n"
                 "@p ld.shared.v4.b32 {%0, %1, %2, %3}, [%8];\n@p ld.shared.v4.b32 {%4, %5, %6, %7}, [%8 + 4096];\n}"
                 : "+r"(q[0]), "+r"(q[1]), "+r"(q[2]), "+r"(q[3]), "+r"(q[4]), "+r"(q[5]), "+r"(q[6]), "+r"(q[7]) : "r"(a) : "memory");
}
static_assert(A_QX == A_KP + 8192, "parking places");
template <bool INIT>
__device__ __forceinline__ void issue_pv(uint32_t (&o)[10], const uint32_t (&P)[32], uint64_t dv) {
    if (INIT) wg_pv_init(o, P[0], P[1], P[2], P[3], dv); else wg_pv_acc(o, P[0], P[1], P[2], P[3], dv);
    #pragma unroll
    for (int k = 1; k < 8; k++) wg_pv_acc(o, P[4*k], P[4*k+1], P[4*k+2], P[4*k+3], dv + k * 16);
}

__device__ __forceinline__ uint4 quad_transpose(uint32_t x0, uint32_t x1, uint32_t x2, uint32_t x3, int t) {
    const bool b0 = t & 1, b1 = t & 2;
    uint32_t s0 = b0 ? x0 : x1, s1 = b0 ? x2 : x3;
    s0 = __shfl_xor_sync(0xffffffffu, s0, 1); s1 = __shfl_xor_sync(0xffffffffu, s1, 1);
    const uint32_t y0 = b0 ? s0 : x0, y1 = b0 ? x1 : s0, y2 = b0 ? s1 : x2, y3 = b0 ? x3 : s1;
    uint32_t u0 = b1 ? y0 : y2, u1 = b1 ? y1 : y3;
    u0 = __shfl_xor_sync(0xffffffffu, u0, 2); u1 = __shfl_xor_sync(0xffffffffu, u1, 2);
    return b1 ? make_uint4(u0, u1, y2, y3) : make_uint4(y0, y1, u0, u1);
}
__device__ __forceinline__ uint32_t movm(uint32_t v) { uint32_t r; asm volatile("movmatrix.sync.aligned.m8n8.trans.b16 %0, %1;" : "=r"(r) : "r"(v)); return r; }
__device__ __forceinline__ void attn_repair(uint32_t lb, int wg, int ow, int pass, int unit) {
    const int tid = tid_now(), w = (tid >> 5) & 3, g = (tid & 31) >> 2, t = tid & 3;
    uint4* const sc = &g_qsave[cta_now()][0][tid & ~96];
    const uint4 qx = __ldcg(sc + (pass * 2 + unit) * 512 + ow * 32), qy = __ldcg(sc + (pass * 2 + unit) * 512 + 256 + ow * 32);
    float ss = ldsf(M_SS + pass * 4);
    if (ss == 0.f) ss = 1.f;
    const uint4 q0 = quad_transpose(qx.x, qx.z, qy.x, qy.z, t), q1 = quad_transpose(qx.y, qx.w, qy.y, qy.w, t);
    const char* kv = g_kv + (size_t)(nt_of(cta_now()) * 2 + pass) * 16 * KV_TILE + t * 2048 + g * 16;
    float o[4][4], m0 = -INFINITY, m1 = -INFINITY, l0 = 0.f, l1 = 0.f;
    #pragma unroll
    for (int j = 0; j < 4; j++) { o[j][0] = 0.f; o[j][1] = 0.f; o[j][2] = 0.f; o[j][3] = 0.f; }
    uint4 kf[8];
    #pragma unroll
    for (int i = 0; i < 8; i++) kf[i] = __ldcg(reinterpret_cast<const uint4*>(kv + ((4 * w - 1) & 15) * KV_TILE + i * 128));
    #pragma unroll 1
    for (int b = 8 * w; b < 8 * w + 8; b++) {
        uint4 vf[8];
        #pragma unroll
        for (int i = 0; i < 8; i++) vf[i] = __ldcg(reinterpret_cast<const uint4*>(kv + (b >> 1) * KV_TILE + (b & 1) * 1024 + 8192 + i * 128));
        float s[8][4];
        #pragma unroll
        for (int i = 0; i < 8; i++) {
            s[i][0] = 0.f; s[i][1] = 0.f; s[i][2] = 0.f; s[i][3] = 0.f;
            mma_f16(s[i], q0.x, q1.x, q0.y, q1.y, kf[i].x, kf[i].y); mma_f16(s[i], q0.z, q1.z, q0.w, q1.w, kf[i].z, kf[i].w);
        }
        #pragma unroll
        for (int i = 0; i < 8; i++) kf[i] = __ldcg(reinterpret_cast<const uint4*>(kv + (((b - 1) >> 1) & 15) * KV_TILE + (~b & 1) * 1024 + i * 128));
        float t0 = m0, t1 = m1;
        #pragma unroll
        for (int i = 0; i < 8; i++) { t0 = fmaxf(t0, fmaxf(s[i][0], s[i][1])); t1 = fmaxf(t1, fmaxf(s[i][2], s[i][3])); }
        t0 = quad_max(t0); t1 = quad_max(t1);
        const float a0 = ex2((m0 - t0) * ss), a1 = ex2((m1 - t1) * ss);
        m0 = t0; m1 = t1;
        l0 *= a0; l1 *= a1;
        #pragma unroll
        for (int j = 0; j < 4; j++) { o[j][0] *= a0; o[j][1] *= a0; o[j][2] *= a1; o[j][3] *= a1; }
        #pragma unroll
        for (int k = 0; k < 4; k++) {
            uint32_t pf[4];
            #pragma unroll
            for (int e = 0; e < 2; e++) {
                const float p0 = ex2((s[2*k+e][0] - m0) * ss), p1 = ex2((s[2*k+e][1] - m0) * ss), p2 = ex2((s[2*k+e][2] - m1) * ss), p3 = ex2((s[2*k+e][3] - m1) * ss);
                l0 += p0 + p1; l1 += p2 + p3;
                pf[2*e] = pack_f16(p0, p1); pf[2*e+1] = pack_f16(p2, p3);
            }
            mma_f16(o[0], pf[0], pf[1], pf[2], pf[3], movm(vf[2*k].x), movm(vf[2*k+1].x));
            mma_f16(o[1], pf[0], pf[1], pf[2], pf[3], movm(vf[2*k].y), movm(vf[2*k+1].y));
            mma_f16(o[2], pf[0], pf[1], pf[2], pf[3], movm(vf[2*k].z), movm(vf[2*k+1].z));
            mma_f16(o[3], pf[0], pf[1], pf[2], pf[3], movm(vf[2*k].w), movm(vf[2*k+1].w));
        }
    }
    sc[24 * 256 + w * 32] = make_uint4(__float_as_uint(m0), __float_as_uint(m1), __float_as_uint(quad_sum(l0)), __float_as_uint(quad_sum(l1)));
    #pragma unroll
    for (int j = 0; j < 4; j++) sc[(25 + j) * 256 + w * 32] = make_uint4(__float_as_uint(o[j][0]), __float_as_uint(o[j][1]), __float_as_uint(o[j][2]), __float_as_uint(o[j][3]));
    named_sync(NB_WG + wg, 128);
    uint4 h[4];
    #pragma unroll
    for (int i = 0; i < 4; i++) { h[i] = __ldcg(sc + 24 * 256 + i * 32); m0 = fmaxf(m0, __uint_as_float(h[i].x)); m1 = fmaxf(m1, __uint_as_float(h[i].y)); }
    float r[4] = {0.f, 0.f, 0.f, 0.f};
    l0 = 0.f; l1 = 0.f;
    #pragma unroll
    for (int i = 0; i < 4; i++) {
        const uint4 v = __ldcg(sc + (25 + w) * 256 + i * 32);
        const float a0 = ex2((__uint_as_float(h[i].x) - m0) * ss), a1 = ex2((__uint_as_float(h[i].y) - m1) * ss);
        l0 = fmaf(a0, __uint_as_float(h[i].z), l0); l1 = fmaf(a1, __uint_as_float(h[i].w), l1);
        r[0] = fmaf(a0, __uint_as_float(v.x), r[0]); r[1] = fmaf(a0, __uint_as_float(v.y), r[1]);
        r[2] = fmaf(a1, __uint_as_float(v.z), r[2]); r[3] = fmaf(a1, __uint_as_float(v.w), r[3]);
    }
    const float iv = 16.f * ldsf(M_IV + pass * 4), i0 = iv * rcp(l0), i1 = iv * rcp(l1);
    uint32_t* dst = reinterpret_cast<uint32_t*>(reinterpret_cast<char*>(g_o) + (o_offset() & ~48u) + ((unit * 64 + (ow - w) * 16) * D_ + pass * 512) * 2) + w * 4 + t;
    dst[0] = pack_bf16(r[0] * i0, r[1] * i0);
    dst[4 * D_] = pack_bf16(r[2] * i1, r[3] * i1);
    named_sync(NB_WG + wg, 128);
    if ((tid & 127) == 0) mbar_arrive(lb + B_OD + (pass * 2 + wg) * 8);
    __syncwarp();
}
__device__ __forceinline__ bool wg_any(bool p, int id) {
    uint32_t r;
    asm volatile("{\n.reg .pred a, b;\nsetp.ne.u32 a, %1, 0;\nbarrier.cta.red.or.aligned.pred b, %2, 128, a;\nselp.u32 %0, 1, 0, b;\n}" : "=r"(r) : "r"((uint32_t)p), "r"(id) : "memory");
    return r != 0;
}

__device__ __forceinline__ void load_gu(uint32_t (&f)[64], uint32_t src, int warp, int lane) {
    const uint32_t row = (warp & 3) * 64 + (lane >> 4) * 8 + (lane & 7), ch = (lane >> 3) & 1, sw = (lane >> 1) & 3;
    const uint32_t a0 = base32(src + (warp >> 2) * 32768 + row * 64 + ((ch ^ sw) << 4)), a1 = base32(a0 ^ 32);
    #pragma unroll
    for (int i = 0; i < 16; i++) ldsm4t(f[4*i], f[4*i+1], f[4*i+2], f[4*i+3], ((i & 1) ? a1 : a0) + ((i >> 1) & 1) * 16384 + (i >> 2) * 1024);
}

__device__ __forceinline__ void arrive_loaded(uint32_t bar, const uint32_t (&f)[64], uint32_t zero) {
    uint32_t x = 0;
    #pragma unroll
    for (int i = 0; i < 16; i++) x |= f[4 * i];
    mbar_arrive_elect(bar + (x & zero));
}
__device__ __forceinline__ void flush(uint32_t (&o2)[10], const uint32_t (&o)[10]) {
    #pragma unroll
    for (int i = 0; i < 10; i++) o2[i] = hadd2(o2[i], o[i]);
}
__device__ __forceinline__ void attention_phase(int L, uint32_t lb, int wg, uint32_t (&qa)[8], uint32_t (&qb)[8], uint32_t (&SA)[32], uint32_t (&SB_)[32], uint64_t dk0, uint64_t dv0, uint32_t ca, uint32_t (&wa)[64], uint32_t zero, uint32_t sixteen) {
    uint32_t PA[32], PB[32], oa[10], ob[10], oa2[10], ob2[10];
    Shift ha, hb;
    uint32_t fail = (lds32(M_SS) ? 3u : 0u) | (lds32(M_SS + 4) ? 12u : 0u);
    ca += base32(fail) >> 4;
    const uint32_t oo = o_offset(), odb = lb + B_OD + wg * 8;
    constexpr uint64_t SL = R_SLOT >> 4, KH = 4096 >> 4;
    unit_start(SA, ha, oa2);
    exp_tile(SA, PA, ha, ca, sixteen);
    #pragma unroll
    for (int i = 0; i < 10; i++) { ob[i] = 0u; ob2[i] = 0u; }
    hb = ha;
    mbar_spin(lb + B_KS, 0);
    mbar_spin(lb + B_ONE, 0);
    #pragma unroll 1
    for (int it = 0; ; it++) {
        const uint32_t ph = it & 1;
        uint32_t qsw = 0;
        #pragma unroll
        for (int u = 0; u < 4; u++) {
            const uint64_t dk = opaque(dk0) + u * SL, dv = opaque(dv0) + u * SL;
            wg_fence();
            if (u == 0) issue_pv<true>(oa, PA, dv); else issue_pv<false>(oa, PA, dv);
            wg_qk_init(SA, qa[0], qa[1], qa[2], qa[3], dk);
            wg_qk_acc(SA, qa[4], qa[5], qa[6], qa[7], dk + KH);
            wg_commit();
            if (u > 0) wg_wait<1>();
            pin(SB_); pin(ob);
            if (u == 0) {
                flush(ob2, ob);
                if (__builtin_expect((it & 3) == 0, 0)) {
                    if (it) unit_end<0, 1>(ob2, hb.bad, odb, oo, fail, ldsf(M_IV));
                    unit_start(SB_, hb, ob2);
                }
            } else mbar_arrive_elect(lb + B_AE + 8 * (u - 1));
            if (u == 3) swap_q(qb, qsw ? qsw + 8192 : 0u);
            exp_tile(SB_, PB, hb, ca, sixteen);
            wg_fence();
            if (u == 0) issue_pv<true>(ob, PB, dv); else issue_pv<false>(ob, PB, dv);
            wg_qk_init(SB_, qb[0], qb[1], qb[2], qb[3], dk);
            wg_qk_acc(SB_, qb[4], qb[5], qb[6], qb[7], dk + KH);
            wg_commit();
            wg_wait<1>();
            pin(SA); pin(oa);
            if (u == 2) { qsw = it == 3 ? A_QX + tid_now() * 16 : 0u; swap_q(qa, qsw); }
            if (u == 3) {
                flush(oa2, oa);
                if (__builtin_expect((it & 3) == 3, 0)) {
                    TL(0, L * 32 + 7 + (it >> 2)); CK(0, L * 32 + 1 + (it >> 2));
                    if (it == 7) goto done;
                    unit_end<0, 0>(oa2, ha.bad, odb, oo, fail, ldsf(M_IV));
                    unit_start(SA, ha, oa2);
                }
            }
            exp_tile(SA, PA, ha, ca, sixteen);
            mbar_spin(lb + B_AF + 8 * ((u + 1) & 3), u < 3 ? ph : ph ^ 1);
        }
        wg_wait<0>();
        mbar_arrive_elect(lb + B_AE + 24);
    }
done:
    const float iv = ldsf(M_IV + 4);
    mbar_spin(lb + B_GU, 0);
    load_gu(wa, F_GU0, tid_now() >> 5, tid_now() & 31);
    unit_end<1, 0>(oa2, ha.bad, odb, oo, fail, iv);
    wg_wait<0>();
    pin(ob);
    mbar_arrive_elect(lb + B_AE + 24);
    flush(ob2, ob);
    unit_end<1, 1>(ob2, hb.bad, odb, oo, fail, iv);
    arrive_loaded(lb + B_FG, wa, zero);
    if (__builtin_expect(wg_any(fail != 0, NB_WG + wg), 0)) {
        uint4* const qs = &g_qsave[cta_now()][0][tid_now()];
        qs[4 * 256] = make_uint4(qa[0], qa[1], qa[2], qa[3]); qs[5 * 256] = make_uint4(qa[4], qa[5], qa[6], qa[7]);
        qs[6 * 256] = make_uint4(qb[0], qb[1], qb[2], qb[3]); qs[7 * 256] = make_uint4(qb[4], qb[5], qb[6], qb[7]);
        #pragma unroll
        for (int i = 0; i < 16; i++) qs[(8 + i) * 256] = make_uint4(wa[4*i], wa[4*i+1], wa[4*i+2], wa[4*i+3]);
        sts32(M_SR + (tid_now() >> 5) * 4, fail);
        named_sync(NB_WG + wg, 128);
        #pragma unroll 1
        for (int r = 0; r < 16; r++)
            if ((warp_uniform(lds32(M_SR + wg * 16 + (r & 3) * 4)) >> (r >> 2)) & 1) attn_repair(lb, wg, r & 3, r >> 3, (r >> 2) & 1);
        #pragma unroll
        for (int i = 0; i < 16; i++) { const uint4 v = __ldcg(qs + (8 + i) * 256); wa[4*i] = v.x; wa[4*i+1] = v.y; wa[4*i+2] = v.z; wa[4*i+3] = v.w; }
    }
    TL(0, L * 32 + 9); CK(0, L * 32 + 8);
}

__device__ __forceinline__ void oproj_steps(float (&acc)[64], uint32_t lb, int wg, int k0, int k1) {
    const bool leader = (tid_now() & 127) == 0;
    #pragma unroll 1
    for (int k = k0; k < k1; k++) {
        const uint32_t st = k & 3;
        mbar_spin(lb + B_OF + 8 * st, (k >> 2) & 1);
        const uint64_t da = desc_sw128(o_a(st) + wg * 8192, 16, 1024);
        const uint64_t db = desc_sw128(o_b(st), 8192, 1024);
        wg_fence();
        #pragma unroll
        for (int kk = 0; kk < 4; kk++) wg_gemm_n128(acc, da + kk * 2, db + kk * 128);
        wg_commit();
        wg_wait<1>();
        if (leader && k > 0) mbar_arrive(lb + B_OE + 8 * ((k - 1) & 3));
    }
}

__device__ __forceinline__ uint32_t lane_key(uint32_t key, int lane) { return (key | 31u) ^ lane; }
__device__ __forceinline__ uint4 best_of(const uint4& e, int lane) {
    const uint32_t m = redux_max(lane_key(e.x, lane)), src = ~m & 31u;
    return make_uint4(m, __shfl_sync(0xffffffffu, e.y, src), __shfl_sync(0xffffffffu, e.z, src), __shfl_sync(0xffffffffu, e.w, src));
}
template <typename T> __device__ __forceinline__ T* early(T* p) { asm volatile("" : "+l"(p)); return p; }
__device__ __forceinline__ void load_wd(uint32_t (&wd)[64], uint32_t lb, int warp, int lane) {
    mbar_spin(lb + B_WD, 0);
    const uint32_t a0 = F_WD + warp * 8192 + ((lane >> 4) * 8 + (lane & 7)) * 128, ch = ((lane >> 3) & 1) ^ (lane & 7);
    #pragma unroll
    for (int i = 0; i < 16; i++) ldsm4t(wd[4*i], wd[4*i+1], wd[4*i+2], wd[4*i+3], base32(a0 + ((ch ^ (i & 6)) << 4)) + (i >> 3) * 4096 + (i & 1) * 2048);
}
__device__ __forceinline__ void stage_tile(const uint32_t (&xa)[4], const uint32_t (&xv)[32]) {
    #pragma unroll
    for (int m = 0; m < 8; m++) stsm4(xa[m & 3] + (m < 4 ? YT0 - XT0 : YT1 - XT0), xv[4*m], xv[4*m+1], xv[4*m+2], xv[4*m+3]);
    fence_async_smem();
    __syncwarp();
}

__device__ __forceinline__ void tail_phase(int L, uint32_t lb, int wg, const uint32_t (&wa)[64]) {
    const int c = cta_now(), blk = blk_of(c), cb = cb_of(c), tid = tid_now();
    const int lane = tid & 31, w = (tid >> 5) & 3, g = lane >> 2, t = lane & 3;
    const int lr0 = wg * 64 + w * 16 + g;
    uint32_t xa[4];
    #pragma unroll
    for (int m = 0; m < 4; m++) xa[m] = base32(XT0 + (wg * 64 + w * 16 + (lane & 15)) * 128 + (((lane >> 4) ^ (lane & 7) ^ (2 * m)) << 4));
    uint32_t xv[32];
    const bool ffn = c < NFC;
    uint32_t wb[64], wd[64];
    float own[6];
    {
        float acc[64];
        #pragma unroll
        for (int i = 0; i < 64; i++) acc[i] = 0.f;
        pin(acc);
        float2 rs0 = make_float2(0.f, 0.f), rs1 = rs0;
        if (L) { rs0 = __ldcg(&g_x.rs1[blk * 128 + lr0]); rs1 = __ldcg(&g_x.rs1[blk * 128 + lr0 + 8]); }
        oproj_steps(acc, lb, wg, 0, 8);
        mbar_spin(lb + B_RES, 0);
        #pragma unroll
        for (int m = 0; m < 8; m++) ldsm4(xv[4*m], xv[4*m+1], xv[4*m+2], xv[4*m+3], xa[m & 3] + (m < 4 ? 0 : XT1 - XT0));
        if (L) {
            const int d = (int)lds32(M_RT + 12) - (blk * 128 + lr0);
            const Ln2 k0 = ln2_coef(rs0.y, d == 0 ? 0.f : rsq(rs0.x + LN_EPS)), k1 = ln2_coef(rs1.y, d == 8 ? 0.f : rsq(rs1.x + LN_EPS));
            #pragma unroll
            for (int j = 0; j < 16; j++) { xv[2*j] = add_ln2(xv[2*j], k0); xv[2*j+1] = add_ln2(xv[2*j+1], k1); }
        }
        pin(xv);
        oproj_steps(acc, lb, wg, 8, 16);
        uint32_t wv[16];
        #pragma unroll
        for (int i = 0; i < 4; i++) ldsm4(wv[4*i], wv[4*i+1], wv[4*i+2], wv[4*i+3], (lane & 1) ? M_RED + (lane >> 3) * 16 + i * 64 : M_RED + 256);
        uint4* const pdst = early(&g_x.part[L][blk][cb][lr0]);
        wg_wait<0>();
        pin(acc);
        if ((tid & 127) == 0) mbar_arrive(lb + B_OE + 24);
        TL(0, L * 32 + 11); CK(0, L * 32 + 13);
        float sa[4] = {0.f, 0.f, 0.f, 0.f}, sb[4] = {0.f, 0.f, 0.f, 0.f}, sc[4] = {0.f, 0.f, 0.f, 0.f};
        float sd[4] = {0.f, 0.f, 0.f, 0.f}, se[4] = {0.f, 0.f, 0.f, 0.f};
        #pragma unroll
        for (int m = 0; m < 8; m++) {
            #pragma unroll
            for (int i = 0; i < 4; i++) xv[4*m+i] = badd2(xv[4*m+i], pack_bf16(acc[8*m + 2*i], acc[8*m + 2*i + 1]));
            mma_bf16(sa, xv[4*m], xv[4*m+1], xv[4*m+2], xv[4*m+3], wv[2*m], wv[2*m+1]);
            mma_bf16_k8(sb, xv[4*m], xv[4*m+1], xv[4*m]); mma_bf16_k8(sc, xv[4*m], xv[4*m+1], xv[4*m+1]);
            mma_bf16_k8(sd, xv[4*m+2], xv[4*m+3], xv[4*m+2]); mma_bf16_k8(se, xv[4*m+2], xv[4*m+3], xv[4*m+3]);
        }
        const float q0 = (g & 1) ? sb[1] + sd[1] : sb[0] + sd[0], q1 = (g & 1) ? sc[3] + se[3] : sc[2] + se[2];
        if (t == (g >> 1)) {
            st_x128(pdst, __float_as_uint(sa[0]), __float_as_uint(q0), __float_as_uint(sa[1]), 0u);
            st_x128(pdst + 8, __float_as_uint(sa[2]), __float_as_uint(q1), __float_as_uint(sa[3]), 0u);
        }
        __syncwarp();
        own[0] = sa[0]; own[1] = __shfl_sync(0xffffffffu, q0, (lane & 28) + (g >> 1)); own[2] = sa[1];
        own[3] = sa[2]; own[4] = __shfl_sync(0xffffffffu, q1, (lane & 28) + (g >> 1)); own[5] = sa[3];
    }
    TL(0, L * 32 + 12);
    load_gu(wb, F_GU1, tid >> 5, lane);
    stage_tile(xa, xv);
    uint4* const hdst = early(&g_x.hdr[L][(tid & 15) * 8 + cb][blk]);
    uint32_t* const cdst = early(&g_x.cand[L][blk][cb * 64 + t * 4]);
    const float ws = ldsf(M_WS);
    float mean, var, rstd;
    uint4 f;
    {
        const bool o0 = cb == 2 * t, o1 = cb == 2 * t + 1;
        const uint32_t m0 = o0 ? 0u : EMPTY, m1 = o1 ? 0u : EMPTY;
        const uint4* const psrc = &g_x.part[L][blk][2 * t][lr0];
        uint4 p[4];
        uint32_t n = 0;
        #pragma unroll 1
        do {
            p[0] = ld_x128(psrc); p[1] = ld_x128(psrc + 128); p[2] = ld_x128(psrc + 8); p[3] = ld_x128(psrc + 136);
            poll_tick(n);
        } while (warp_any((((p[0].w | p[2].w) & m0) | ((p[1].w | p[3].w) & m1)) != 0));
        mbar_arrive_elect_p(lb + B_XS, L == 0);
        float v[8];
        #pragma unroll
        for (int h = 0; h < 2; h++) {
            v[3*h] = (o0 ? own[3*h] : __uint_as_float(p[2*h].x)) + (o1 ? own[3*h] : __uint_as_float(p[2*h+1].x));
            v[3*h+1] = (o0 ? own[3*h+1] : __uint_as_float(p[2*h].y)) + (o1 ? own[3*h+1] : __uint_as_float(p[2*h+1].y));
            v[3*h+2] = (o0 ? own[3*h+2] : __uint_as_float(p[2*h].z)) + (o1 ? own[3*h+2] : __uint_as_float(p[2*h+1].z));
        }
        halve<3>(v, lane, 1);
        #pragma unroll
        for (int i = 0; i < 3; i++) v[i] += __shfl_xor_sync(0xffffffffu, v[i], 2);
        mean = v[0] * (1.f / D_);
        var = fmaxf(v[1] * (1.f / D_) - mean * mean, 0.f);
        rstd = rsq(var + LN_EPS);
        TL(0, L * 32 + 13);
        const uint32_t key = lane_key(order_bits(rstd * (v[2] - mean * ws)), lane);
        if (redux_max(key) == key) sts128(M_SR + (tid >> 5) * 16, key, __float_as_uint(mean), __float_as_uint(rstd), blk * 128 + lr0 + 8 * (t & 1));
        named_sync(NB_CONS, 256);
        f = best_of(lds128(M_SR + (lane & 7) * 16), lane);
        st_x128_if(tid < 16, hdst, f.x, f.y, f.z, f.w);
        const int d = (int)f.w - (blk * 128 + lr0);
        if ((d & ~8) == 0) {
            #pragma unroll
            for (int b = 0; b < 4; b++)
                st_x128(cdst + b * 16, d ? xv[8*b+1] : xv[8*b], d ? xv[8*b+3] : xv[8*b+2], d ? xv[8*b+5] : xv[8*b+4], d ? xv[8*b+7] : xv[8*b+6]);
        }
        __syncwarp();
    }
    if (t < 2) {
        if (L) { const Ln2 k = ln2_coef(mean, rstd); sts128(XT0 + (lr0 + 8 * t) * 16, k.nm, k.rh, k.rl, k.c); }
        else if (cb == 0) st_x64(&g_x.rs1[blk * 128 + lr0 + 8 * t], __float_as_uint(var), __float_as_uint(mean));
    }
    TL(0, L * 32 + 28);
    if (tid == 0) sts32(M_CR, f.w);
    __syncwarp();
    mbar_arrive_elect_p(lb + B_XS, L);
    load_wd(wd, lb, tid >> 5, lane);
    TL(0, L * 32 + 25);
    const uint32_t* const xsrc = early(&g_x.cand[L][0][(tid >> 5) * 32 + t * 4]);
    float* const ydst = early(&g_x.ypart[L][(tid >> 5) * 16 + t * 4][c][g]);
    uint4 e;
    {
        uint32_t n = 0;
        #pragma unroll 1
        do { e = ld_x128(&g_x.hdr[L][blk * 8 + cb][lane & 15]); poll_tick(n); } while (warp_any(e.w == EMPTY && (lane & 15) != blk));
        if ((lane & 15) == blk) e = f;
        e = best_of(e, lane);
    }
    TL(0, L * 32 + 14);
    if (tid == 0) sts128(M_RT + 16 * L, (e.x & 0x80000000u) ? e.x ^ 0x80000000u : ~e.x, e.y, e.z, e.w);
    if (tid == 0) mbar_arrive(lb + B_RT);
    if (ffn) {
        const uint32_t* src = xsrc + (~e.x & 15u) * (D_ / 2);
        const Ln2 kx = ln2_coef(__uint_as_float(e.y), __uint_as_float(e.z));
        uint4 x[4];
        uint32_t n = 0;
        #pragma unroll 1
        do {
            x[0] = ld_x128(src); x[1] = ld_x128(src + 16); x[2] = ld_x128(src + 256); x[3] = ld_x128(src + 272);
            poll_tick(n);
        } while (warp_any(max(max(x[0].x, x[1].x), max(x[2].x, x[3].x)) == EMPTY));
        TL(0, L * 32 + 15);
        float d[4][4];
        #pragma unroll
        for (int i = 0; i < 4; i++) { d[i][0] = 0.f; d[i][1] = 0.f; d[i][2] = 0.f; d[i][3] = 0.f; }
        #pragma unroll
        for (int k = 0; k < 8; k++) {
            const uint32_t b0 = ln2((k & 1) ? x[k >> 1].z : x[k >> 1].x, kx), b1 = ln2((k & 1) ? x[k >> 1].w : x[k >> 1].y, kx);
            const uint32_t* f = (k < 4 ? wa : wb) + (k & 3) * 16;
            #pragma unroll
            for (int i = 0; i < 4; i++) mma_bf16(d[i], f[4*i], f[4*i+1], f[4*i+2], f[4*i+3], b0, b1);
        }
        #pragma unroll
        for (int h = 0; h < 2; h++) {
            const float a = (t & 1) ? d[1][2*h] : d[0][2*h], b = (t & 1) ? d[3][2*h] : d[2][2*h];
            stsf(M_RED + ((tid >> 5) * 64 + t * 16 + h * 8 + g) * 4, (t & 2) ? b : a);
        }
        named_sync(NB_CONS, 256);
        TL(0, L * 32 + 16);
        float2 v[8];
        #pragma unroll
        for (int i = 0; i < 8; i++) v[i] = lds64f(base32(M_RED + lane * 8) + i * 256);
        const float s0 = ((v[0].x + v[1].x) + (v[2].x + v[3].x)) + ((v[4].x + v[5].x) + (v[6].x + v[7].x));
        const float s1 = ((v[0].y + v[1].y) + (v[2].y + v[3].y)) + ((v[4].y + v[5].y) + (v[6].y + v[7].y));
        const uint32_t mine = pack_bf16(s0, s1), other = __shfl_xor_sync(0xffffffffu, mine, 16);
        const uint32_t gv = lane < 16 ? mine : other, uv = lane < 16 ? other : mine;
        const float g0 = bf_lo(gv), g1 = bf_hi(gv);
        const uint32_t hv = bmul2(pack_bf16(g0 * sigmoid(g0), g1 * sigmoid(g1)), uv);
        uint32_t hb[4];
        #pragma unroll
        for (int i = 0; i < 4; i++) hb[i] = __shfl_sync(0xffffffffu, hv, 4 * i + t);
        float y[8][4];
        #pragma unroll
        for (int i = 0; i < 8; i++) {
            y[i][0] = 0.f; y[i][1] = 0.f; y[i][2] = 0.f; y[i][3] = 0.f;
            mma_bf16(y[i], wd[8*i], wd[8*i+1], wd[8*i+2], wd[8*i+3], hb[0], hb[1]);
            mma_bf16(y[i], wd[8*i+4], wd[8*i+5], wd[8*i+6], wd[8*i+7], hb[2], hb[3]);
        }
        #pragma unroll
        for (int i = 0; i < 2; i++)
            #pragma unroll
            for (int h = 0; h < 2; h++) {
                const float a = (t & 1) ? y[2 + i][2*h] : y[i][2*h], b = (t & 1) ? y[6 + i][2*h] : y[4 + i][2*h];
                st_x32(ydst + (i * 2 + h) * (NFC * 8), __float_as_uint((t & 2) ? b : a));
            }
    }
    __syncwarp();
    mbar_arrive_elect(lb + B_FD);
    TL(0, L * 32 + 17);
}

__device__ __forceinline__ void qkv_load_w(const Maps& mp, uint32_t dst, int k, uint32_t fb) { tma_load3(dst, &mp.wqkv, nt_of(blockIdx.x) * 64, k * 64, 0, fb); }
__device__ __forceinline__ void qkv_load_x(const CUtensorMap* tx, uint32_t sa, int k, uint32_t fb) {
    #pragma unroll
    for (int a = 0; a < 2; a++) tma_load(sa + a * 16384, tx, k * 64, mt_of(blockIdx.x) * 256 + a * 128, fb);
}
__device__ __forceinline__ void producer_role(const Maps& mp) {
    const int c = blockIdx.x, mt = mt_of(c), nt = nt_of(c), blk = blk_of(c), cb = cb_of(c);
    const uint64_t pol = policy_evict_first();
    #pragma unroll 1
    for (int L = 0; L < 2; L++) {
        const uint32_t lb = M_BAR + L * BAR_SET;
        const CUtensorMap* tx = &mp.x[L];
        mbar_expect_tx(lb + B_SW, 49152);
        if (L == 0) {
            mbar_nap(lb + B_QF, 0);
            qkv_load_w(mp, SD_W, mt * 2, lb + B_SW);
            qkv_load_w(mp, SD_W + 24576, mt * 2 + 1, lb + B_SW);
        }
        {
            uint32_t st = 0, ph = L;
            #pragma unroll 1
            for (int k = L ? 0 : 3; k < 16; k++) {
                mbar_sleep(k < 2 ? M_BAR + (k ? B_FD : B_XS) : lb + B_QE + 8 * st, k < 2 ? 0 : ph);
                const uint32_t fb = lb + B_QF + 8 * st, sa = SB + st * Q_STB;
                mbar_expect_tx(fb, Q_STB);
                qkv_load_w(mp, sa + Q_ABYTES, k, fb);
                if (k == 0) {
                    mbar_nap(M_BAR + B_XD, 0);
                    flags16_wait(g_x.x[mt]);
                    fence_async_global();
                    mbar_nap(M_BAR + B_RT, 0);
                    TL(256, 32);
                }
                qkv_load_x(tx, sa, k, fb);
                if (L && k >= 3 && k < 7) tma_load(SD_W + (k - 3) * 12288, &mp.r, c * 24, (k - 3) * 256, lb + B_SW);
                if (++st == 3) { st = 0; ph ^= 1; }
            }
        }
        mbar_sleep(lb + B_QE, 1);
        TL(256, L * 32 + 26);
        mbar_arrive(lb + B_AF);
        {
            const char* kv = g_kv + (size_t)nt * 32 * KV_TILE;
            const uint8_t* fl = g_x.kv[L][nt * 2];
            __nanosleep(200);
            #pragma unroll 1
            for (int j = 1; j < 4; j++) {
                flag_wait(fl + ((2 * mt + j + 1) & 15));
                fence_async_global();
                const uint32_t bytes = j == 1 ? 8192 : 16384;
                mbar_expect_tx(lb + B_AF + 8 * j, bytes);
                bulk_load(A_RING + j * R_SLOT, kv + ((2 * mt + j) & 15) * KV_TILE, bytes, lb + B_AF + 8 * j);
                if (j == 1) TL(256, L * 32 + 21);
            }
            flags16_wait(fl);
            fence_async_global();
            int t0 = 2 * mt;
            #pragma unroll 1
            for (int it = 1; it < 8; it++) {
                #pragma unroll
                for (int u = 0; u < 4; u++) {
                    const char* src = kv + ((t0 + 4 * it + u) & 15) * KV_TILE;
                    const uint32_t fb = lb + B_AF + 8 * u, dst = A_RING + u * R_SLOT;
                    mbar_nap(lb + B_AE + 8 * u, (it - 1) & 1);
                    mbar_expect_tx(fb, 16384);
                    if (u < 3) bulk_load(dst, src, 16384, fb);
                    else {
                        bulk_load(dst + 8192, src + 8192, 8192, fb);
                        if (it == 3) {
                            flags16_wait(fl + 128);
                            fence_async_global();
                            kv += 16 * KV_TILE; src = kv + 15 * KV_TILE; t0 = 0;
                        }
                        bulk_load(dst, src, 8192, fb);
                    }
                }
            }
        }
        #pragma unroll 1
        for (int it = 0; it < 4; it++) {
            #pragma unroll
            for (int s = 0; s < 4; s++) {
                mbar_spin(lb + (it ? B_OE + 8 * s : s < 2 ? B_AE + 8 + 8 * s : B_FG), it ? (it - 1) & 1 : s < 2);
                const uint32_t fb = lb + B_OF + 8 * s;
                mbar_expect_tx(fb, 32768);
                #pragma unroll
                for (int b = 0; b < 2; b++)
                    tma_load5(o_b(s) + b * 8192, &mp.wo[it >> 1], cb * 128 + b * 64, (it & 1) * 8 + s * 2, fb);
                if (s == 0 && !(it & 1)) {
                    ctr_wait(g_x.o[L][blk][it >> 1], 15);
                    fence_async_global();
                    TL(256, L * 32 + 10);
                }
                tma_load(o_a(s), &mp.o, it * 256 + s * 64, blk * 128, fb);
            }
            if (it == 0) {
                mbar_spin(lb + B_AE + 24, 1);
                mbar_expect_tx(lb + B_RES, 32768);
                tma_load_s(XT0, tx, cb * 128, blk * 128, lb + B_RES, pol);
                tma_load_s(XT1, tx, cb * 128 + 64, blk * 128, lb + B_RES, pol);
            }
        }
        if (c < NFC) {
            #pragma unroll 1
            for (int i = 0; i < 4; i++) {
                mbar_spin(lb + B_OE + 16 + 8 * (i >> 1), 1);
                tma_load3_s(F_WD + i * 16384, &mp.d, 0, c * 32, i * 4, lb + B_WD, pol);
            }
        }
    }
}

__global__ void __launch_bounds__(384, 1) k_all(const __grid_constant__ Maps mp, const bf16* __restrict__ x0, const bf16* __restrict__ wo, const bf16* __restrict__ w_down,
                                                const bf16* __restrict__ w_r, bf16* __restrict__ out, const uint64_t dk0, const uint64_t dv0, const uint32_t ca, const uint32_t zero, const uint32_t sixteen) {
    extern __shared__ __align__(1024) char smem[];
    if (smem_u32(smem) != SB) __trap();
    const int warp = warp_uniform(threadIdx.x >> 5), wg = warp >> 2;
    TL(0, 0);
    if (warp == 8) {
      if (elect_one()) {
        tm_prefetch(&mp.x[0]); tm_prefetch(&mp.wqkv);
        #pragma unroll
        for (int s = 0; s < 3; s++) { mbar_init(M_BAR + B_QF + 8 * s, 1); mbar_init(M_BAR + BAR_SET + B_QF + 8 * s, 1); }
        fence_mbar_init();
        #pragma unroll 1
        for (int s = 0; s < 3; s++) {
            const uint32_t sa = SB + s * Q_STB, fb = M_BAR + B_QF + 8 * s;
            mbar_expect_tx(fb, Q_STB);
            qkv_load_x(&mp.x[0], sa, s, fb);
            qkv_load_w(mp, sa + Q_ABYTES, s, fb);
        }
      }
      __syncwarp();
    } else if (warp > 8) {
        if (elect_one()) {
            const uint32_t o0 = warp == 9 ? B_AF : warp == 10 ? B_QE : B_AE, o1 = warp == 9 ? B_QE : warp == 10 ? B_AE : B_END, cnt = warp == 9 ? 1 : warp == 10 ? 2 : 8;
            #pragma unroll 1
            for (uint32_t o = o0; o < o1; o += 8) { const uint32_t n = o == B_K0 ? 4 : cnt; mbar_init(M_BAR + o, n); mbar_init(M_BAR + BAR_SET + o, n); }
            fence_mbar_init();
        }
        __syncwarp();
    }
    __syncthreads();
    if (wg == 2) {
        reg_dec<40>();
        if (warp > 8) side_role(mp, x0, wo, w_down, w_r, out);
        else if (elect_one()) producer_role(mp);
    } else {
        reg_inc<232>();
        #pragma unroll 1
        for (int L = 0; L < 2; L++) {
            const uint32_t lb = M_BAR + L * BAR_SET;
            uint32_t qa[8], qb[8], sa[32], sb[32], wa[64];
            qkv_phase(L, lb, wg, qa, qb, sa, sb);
            attention_phase(L, lb, wg, qa, qb, sa, sb, dk0, dv0, ca, wa, zero, sixteen);
            tail_phase(L, lb, wg, wa);
        }
    }
}

typedef CUresult (*EncodeFn)(CUtensorMap*, CUtensorMapDataType, cuuint32_t, void*, const cuuint64_t*, const cuuint64_t*, const cuuint32_t*,
                             const cuuint32_t*, CUtensorMapInterleave, CUtensorMapSwizzle, CUtensorMapL2promotion, CUtensorMapFloatOOBfill);

void make_map(EncodeFn enc, CUtensorMap* tm, const void* ptr, int rank, const cuuint64_t* dims, const cuuint64_t* strides, const cuuint32_t* box, CUtensorMapSwizzle sw) {
    const cuuint32_t es[5] = {1, 1, 1, 1, 1};
    enc(tm, CU_TENSOR_MAP_DATA_TYPE_BFLOAT16, rank, const_cast<void*>(ptr), dims, strides, box, es, CU_TENSOR_MAP_INTERLEAVE_NONE, sw,
        box[0] == 64 ? CU_TENSOR_MAP_L2_PROMOTION_L2_128B : CU_TENSOR_MAP_L2_PROMOTION_NONE, CU_TENSOR_MAP_FLOAT_OOB_FILL_NONE);
}
void make_map2(EncodeFn enc, CUtensorMap* tm, const void* ptr, uint64_t cols, uint64_t rows, uint32_t bc, uint32_t br, CUtensorMapSwizzle sw) {
    const cuuint64_t dims[2] = {cols, rows}, strides[1] = {cols * 2};
    const cuuint32_t box[2] = {bc, br};
    make_map(enc, tm, ptr, 2, dims, strides, box, sw);
}

}

extern "C" void kernel_launch(void* const* d_in, const int* in_sizes, int n_in, void* d_out, int out_size) {
    const bf16* x0 = (const bf16*)d_in[0];
    const bf16* wqkv = (const bf16*)d_in[1];
    const bf16* wo = (const bf16*)d_in[2];
    const bf16* w_r = (const bf16*)d_in[4];
    const bf16* w_gate = (const bf16*)d_in[5];
    const bf16* w_up = (const bf16*)d_in[6];
    const bf16* w_down = (const bf16*)d_in[7];

    EncodeFn enc = nullptr;
    cudaDriverEntryPointQueryResult qr;
    cudaGetDriverEntryPoint("cuTensorMapEncodeTiled", (void**)&enc, cudaEnableDefault, &qr);
    void *p_o, *p_x1;
    cudaGetSymbolAddress(&p_o, g_o); cudaGetSymbolAddress(&p_x1, g_x1);
    const CUtensorMapSwizzle S128 = CU_TENSOR_MAP_SWIZZLE_128B, S64 = CU_TENSOR_MAP_SWIZZLE_64B, S0 = CU_TENSOR_MAP_SWIZZLE_NONE;
    Maps mp;
    make_map2(enc, &mp.x[0], x0, D_, S_, 64, 128, S128); make_map2(enc, &mp.x[1], p_x1, D_, S_, 64, 128, S128);
    make_map2(enc, &mp.o, p_o, D_, S_, 64, 128, S128);
    {
        const cuuint64_t dims[3] = {D_, D_, 3}, strides[2] = {3 * D_ * 2, D_ * 2};
        const cuuint32_t box[3] = {64, 64, 3};
        make_map(enc, &mp.wqkv, wqkv, 3, dims, strides, box, S128);
    }
    make_map2(enc, &mp.r, wqkv, 3 * D_, D_, 24, 256, S0);
    make_map2(enc, &mp.g, w_gate, FF, D_, 32, 256, S64); make_map2(enc, &mp.u, w_up, FF, D_, 32, 256, S64);
    for (int p = 0; p < 2; p++) {
        const cuuint64_t dims[5] = {D_, 2, 4, 4, 16}, strides[4] = {D_ * 2, 8 * D_ * 2, 2 * D_ * 2, 64 * D_ * 2};
        const cuuint32_t box[5] = {64, 2, 4, 4, 2};
        make_map(enc, &mp.wo[p], wo + (size_t)p * 32 * D_, 5, dims, strides, box, S128);
    }
    {
        const cuuint64_t dims[3] = {64, FF, 16}, strides[2] = {D_ * 2, 128};
        const cuuint32_t box[3] = {64, 32, 4};
        make_map(enc, &mp.d, w_down, 3, dims, strides, box, S128);
    }
    cudaFuncSetAttribute(k_all, cudaFuncAttributeMaxDynamicSharedMemorySize, K_SMEM);
    k_all<<<128, 384, K_SMEM, cudaStreamPerThread>>>(mp, x0, wo, w_down, w_r, (bf16*)d_out, desc_plain(A_RING, 2048, 128), desc_plain(A_RING + 8192, 128, 2048), 0x64A264A2u, 0u, 16u);
}
```

```cpp
#include <cuda_runtime.h>
#include <cuda_bf16.h>
#include <cuda_fp16.h>
#include <cuda.h>
#include <cudaTypedefs.h>
#include <stdint.h>

namespace {

typedef __nv_bfloat16 bf16;

constexpr int S_ = 2048, D_ = 1024, NH = 32, FF = 3584, NFC = FF / 32;
constexpr float LN_EPS = 1e-5f;
constexpr float QSCALE = 0.17677669529663687f * 1.4426950408889634f;
constexpr uint32_t EMPTY = 0xFFFFFFFFu;

constexpr int KV_TILE = 16384;
__device__ __align__(1024) char g_kv[NH * 16 * KV_TILE];
__device__ __align__(1024) bf16 g_o[S_ * D_];
__device__ __align__(1024) bf16 g_x1[S_ * D_];
__device__ __align__(16) float2 g_cs[8][3 * D_];
__device__ __align__(16) float2 g_rs0[S_];
__device__ uint4 g_qsave[128][29][256];
struct Xchg {
    uint4 part[2][16][8][128];
    float ypart[2][128][NFC][8];
    uint32_t cand[2][16][D_ / 2];
    uint4 hdr[2][128][16];
    float2 rs1[S_];
    float fix[3 * D_];
    uint32_t x2row[D_ / 2];
    uint8_t kv[2][NH][128];
    int o[2][16][2][32];
    uint8_t x[8][128];
};
constexpr int FILL = (sizeof(Xchg) / 128 + 127) / 128 * 8;
union XchgFill { Xchg x; uint4 fill[128][FILL]; };
static_assert(FILL > 768 && FILL <= 1024, "exchange area");
__device__ __align__(128) XchgFill g_u;
#define g_x g_u.x
__device__ int g_pctr;

constexpr uint32_t SMEM_BASE = 1024;

__device__ __forceinline__ int tid_now() { int v; asm volatile("mov.u32 %0, %%tid.x;" : "=r"(v)); return v; }
__device__ __forceinline__ int cta_now() { int v; asm volatile("mov.u32 %0, %%ctaid.x;" : "=r"(v)); return v; }
__device__ __forceinline__ uint64_t opaque(uint64_t v) { uint64_t r; asm volatile("mov.b64 %0, %1;" : "=l"(r) : "l"(v)); return r; }
__device__ __forceinline__ uint32_t base32(uint32_t v) { uint32_t r; asm("mov.b32 %0, %1;" : "=r"(r) : "r"(v)); return r; }
__device__ __forceinline__ uint32_t smem_u32(const void* p) { return (uint32_t)__cvta_generic_to_shared(p); }
__device__ __forceinline__ void mbar_init(uint32_t bar, int cnt) { asm volatile("mbarrier.init.shared::cta.b64 [%0], %1;" :: "r"(bar), "r"(cnt) : "memory"); }
__device__ __forceinline__ void mbar_expect_tx(uint32_t bar, uint32_t bytes) { asm volatile("mbarrier.arrive.expect_tx.shared::cta.b64 _, [%0], %1;" :: "r"(bar), "r"(bytes) : "memory"); }
__device__ __forceinline__ void mbar_arrive(uint32_t bar) { asm volatile("mbarrier.arrive.shared::cta.b64 _, [%0];" :: "r"(bar) : "memory"); }
__device__ __forceinline__ void mbar_sleep(uint32_t bar, uint32_t parity) {
    asm volatile("{\n.reg .pred p;\n.reg .u32 n;\nmov.u32 n, 0;\n"
                 "LAB_WAIT:\nmbarrier.try_wait.parity.shared::cta.b64 p, [%0], %1, 0x10000;\n@p bra LAB_DONE;\n"
                 "add.u32 n, n, 1;\nsetp.lt.u32 p, n, 0x10000;\n@p bra LAB_WAIT;\ntrap;\nLAB_DONE:\n}" :: "r"(bar), "r"(parity) : "memory");
}
__device__ __forceinline__ void mbar_nap(uint32_t bar, uint32_t parity) {
    asm volatile("{\n.reg .pred p;\nLAB_WAIT:\nmbarrier.try_wait.parity.shared::cta.b64 p, [%0], %1, 0x10000;\n@!p bra LAB_WAIT;\n}" :: "r"(bar), "r"(parity) : "memory");
}
__device__ __forceinline__ void mbar_spin(uint32_t bar, uint32_t parity) {
    asm volatile("{\n.reg .pred p;\nLAB_WAIT:\nmbarrier.try_wait.parity.shared::cta.b64 p, [%0], %1;\n@!p bra LAB_WAIT;\n}" :: "r"(bar), "r"(parity) : "memory");
}
__device__ __forceinline__ uint32_t mbar_test(uint32_t bar, uint32_t parity) {
    uint32_t ok;
    asm volatile("{\n.reg .pred p;\nmbarrier.test_wait.parity.shared::cta.b64 p, [%1], %2;\nselp.u32 %0, 1, 0, p;\n}" : "=r"(ok) : "r"(bar), "r"(parity) : "memory");
    return ok;
}
__device__ __forceinline__ bool elect_one() {
    uint32_t r;
    asm volatile("{\n.reg .pred p;\nelect.sync _|p, 0xffffffff;\nselp.u32 %0, 1, 0, p;\n}" : "=r"(r));
    return r != 0;
}
__device__ __forceinline__ void mbar_arrive_elect(uint32_t bar) {
    asm volatile("{\n.reg .pred p;\nelect.sync _|p, 0xffffffff;\n@p mbarrier.arrive.shared::cta.b64 _, [%0];\n}" :: "r"(bar) : "memory");
}
__device__ __forceinline__ void mbar_arrive_elect_p(uint32_t bar, uint32_t on) {
    asm volatile("{\n.reg .pred p, q;\nelect.sync _|p, 0xffffffff;\nsetp.ne.and.u32 q, %1, 0, p;\n@q mbarrier.arrive.shared::cta.b64 _, [%0];\n}" :: "r"(bar), "r"(on) : "memory");
}
__device__ __forceinline__ int warp_uniform(int v) { return __shfl_sync(0xffffffffu, v, 0); }
__device__ __forceinline__ void fence_mbar_init() { asm volatile("fence.mbarrier_init.release.cluster;" ::: "memory"); }
__device__ __forceinline__ void fence_async_smem() { asm volatile("fence.proxy.async.shared::cta;" ::: "memory"); }
__device__ __forceinline__ void fence_async_global() { asm volatile("fence.proxy.async.global;" ::: "memory"); }
__device__ __forceinline__ void named_sync(int id, int n) { asm volatile("bar.sync %0, %1;" :: "r"(id), "r"(n) : "memory"); }
__device__ __forceinline__ void named_arrive(int id, int n) { asm volatile("bar.arrive %0, %1;" :: "r"(id), "r"(n) : "memory"); }
__device__ __forceinline__ void bulk_load(uint32_t dst, const void* src, uint32_t bytes, uint32_t bar) {
    asm volatile("cp.async.bulk.shared::cluster.global.mbarrier::complete_tx::bytes [%0], [%1], %2, [%3];" :: "r"(dst), "l"(src), "r"(bytes), "r"(bar) : "memory");
}
__device__ __forceinline__ void bulk_store(void* dst, uint32_t src, uint32_t bytes) {
    asm volatile("cp.async.bulk.global.shared::cta.bulk_group [%0], [%1], %2;" :: "l"(dst), "r"(src), "r"(bytes) : "memory");
}
__device__ __forceinline__ void bulk_commit() { asm volatile("cp.async.bulk.commit_group;" ::: "memory"); }
__device__ __forceinline__ void bulk_wait() { asm volatile("cp.async.bulk.wait_group 0;" ::: "memory"); }
__device__ __forceinline__ void l2_prefetch(const void* src, uint32_t bytes) {
    asm volatile("cp.async.bulk.prefetch.L2.global [%0], %1;" :: "l"(src), "r"(bytes) : "memory");
}
__device__ __forceinline__ void tma_load(uint32_t dst, const CUtensorMap* tm, int c0, int c1, uint32_t bar) {
    asm volatile("cp.async.bulk.tensor.2d.shared::cluster.global.mbarrier::complete_tx::bytes [%0], [%1, {%3, %4}], [%2];"
                 :: "r"(dst), "l"(tm), "r"(bar), "r"(c0), "r"(c1) : "memory");
}
__device__ __forceinline__ void tma_load3(uint32_t dst, const CUtensorMap* tm, int c0, int c1, int c2, uint32_t bar) {
    asm volatile("cp.async.bulk.tensor.3d.shared::cluster.global.mbarrier::complete_tx::bytes [%0], [%1, {%3, %4, %5}], [%2];"
                 :: "r"(dst), "l"(tm), "r"(bar), "r"(c0), "r"(c1), "r"(c2) : "memory");
}
__device__ __forceinline__ void tma_load5(uint32_t dst, const CUtensorMap* tm, int c0, int c4, uint32_t bar) {
    asm volatile("cp.async.bulk.tensor.5d.shared::cluster.global.mbarrier::complete_tx::bytes [%0], [%1, {%3, %5, %5, %5, %4}], [%2];"
                 :: "r"(dst), "l"(tm), "r"(bar), "r"(c0), "r"(c4), "r"(0) : "memory");
}
__device__ __forceinline__ uint64_t policy_evict_first() { uint64_t p; asm volatile("createpolicy.fractional.L2::evict_first.b64 %0, 1.0;" : "=l"(p)); return p; }
__device__ __forceinline__ void tma_load_s(uint32_t dst, const CUtensorMap* tm, int c0, int c1, uint32_t bar, uint64_t pol) {
    asm volatile("cp.async.bulk.tensor.2d.shared::cluster.global.mbarrier::complete_tx::bytes.L2::cache_hint [%0], [%1, {%3, %4}], [%2], %5;"
                 :: "r"(dst), "l"(tm), "r"(bar), "r"(c0), "r"(c1), "l"(pol) : "memory");
}
__device__ __forceinline__ void tma_load3_s(uint32_t dst, const CUtensorMap* tm, int c0, int c1, int c2, uint32_t bar, uint64_t pol) {
    asm volatile("cp.async.bulk.tensor.3d.shared::cluster.global.mbarrier::complete_tx::bytes.L2::cache_hint [%0], [%1, {%3, %4, %5}], [%2], %6;"
                 :: "r"(dst), "l"(tm), "r"(bar), "r"(c0), "r"(c1), "r"(c2), "l"(pol) : "memory");
}
__device__ __forceinline__ void tma_store(const CUtensorMap* tm, uint32_t src, int c0, int c1) {
    asm volatile("cp.async.bulk.tensor.2d.global.shared::cta.bulk_group [%0, {%2, %3}], [%1];" :: "l"(tm), "r"(src), "r"(c0), "r"(c1) : "memory");
}
__device__ __forceinline__ void tma_prefetch(const CUtensorMap* tm, int c0, int c1) {
    asm volatile("cp.async.bulk.prefetch.tensor.2d.L2.global [%0, {%1, %2}];" :: "l"(tm), "r"(c0), "r"(c1) : "memory");
}
__device__ __forceinline__ void tm_prefetch(const CUtensorMap* tm) { asm volatile("prefetch.tensormap [%0];" :: "l"(tm) : "memory"); }
__device__ __forceinline__ void wg_fence() { asm volatile("wgmma.fence.sync.aligned;" ::: "memory"); }
__device__ __forceinline__ void wg_commit() { asm volatile("wgmma.commit_group.sync.aligned;" ::: "memory"); }
template <int N> __device__ __forceinline__ void wg_wait() { asm volatile("wgmma.wait_group.sync.aligned %0;" :: "n"(N) : "memory"); }
template <int N> __device__ __forceinline__ void pin(uint32_t (&r)[N]) {
    #pragma unroll
    for (int i = 0; i < N; i++) asm volatile("" : "+r"(r[i]) :: "memory");
}
template <int N> __device__ __forceinline__ void pin(float (&r)[N]) {
    #pragma unroll
    for (int i = 0; i < N; i++) asm volatile("" : "+f"(r[i]) :: "memory");
}
template <int N> __device__ __forceinline__ void reg_inc() { asm volatile("setmaxnreg.inc.sync.aligned.u32 %0;" :: "n"(N)); }
template <int N> __device__ __forceinline__ void reg_dec() { asm volatile("setmaxnreg.dec.sync.aligned.u32 %0;" :: "n"(N)); }
__host__ __device__ constexpr uint64_t desc_plain(uint32_t addr, uint32_t lbo, uint32_t sbo) {
    return (uint64_t)((addr & 0x3FFFF) >> 4) | ((uint64_t)(lbo >> 4) << 16) | ((uint64_t)(sbo >> 4) << 32);
}
__host__ __device__ constexpr uint64_t desc_sw128(uint32_t addr, uint32_t lbo, uint32_t sbo) { return desc_plain(addr, lbo, sbo) | (1ull << 62); }
__host__ __device__ constexpr uint64_t desc_sw64(uint32_t addr, uint32_t lbo, uint32_t sbo) { return desc_plain(addr, lbo, sbo) | (2ull << 62); }

__device__ __forceinline__ uint32_t lds32(uint32_t a) { uint32_t v; asm volatile("ld.shared.b32 %0, [%1];" : "=r"(v) : "r"(a) : "memory"); return v; }
__device__ __forceinline__ uint32_t lds16(uint32_t a) { uint32_t v; asm volatile("ld.shared.u16 %0, [%1];" : "=r"(v) : "r"(a) : "memory"); return v; }
__device__ __forceinline__ float ldsf(uint32_t a) { return __uint_as_float(lds32(a)); }
__device__ __forceinline__ float2 lds64f(uint32_t a) { float2 v; asm volatile("ld.shared.v2.f32 {%0, %1}, [%2];" : "=f"(v.x), "=f"(v.y) : "r"(a) : "memory"); return v; }
__device__ __forceinline__ uint4 lds128(uint32_t a) { uint4 v; asm volatile("ld.shared.v4.b32 {%0, %1, %2, %3}, [%4];" : "=r"(v.x), "=r"(v.y), "=r"(v.z), "=r"(v.w) : "r"(a) : "memory"); return v; }
__device__ __forceinline__ void sts16(uint32_t a, uint32_t v) { asm volatile("st.shared.b16 [%0], %1;" :: "r"(a), "h"((uint16_t)v) : "memory"); }
__device__ __forceinline__ void sts32(uint32_t a, uint32_t v) { asm volatile("st.shared.b32 [%0], %1;" :: "r"(a), "r"(v) : "memory"); }
__device__ __forceinline__ void stsf(uint32_t a, float v) { sts32(a, __float_as_uint(v)); }
__device__ __forceinline__ void sts64(uint32_t a, uint32_t x, uint32_t y) { asm volatile("st.shared.v2.b32 [%0], {%1, %2};" :: "r"(a), "r"(x), "r"(y) : "memory"); }
__device__ __forceinline__ void sts128(uint32_t a, uint32_t x, uint32_t y, uint32_t z, uint32_t w) { asm volatile("st.shared.v4.b32 [%0], {%1, %2, %3, %4};" :: "r"(a), "r"(x), "r"(y), "r"(z), "r"(w) : "memory"); }
__device__ __forceinline__ void stsm4(uint32_t a, uint32_t x, uint32_t y, uint32_t z, uint32_t w) {
    asm volatile("stmatrix.sync.aligned.m8n8.x4.shared.b16 [%0], {%1, %2, %3, %4};" :: "r"(a), "r"(x), "r"(y), "r"(z), "r"(w) : "memory");
}
__device__ __forceinline__ void ldsm4(uint32_t& a0, uint32_t& a1, uint32_t& a2, uint32_t& a3, uint32_t addr) {
    asm volatile("ldmatrix.sync.aligned.m8n8.x4.shared.b16 {%0,%1,%2,%3}, [%4];" : "=r"(a0), "=r"(a1), "=r"(a2), "=r"(a3) : "r"(addr) : "memory");
}
__device__ __forceinline__ void ldsm4t(uint32_t& a0, uint32_t& a1, uint32_t& a2, uint32_t& a3, uint32_t addr) {
    asm volatile("ldmatrix.sync.aligned.m8n8.x4.trans.shared.b16 {%0,%1,%2,%3}, [%4];" : "=r"(a0), "=r"(a1), "=r"(a2), "=r"(a3) : "r"(addr) : "memory");
}
__device__ __forceinline__ void mma_bf16(float (&d)[4], uint32_t a0, uint32_t a1, uint32_t a2, uint32_t a3, uint32_t b0, uint32_t b1) {
    asm("mma.sync.aligned.m16n8k16.row.col.f32.bf16.bf16.f32 {%0,%1,%2,%3}, {%4,%5,%6,%7}, {%8,%9}, {%0,%1,%2,%3};"
        : "+f"(d[0]), "+f"(d[1]), "+f"(d[2]), "+f"(d[3]) : "r"(a0), "r"(a1), "r"(a2), "r"(a3), "r"(b0), "r"(b1));
}
__device__ __forceinline__ void mma_bf16_k8(float (&d)[4], uint32_t a0, uint32_t a1, uint32_t b0) {
    asm("mma.sync.aligned.m16n8k8.row.col.f32.bf16.bf16.f32 {%0,%1,%2,%3}, {%4,%5}, {%6}, {%0,%1,%2,%3};"
        : "+f"(d[0]), "+f"(d[1]), "+f"(d[2]), "+f"(d[3]) : "r"(a0), "r"(a1), "r"(b0));
}
__device__ __forceinline__ void mma_f16(float (&d)[4], uint32_t a0, uint32_t a1, uint32_t a2, uint32_t a3, uint32_t b0, uint32_t b1) {
    asm("mma.sync.aligned.m16n8k16.row.col.f32.f16.f16.f32 {%0,%1,%2,%3}, {%4,%5,%6,%7}, {%8,%9}, {%0,%1,%2,%3};"
        : "+f"(d[0]), "+f"(d[1]), "+f"(d[2]), "+f"(d[3]) : "r"(a0), "r"(a1), "r"(a2), "r"(a3), "r"(b0), "r"(b1));
}
__device__ __forceinline__ void stg128_pred(void* p, const uint4& v, bool on) {
    asm volatile("{\n.reg .pred q;\nsetp.ne.u32 q, %5, 0;\n@q st.global.v4.b32 [%0], {%1, %2, %3, %4};\n}"
                 :: "l"(p), "r"(v.x), "r"(v.y), "r"(v.z), "r"(v.w), "r"((uint32_t)on) : "memory");
}
__device__ __forceinline__ void st_x32(void* p, uint32_t v) { asm volatile("st.relaxed.gpu.global.u32 [%0], %1;" :: "l"(p), "r"(v) : "memory"); }
__device__ __forceinline__ void st_x64(void* p, uint32_t x, uint32_t y) {
    asm volatile("{\n.reg .b64 v;\nmov.b64 v, {%1, %2};\nst.relaxed.gpu.global.b64 [%0], v;\n}" :: "l"(p), "r"(x), "r"(y) : "memory");
}
__device__ __forceinline__ void st_x128(void* p, uint32_t x, uint32_t y, uint32_t z, uint32_t w) {
    asm volatile("{\n.reg .b64 a, b;\n.reg .b128 v;\nmov.b64 a, {%1, %2};\nmov.b64 b, {%3, %4};\nmov.b128 v, {a, b};\nst.relaxed.gpu.global.b128 [%0], v;\n}"
                 :: "l"(p), "r"(x), "r"(y), "r"(z), "r"(w) : "memory");
}
__device__ __forceinline__ void st_x128_if(bool on, void* p, uint32_t x, uint32_t y, uint32_t z, uint32_t w) {
    asm volatile("{\n.reg .pred q;\n.reg .b64 a, b;\n.reg .b128 v;\nsetp.ne.u32 q, %5, 0;\nmov.b64 a, {%1, %2};\nmov.b64 b, {%3, %4};\nmov.b128 v, {a, b};\n"
                 "@q st.relaxed.gpu.global.b128 [%0], v;\n}" :: "l"(p), "r"(x), "r"(y), "r"(z), "r"(w), "r"((uint32_t)on) : "memory");
}
__device__ __forceinline__ uint32_t ld_x32(const void* p) { uint32_t v; asm volatile("ld.relaxed.gpu.global.u32 %0, [%1];" : "=r"(v) : "l"(p) : "memory"); return v; }
__device__ __forceinline__ uint2 ld_x64(const void* p) {
    uint2 v; asm volatile("{\n.reg .b64 a;\nld.relaxed.gpu.global.b64 a, [%2];\nmov.b64 {%0, %1}, a;\n}" : "=r"(v.x), "=r"(v.y) : "l"(p) : "memory"); return v;
}
__device__ __forceinline__ uint4 ld_x128(const void* p) {
    uint4 v;
    asm volatile("{\n.reg .b64 a, b;\n.reg .b128 v;\nld.relaxed.gpu.global.b128 v, [%4];\nmov.b128 {a, b}, v;\nmov.b64 {%0, %1}, a;\nmov.b64 {%2, %3}, b;\n}"
                 : "=r"(v.x), "=r"(v.y), "=r"(v.z), "=r"(v.w) : "l"(p) : "memory");
    return v;
}
__device__ __forceinline__ void poll_tick(uint32_t& n) { asm volatile("{\n.reg .pred p;\nadd.u32 %0, %0, 1;\nsetp.ge.u32 p, %0, 0x800000;\n@p st.global.u32 [%1], %0;\n}" : "+r"(n) : "l"(0ull)); }
__device__ __forceinline__ void ctr_arrive(int* c) { asm volatile("red.release.gpu.global.add.s32 [%0], 1;" :: "l"(c) : "memory"); }
__device__ __forceinline__ void ctr_wait(const int* c, int target) {
    int v;
    uint32_t n = 0;
    #pragma unroll 1
    do {
        asm volatile("ld.acquire.gpu.global.s32 %0, [%1];" : "=r"(v) : "l"(c) : "memory");
        poll_tick(n);
    } while (v < target);
}
__device__ __forceinline__ void flag_wait(const uint8_t* f) {
    uint32_t n = 0, v;
    #pragma unroll 1
    do { asm volatile("ld.acquire.gpu.global.u8 %0, [%1];" : "=r"(v) : "l"(f) : "memory"); poll_tick(n); } while (v);
}
__device__ __forceinline__ void flags16_wait(const uint8_t* f) {
    uint32_t n = 0;
    uint64_t v;
    #pragma unroll 1
    do {
        asm volatile("{\n.reg .b64 a, b;\n.reg .b128 v;\nld.acquire.gpu.global.b128 v, [%1];\nmov.b128 {a, b}, v;\nor.b64 %0, a, b;\n}" : "=l"(v) : "l"(f) : "memory");
        poll_tick(n);
    } while (v != 0);
}
__device__ __forceinline__ bool any_empty(const uint4& v) { return v.x == EMPTY || v.y == EMPTY || v.z == EMPTY || v.w == EMPTY; }
__device__ __forceinline__ bool warp_any(bool p) { return __any_sync(0xffffffffu, p); }

__device__ __forceinline__ float ex2(float x) { float y; asm("ex2.approx.ftz.f32 %0, %1;" : "=f"(y) : "f"(x)); return y; }
__device__ __forceinline__ float rsq(float x) { float y; asm("rsqrt.approx.ftz.f32 %0, %1;" : "=f"(y) : "f"(x)); return y; }
__device__ __forceinline__ float rcp(float x) { float y; asm("rcp.approx.ftz.f32 %0, %1;" : "=f"(y) : "f"(x)); return y; }
__device__ __forceinline__ float sigmoid(float x) { return rcp(1.f + ex2(x * -1.4426950408889634f)); }
__device__ __forceinline__ uint32_t pack_bf16(float lo, float hi) { uint32_t r; asm("cvt.rn.bf16x2.f32 %0, %1, %2;" : "=r"(r) : "f"(hi), "f"(lo)); return r; }
__device__ __forceinline__ uint32_t pack_f16(float lo, float hi) { uint32_t r; asm("cvt.rn.f16x2.f32 %0, %1, %2;" : "=r"(r) : "f"(hi), "f"(lo)); return r; }
__device__ __forceinline__ float bf_lo(uint32_t v) { return __uint_as_float(v << 16); }
__device__ __forceinline__ float bf_hi(uint32_t v) { return __uint_as_float(v & 0xFFFF0000u); }
__device__ __forceinline__ float bf_round(float x) { return __uint_as_float(pack_bf16(0.f, x)); }
__device__ __forceinline__ void h2_unpack(uint32_t v, float& lo, float& hi) {
    asm("{.reg .f16 l, h; mov.b32 {l, h}, %2; cvt.f32.f16 %0, l; cvt.f32.f16 %1, h;}" : "=f"(lo), "=f"(hi) : "r"(v));
}
__device__ __forceinline__ uint32_t hadd2(uint32_t a, uint32_t b) { uint32_t r; asm("add.rn.f16x2 %0, %1, %2;" : "=r"(r) : "r"(a), "r"(b)); return r; }
__device__ __forceinline__ uint32_t hmax2(uint32_t a, uint32_t b) { uint32_t r; asm("max.f16x2 %0, %1, %2;" : "=r"(r) : "r"(a), "r"(b)); return r; }
__device__ __forceinline__ uint32_t badd2(uint32_t a, uint32_t b) { uint32_t r; asm("add.rn.bf16x2 %0, %1, %2;" : "=r"(r) : "r"(a), "r"(b)); return r; }
__device__ __forceinline__ uint32_t bmul2(uint32_t a, uint32_t b) { uint32_t r; asm("mul.rn.bf16x2 %0, %1, %2;" : "=r"(r) : "r"(a), "r"(b)); return r; }
__device__ __forceinline__ float warp_sum(float v) {
    #pragma unroll
    for (int o = 16; o > 0; o >>= 1) v += __shfl_xor_sync(0xffffffffu, v, o);
    return v;
}
__device__ __forceinline__ float quad_sum(float v) { v += __shfl_xor_sync(0xffffffffu, v, 1); return v + __shfl_xor_sync(0xffffffffu, v, 2); }
__device__ __forceinline__ float quad_max(float v) { v = fmaxf(v, __shfl_xor_sync(0xffffffffu, v, 1)); return fmaxf(v, __shfl_xor_sync(0xffffffffu, v, 2)); }
__device__ __forceinline__ uint32_t redux_max(uint32_t v) { uint32_t r; asm volatile("redux.sync.max.u32 %0, %1, 0xffffffff;" : "=r"(r) : "r"(v)); return r; }
__device__ __forceinline__ uint32_t redux_min(uint32_t v) { uint32_t r; asm volatile("redux.sync.min.u32 %0, %1, 0xffffffff;" : "=r"(r) : "r"(v)); return r; }
__device__ __forceinline__ uint32_t order_bits(float r) { const uint32_t u = __float_as_uint(r); return (u & 0x80000000u) ? ~u : (u | 0x80000000u); }
struct Ln2 { uint32_t nm, rh, rl, c; };
__device__ __forceinline__ Ln2 ln2_coef(float mean, float rstd) {
    const uint32_t a = pack_bf16(-mean, rstd), b = pack_bf16((-mean - bf_lo(a)) * rstd, rstd - bf_hi(a));
    return {__byte_perm(a, 0, 0x1010), __byte_perm(a, 0, 0x3232), __byte_perm(b, 0, 0x3232), __byte_perm(b, 0, 0x1010)};
}
__device__ __forceinline__ uint32_t bfma2(uint32_t a, uint32_t b, uint32_t c) { uint32_t r; asm("fma.rn.bf16x2 %0, %1, %2, %3;" : "=r"(r) : "r"(a), "r"(b), "r"(c)); return r; }
__device__ __forceinline__ uint32_t ln2(uint32_t v, const Ln2& k) { const uint32_t d = badd2(v, k.nm); return bfma2(d, k.rh, bfma2(d, k.rl, k.c)); }
__device__ __forceinline__ uint32_t add_ln2(uint32_t v, const Ln2& k) { return badd2(v, ln2(v, k)); }

#define TL(TID, i)
#define CK(TID, i)

__device__ __forceinline__ void wg_gemm_n128(float (&d)[64], uint64_t desca, uint64_t desc) {
    asm volatile("{\n.reg .pred p;\nsetp.ne.b32 p, 1, 0;\n"
        "wgmma.mma_async.sync.aligned.m64n128k16.f32.bf16.bf16 "
        "{%0,%1,%2,%3,%4,%5,%6,%7,%8,%9,%10,%11,%12,%13,%14,%15,%16,%17,%18,%19,%20,%21,%22,%23,%24,%25,%26,%27,%28,%29,%30,%31,%32,%33,%34,%35,%36,%37,%38,%39,%40,%41,%42,%43,%44,%45,%46,%47,%48,%49,%50,%51,%52,%53,%54,%55,%56,%57,%58,%59,%60,%61,%62,%63}, "
        "%64, %65, p, 1, 1, 0, 1;\n}\n"
        : "+f"(d[0]), "+f"(d[1]), "+f"(d[2]), "+f"(d[3]), "+f"(d[4]), "+f"(d[5]), "+f"(d[6]), "+f"(d[7]), "+f"(d[8]), "+f"(d[9]), "+f"(d[10]), "+f"(d[11]),
          "+f"(d[12]), "+f"(d[13]), "+f"(d[14]), "+f"(d[15]), "+f"(d[16]), "+f"(d[17]), "+f"(d[18]), "+f"(d[19]), "+f"(d[20]), "+f"(d[21]), "+f"(d[22]), "+f"(d[23]),
          "+f"(d[24]), "+f"(d[25]), "+f"(d[26]), "+f"(d[27]), "+f"(d[28]), "+f"(d[29]), "+f"(d[30]), "+f"(d[31]), "+f"(d[32]), "+f"(d[33]), "+f"(d[34]), "+f"(d[35]),
          "+f"(d[36]), "+f"(d[37]), "+f"(d[38]), "+f"(d[39]), "+f"(d[40]), "+f"(d[41]), "+f"(d[42]), "+f"(d[43]), "+f"(d[44]), "+f"(d[45]), "+f"(d[46]), "+f"(d[47]),
          "+f"(d[48]), "+f"(d[49]), "+f"(d[50]), "+f"(d[51]), "+f"(d[52]), "+f"(d[53]), "+f"(d[54]), "+f"(d[55]), "+f"(d[56]), "+f"(d[57]), "+f"(d[58]), "+f"(d[59]),
          "+f"(d[60]), "+f"(d[61]), "+f"(d[62]), "+f"(d[63])
        : "l"(desca), "l"(desc));
}
__device__ __forceinline__ void wg_gemm_n192(float (&d)[96], uint64_t desca, uint64_t desc) {
    asm volatile("{\n.reg .pred p;\nsetp.ne.b32 p, 1, 0;\n"
        "wgmma.mma_async.sync.aligned.m64n192k16.f32.bf16.bf16 "
        "{%0,%1,%2,%3,%4,%5,%6,%7,%8,%9,%10,%11,%12,%13,%14,%15,%16,%17,%18,%19,%20,%21,%22,%23,%24,%25,%26,%27,%28,%29,%30,%31,%32,%33,%34,%35,%36,%37,%38,%39,%40,%41,%42,%43,%44,%45,%46,%47,%48,%49,%50,%51,%52,%53,%54,%55,%56,%57,%58,%59,%60,%61,%62,%63,%64,%65,%66,%67,%68,%69,%70,%71,%72,%73,%74,%75,%76,%77,%78,%79,%80,%81,%82,%83,%84,%85,%86,%87,%88,%89,%90,%91,%92,%93,%94,%95}, "
        "%96, %97, p, 1, 1, 0, 1;\n}\n"
        : "+f"(d[0]), "+f"(d[1]), "+f"(d[2]), "+f"(d[3]), "+f"(d[4]), "+f"(d[5]), "+f"(d[6]), "+f"(d[7]), "+f"(d[8]), "+f"(d[9]), "+f"(d[10]), "+f"(d[11]),
          "+f"(d[12]), "+f"(d[13]), "+f"(d[14]), "+f"(d[15]), "+f"(d[16]), "+f"(d[17]), "+f"(d[18]), "+f"(d[19]), "+f"(d[20]), "+f"(d[21]), "+f"(d[22]), "+f"(d[23]),
          "+f"(d[24]), "+f"(d[25]), "+f"(d[26]), "+f"(d[27]), "+f"(d[28]), "+f"(d[29]), "+f"(d[30]), "+f"(d[31]), "+f"(d[32]), "+f"(d[33]), "+f"(d[34]), "+f"(d[35]),
          "+f"(d[36]), "+f"(d[37]), "+f"(d[38]), "+f"(d[39]), "+f"(d[40]), "+f"(d[41]), "+f"(d[42]), "+f"(d[43]), "+f"(d[44]), "+f"(d[45]), "+f"(d[46]), "+f"(d[47]),
          "+f"(d[48]), "+f"(d[49]), "+f"(d[50]), "+f"(d[51]), "+f"(d[52]), "+f"(d[53]), "+f"(d[54]), "+f"(d[55]), "+f"(d[56]), "+f"(d[57]), "+f"(d[58]), "+f"(d[59]),
          "+f"(d[60]), "+f"(d[61]), "+f"(d[62]), "+f"(d[63]), "+f"(d[64]), "+f"(d[65]), "+f"(d[66]), "+f"(d[67]), "+f"(d[68]), "+f"(d[69]), "+f"(d[70]), "+f"(d[71]),
          "+f"(d[72]), "+f"(d[73]), "+f"(d[74]), "+f"(d[75]), "+f"(d[76]), "+f"(d[77]), "+f"(d[78]), "+f"(d[79]), "+f"(d[80]), "+f"(d[81]), "+f"(d[82]), "+f"(d[83]),
          "+f"(d[84]), "+f"(d[85]), "+f"(d[86]), "+f"(d[87]), "+f"(d[88]), "+f"(d[89]), "+f"(d[90]), "+f"(d[91]), "+f"(d[92]), "+f"(d[93]), "+f"(d[94]), "+f"(d[95])
        : "l"(desca), "l"(desc));
}
__device__ __forceinline__ void wg_gemm_n192_init(float (&d)[96], uint64_t desca, uint64_t desc) {
    asm volatile("{\n.reg .pred p;\nsetp.ne.b32 p, 0, 0;\n"
        "wgmma.mma_async.sync.aligned.m64n192k16.f32.bf16.bf16 "
        "{%0,%1,%2,%3,%4,%5,%6,%7,%8,%9,%10,%11,%12,%13,%14,%15,%16,%17,%18,%19,%20,%21,%22,%23,%24,%25,%26,%27,%28,%29,%30,%31,%32,%33,%34,%35,%36,%37,%38,%39,%40,%41,%42,%43,%44,%45,%46,%47,%48,%49,%50,%51,%52,%53,%54,%55,%56,%57,%58,%59,%60,%61,%62,%63,%64,%65,%66,%67,%68,%69,%70,%71,%72,%73,%74,%75,%76,%77,%78,%79,%80,%81,%82,%83,%84,%85,%86,%87,%88,%89,%90,%91,%92,%93,%94,%95}, "
        "%96, %97, p, 1, 1, 0, 1;\n}\n"
        : "=f"(d[0]), "=f"(d[1]), "=f"(d[2]), "=f"(d[3]), "=f"(d[4]), "=f"(d[5]), "=f"(d[6]), "=f"(d[7]), "=f"(d[8]), "=f"(d[9]), "=f"(d[10]), "=f"(d[11]),
          "=f"(d[12]), "=f"(d[13]), "=f"(d[14]), "=f"(d[15]), "=f"(d[16]), "=f"(d[17]), "=f"(d[18]), "=f"(d[19]), "=f"(d[20]), "=f"(d[21]), "=f"(d[22]), "=f"(d[23]),
          "=f"(d[24]), "=f"(d[25]), "=f"(d[26]), "=f"(d[27]), "=f"(d[28]), "=f"(d[29]), "=f"(d[30]), "=f"(d[31]), "=f"(d[32]), "=f"(d[33]), "=f"(d[34]), "=f"(d[35]),
          "=f"(d[36]), "=f"(d[37]), "=f"(d[38]), "=f"(d[39]), "=f"(d[40]), "=f"(d[41]), "=f"(d[42]), "=f"(d[43]), "=f"(d[44]), "=f"(d[45]), "=f"(d[46]), "=f"(d[47]),
          "=f"(d[48]), "=f"(d[49]), "=f"(d[50]), "=f"(d[51]), "=f"(d[52]), "=f"(d[53]), "=f"(d[54]), "=f"(d[55]), "=f"(d[56]), "=f"(d[57]), "=f"(d[58]), "=f"(d[59]),
          "=f"(d[60]), "=f"(d[61]), "=f"(d[62]), "=f"(d[63]), "=f"(d[64]), "=f"(d[65]), "=f"(d[66]), "=f"(d[67]), "=f"(d[68]), "=f"(d[69]), "=f"(d[70]), "=f"(d[71]),
          "=f"(d[72]), "=f"(d[73]), "=f"(d[74]), "=f"(d[75]), "=f"(d[76]), "=f"(d[77]), "=f"(d[78]), "=f"(d[79]), "=f"(d[80]), "=f"(d[81]), "=f"(d[82]), "=f"(d[83]),
          "=f"(d[84]), "=f"(d[85]), "=f"(d[86]), "=f"(d[87]), "=f"(d[88]), "=f"(d[89]), "=f"(d[90]), "=f"(d[91]), "=f"(d[92]), "=f"(d[93]), "=f"(d[94]), "=f"(d[95])
        : "l"(desca), "l"(desc));
}
__device__ __forceinline__ void wg_qk_init(uint32_t (&d)[32], uint32_t a0, uint32_t a1, uint32_t a2, uint32_t a3, uint64_t desc) {
    asm volatile("{\n.reg .pred p;\nsetp.ne.b32 p, 0, 0;\n"
        "wgmma.mma_async.sync.aligned.m64n128k16.f16.f16.f16 "
        "{%0,%1,%2,%3,%4,%5,%6,%7,%8,%9,%10,%11,%12,%13,%14,%15,%16,%17,%18,%19,%20,%21,%22,%23,%24,%25,%26,%27,%28,%29,%30,%31}, "
        "{%32,%33,%34,%35}, %36, p, 1, 1, 0;\n}\n"
        : "=r"(d[0]), "=r"(d[1]), "=r"(d[2]), "=r"(d[3]), "=r"(d[4]), "=r"(d[5]), "=r"(d[6]), "=r"(d[7]), "=r"(d[8]), "=r"(d[9]), "=r"(d[10]), "=r"(d[11]),
          "=r"(d[12]), "=r"(d[13]), "=r"(d[14]), "=r"(d[15]), "=r"(d[16]), "=r"(d[17]), "=r"(d[18]), "=r"(d[19]), "=r"(d[20]), "=r"(d[21]), "=r"(d[22]), "=r"(d[23]),
          "=r"(d[24]), "=r"(d[25]), "=r"(d[26]), "=r"(d[27]), "=r"(d[28]), "=r"(d[29]), "=r"(d[30]), "=r"(d[31])
        : "r"(a0), "r"(a1), "r"(a2), "r"(a3), "l"(desc));
}
__device__ __forceinline__ void wg_qk_acc(uint32_t (&d)[32], uint32_t a0, uint32_t a1, uint32_t a2, uint32_t a3, uint64_t desc) {
    asm volatile("{\n.reg .pred p;\nsetp.ne.b32 p, 1, 0;\n"
        "wgmma.mma_async.sync.aligned.m64n128k16.f16.f16.f16 "
        "{%0,%1,%2,%3,%4,%5,%6,%7,%8,%9,%10,%11,%12,%13,%14,%15,%16,%17,%18,%19,%20,%21,%22,%23,%24,%25,%26,%27,%28,%29,%30,%31}, "
        "{%32,%33,%34,%35}, %36, p, 1, 1, 0;\n}\n"
        : "+r"(d[0]), "+r"(d[1]), "+r"(d[2]), "+r"(d[3]), "+r"(d[4]), "+r"(d[5]), "+r"(d[6]), "+r"(d[7]), "+r"(d[8]), "+r"(d[9]), "+r"(d[10]), "+r"(d[11]),
          "+r"(d[12]), "+r"(d[13]), "+r"(d[14]), "+r"(d[15]), "+r"(d[16]), "+r"(d[17]), "+r"(d[18]), "+r"(d[19]), "+r"(d[20]), "+r"(d[21]), "+r"(d[22]), "+r"(d[23]),
          "+r"(d[24]), "+r"(d[25]), "+r"(d[26]), "+r"(d[27]), "+r"(d[28]), "+r"(d[29]), "+r"(d[30]), "+r"(d[31])
        : "r"(a0), "r"(a1), "r"(a2), "r"(a3), "l"(desc));
}
__device__ __forceinline__ void wg_pv_init(uint32_t (&d)[10], uint32_t a0, uint32_t a1, uint32_t a2, uint32_t a3, uint64_t desc) {
    asm volatile("{\n.reg .pred p;\nsetp.ne.b32 p, 0, 0;\n"
        "wgmma.mma_async.sync.aligned.m64n40k16.f16.f16.f16 "
        "{%0,%1,%2,%3,%4,%5,%6,%7,%8,%9}, "
        "{%10,%11,%12,%13}, %14, p, 1, 1, 1;\n}\n"
        : "=r"(d[0]), "=r"(d[1]), "=r"(d[2]), "=r"(d[3]), "=r"(d[4]), "=r"(d[5]), "=r"(d[6]), "=r"(d[7]), "=r"(d[8]), "=r"(d[9])
        : "r"(a0), "r"(a1), "r"(a2), "r"(a3), "l"(desc));
}
__device__ __forceinline__ void wg_pv_acc(uint32_t (&d)[10], uint32_t a0, uint32_t a1, uint32_t a2, uint32_t a3, uint64_t desc) {
    asm volatile("{\n.reg .pred p;\nsetp.ne.b32 p, 1, 0;\n"
        "wgmma.mma_async.sync.aligned.m64n40k16.f16.f16.f16 "
        "{%0,%1,%2,%3,%4,%5,%6,%7,%8,%9}, "
        "{%10,%11,%12,%13}, %14, p, 1, 1, 1;\n}\n"
        : "+r"(d[0]), "+r"(d[1]), "+r"(d[2]), "+r"(d[3]), "+r"(d[4]), "+r"(d[5]), "+r"(d[6]), "+r"(d[7]), "+r"(d[8]), "+r"(d[9])
        : "r"(a0), "r"(a1), "r"(a2), "r"(a3), "l"(desc));
}

constexpr uint32_t SB = SMEM_BASE;
constexpr uint32_t R_SLOT = 18432, A_RING = SB, A_KP = SB + 73728, A_QX = SB + 81920, A_STB = SB + 98304;
constexpr uint32_t F_GU0 = SB + 98304, F_GU1 = SB + 163840, F_WD = F_GU0;
__host__ __device__ constexpr uint32_t o_a(uint32_t s) { return s == 0 ? SB : s == 1 ? A_QX : F_GU0 + (s - 2) * 32768; }
__host__ __device__ constexpr uint32_t o_b(uint32_t s) { return s < 2 ? SB + 16384 + s * 16384 : F_GU0 + 16384 + (s - 2) * 32768; }
constexpr uint32_t XT0 = SB + 49152, XT1 = XT0 + 16384, YT0 = o_a(0), YT1 = o_a(1);
constexpr uint32_t Q_ABYTES = 256 * 64 * 2, Q_STB = Q_ABYTES + 192 * 64 * 2;
constexpr uint32_t Q_CS = SB + 3 * Q_STB, Q_RC = Q_CS + 768, Q_FIX = Q_RC + 2048;
constexpr uint32_t SD_VEC = SB + 176128, SD_W = SB + 180224;
static_assert(Q_FIX + 768 <= SD_VEC, "smem");
constexpr uint32_t M_RED = SB + 229376, M_BAR = M_RED + 2048, BAR_SET = 336, M_HS = M_BAR + 2 * BAR_SET, M_SM = M_HS + 128;
constexpr uint32_t M_IV = M_SM;
constexpr uint32_t M_WS = M_SM + 16;
constexpr uint32_t M_CR = M_SM + 20;
constexpr uint32_t M_SS = M_SM + 24;
constexpr uint32_t M_RT = M_SM + 32;
constexpr uint32_t M_SR = M_SM + 96;
constexpr int K_SMEM = M_SR + 128 - SB;
static_assert(K_SMEM == 232448, "smem");
constexpr uint32_t B_QF = 0, B_AF = 24, B_OF = 56, B_RES = 88, B_GU = 96, B_WD = 104, B_RT = 112, B_SW = 120, B_ONE = 128, B_XD = 136, B_QE = 144, B_OE = 168,
                   B_PX = 200, B_AE = 224, B_OD = 256, B_FG = 288, B_FD = 296, B_XS = 304, B_KS = 312, B_K0 = 320, B_END = 328;
constexpr int NB_ML = 1, NB_CONS = 2, NB_SIDE = 3, NB_EPI = 4, NB_WG = 6;

__device__ __forceinline__ int mt_of(int c) { return (c >> 2) & 7; }
__device__ __forceinline__ int nt_of(int c) { return (c >> 5) * 4 + (c & 3); }
__device__ __forceinline__ int blk_of(int c) { return c >> 3; }
__device__ __forceinline__ int cb_of(int c) { return c & 7; }

struct Maps { CUtensorMap x[2], wqkv, o, wo[2], r, g, u, d; };

template <int N>
__device__ __forceinline__ void halve(float (&v)[8], int lane, int bit) {
    const bool up = lane & bit;
    #pragma unroll
    for (int i = 0; i < N; i++) v[i] = (up ? v[N + i] : v[i]) + __shfl_xor_sync(0xffffffffu, up ? v[i] : v[N + i], bit);
}

__device__ __forceinline__ void reset_exchange(int c, int t) {
    #pragma unroll 1
    for (int i = t; i < FILL; i += 96) g_u.fill[c][i] = make_uint4(EMPTY, EMPTY, EMPTY, EMPTY);
}
__device__ __forceinline__ void prep_work(const bf16* __restrict__ x0, const bf16* __restrict__ w_r, uint32_t lb) {
    const int t = tid_now() - 288, c = cta_now(), lane = t & 31, warp = warp_uniform(t >> 5);
    const uint32_t wb = SD_W + warp * 8192;
    mbar_nap(lb + B_SW, 0);
    {
        float cs[8], cq[8];
        #pragma unroll
        for (int i = 0; i < 8; i++) { cs[i] = 0.f; cq[i] = 0.f; }
        #pragma unroll 1
        for (int h = 0; h < 2; h++) {
            #pragma unroll 2
            for (int r = 0; r < 16; r++) {
                const uint4 u = lds128(wb + h * 24576 + (lane >> 3) * 128 + r * 512 + (((lane & 7) ^ ((r * 4 + (lane >> 3)) & 7)) << 4));
                const uint32_t w[4] = {u.x, u.y, u.z, u.w};
                #pragma unroll
                for (int e = 0; e < 4; e++) {
                    const float a = bf_lo(w[e]), b = bf_hi(w[e]);
                    cs[2*e] += a; cs[2*e+1] += b; cq[2*e] = fmaf(a, a, cq[2*e]); cq[2*e+1] = fmaf(b, b, cq[2*e+1]);
                }
            }
            fence_async_smem();
            __syncwarp();
            if (elect_one()) {
                const uint32_t bytes = h == 0 ? 8192 : warp < 2 ? 4096 : 2048;
                mbar_expect_tx(lb + B_PX + warp * 8, bytes);
                bulk_load(wb + h * 24576, h && warp == 2 ? w_r : x0 + (size_t)(c * 16 + (h ? 12 + warp * 2 : warp * 4)) * D_, bytes, lb + B_PX + warp * 8);
            }
            __syncwarp();
        }
        halve<4>(cs, lane, 16); halve<2>(cs, lane, 8);
        halve<4>(cq, lane, 16); halve<2>(cq, lane, 8);
        *reinterpret_cast<float4*>(&g_cs[mt_of(c)][warp * D_ + nt_of(c) * 64 + (lane & 7) * 8 + (lane >> 3) * 2]) = make_float4(cs[0], cq[0], cs[1], cq[1]);
    }
    TL(288, 22);
    reset_exchange(c, t);
    mbar_nap(lb + B_PX + warp * 8, 0);
    #pragma unroll 1
    for (int i = 0; i < (warp < 2 ? 6 : 5); i++) {
        const int r = i < 4 ? warp * 4 + i : 8 + warp * 2 + i;
        float s0 = 0.f, s1 = 0.f, q0 = 0.f, q1 = 0.f;
        #pragma unroll 2
        for (int j = 0; j < 4; j++) {
            const uint4 u = lds128(wb + (i >> 2) * 16384 + i * 2048 + j * 512 + lane * 16);
            const uint32_t w[4] = {u.x, u.y, u.z, u.w};
            #pragma unroll
            for (int e = 0; e < 4; e++) { const float a = bf_lo(w[e]), b = bf_hi(w[e]); s0 += a; s1 += b; q0 = fmaf(a, a, q0); q1 = fmaf(b, b, q1); }
        }
        s0 += s1; q0 += q1;
        float v = (lane & 16 ? q0 : s0) + __shfl_xor_sync(0xffffffffu, lane & 16 ? s0 : q0, 16);
        #pragma unroll
        for (int o = 8; o > 0; o >>= 1) v += __shfl_xor_sync(0xffffffffu, v, o);
        const float mean = v * (1.f / D_), sq = __shfl_xor_sync(0xffffffffu, mean, 16);
        if (lane == 0) {
            if (r < 16) g_rs0[c * 16 + r] = make_float2(fmaxf(sq - mean * mean, 0.f), mean);
            else stsf(M_WS, v);
        }
    }
    named_sync(NB_SIDE, 96);
    if (t == 0) { TL(288, 23); ctr_arrive(&g_pctr); ctr_wait(&g_pctr, 128); TL(288, 24); }
    named_sync(NB_SIDE, 96);
}

constexpr float TCOMP = 1.00245f;
__device__ __forceinline__ int half_exp(uint32_t bits, int off) { return min(max((((int)(bits >> 23) - 125) >> 1) + off, -55), 55); }
__device__ __forceinline__ float pow2(int e) { return __uint_as_float((uint32_t)(127 + e) << 23); }
__device__ __forceinline__ void head_scales(int h) {
    const float fq = ldsf(M_SR + h * 4), fk = ldsf(M_SR + 8 + h * 4);
    const uint32_t vmax = lds32(M_SR + 16 + h * 4), vmin = lds32(M_SR + 24 + h * 4);
    const bool ok = fq <= 1024.f && fk <= 1024.f && fq * fk <= 50000.f && vmax <= vmin + (12u << 23);
    const int a = ok ? 0 : half_exp(__float_as_uint(fq), -8), b = ok ? 0 : half_exp(__float_as_uint(fk), -8), v = half_exp(vmax, ok ? 3 : -10);
    stsf(M_HS + h * 4, TCOMP * QSCALE * pow2(-a)); stsf(M_HS + 8 + h * 4, TCOMP * pow2(-b)); stsf(M_HS + 16 + h * 4, TCOMP * pow2(-v));
    stsf(M_SS + h * 4, ok ? 0.f : pow2(a + b));
    stsf(M_IV + h * 4, pow2(v - 4));
}

__device__ __forceinline__ void epi_inputs(int L, const bf16* __restrict__ w_r) {
    const int t = tid_now() - 288, c = cta_now(), mt = mt_of(c), nt = nt_of(c), lane = t & 31;
    const uint32_t wr = t < 64 ? __ldg(reinterpret_cast<const uint32_t*>(w_r) + cb_of(c) * 64 + t) : 0x3F803F80u;
    #pragma unroll 1
    for (int k = 0; k < 3; k++) {
        const int i = t + 96 * k, col = (i >> 6) * D_ + nt * 64 + (i & 63);
        const float2* rsp = (L ? g_x.rs1 : g_rs0) + mt * 256 + (i & 255);
        uint2 sv = ld_x64(rsp);
        if (k < 2) {
            float2 p[8];
            #pragma unroll
            for (int j = 0; j < 8; j++) p[j] = __ldcg(&g_cs[j][col]);
            stsf(Q_CS + i * 4, ((p[0].x + p[1].x) + (p[2].x + p[3].x)) + ((p[4].x + p[5].x) + (p[6].x + p[7].x)));
            const float zz = ((p[0].y + p[1].y) + (p[2].y + p[3].y)) + ((p[4].y + p[5].y) + (p[6].y + p[7].y));
            const float zs = warp_sum(zz);
            const uint32_t zb = __float_as_uint(zz), zmax = redux_max(zb), zmin = redux_min(zb ? zb : 0x7F800000u);
            if (lane == 0) {
                sts32(M_SR + (i >> 5) * 4, i < 128 ? __float_as_uint(zs) : zmax);
                if (i >= 128) sts32(M_SR + 8 + (i >> 5) * 4, zmin);
            }
        } else {
            named_sync(NB_SIDE, 96);
            if (t < 2) head_scales(t);
            __syncwarp();
        }
        uint32_t n = 0;
        #pragma unroll 1
        while (warp_any(sv.x == EMPTY)) { sv = ld_x64(rsp); poll_tick(n); }
        const float var = __uint_as_float(sv.x), a = L ? 1.f + rsq(var + LN_EPS) : 1.f;
        sts64(Q_RC + (i & 255) * 8, __float_as_uint(a * rsq(a * a * var + LN_EPS)), sv.y ^ 0x80000000u);
    }
    if (t < 68) sts32(M_RED + t * 4, wr);
}

__device__ __forceinline__ void ffn_finish(int L, bf16* __restrict__ out) {
    const int t = tid_now() - 288, c = cta_now(), lane = t & 31, warp = warp_uniform(t >> 5);
    TL(288, L * 32 + 29);
    const uint4 rv = lds128(M_RT + 16 * L);
    const int idx = (int)rv.w;
    const uint32_t* xsrc = &g_x.cand[L][idx >> 7][(c >> 2) * 16 + (t & 3) * 4 + (c & 3)];
    const uint8_t* fsrc = &g_x.x[idx >> 8][((idx >> 7) & 1) * 8 + (c >> 4)];
    uint32_t xw, busy;
    const float sg = sigmoid(bf_round(__uint_as_float(rv.x)));
    uint32_t rsel = pack_bf16(sg, sg);
    Ln2 kx = ln2_coef(__uint_as_float(rv.y), __uint_as_float(rv.z));
    uint32_t* dst = reinterpret_cast<uint32_t*>(L ? out : g_x1) + idx * (D_ / 2) + c * 4 + t;
    asm volatile("" : "+r"(rsel), "+r"(kx.nm), "+r"(kx.rh), "+r"(kx.rl), "+r"(kx.c), "+l"(dst));
    float a[8] = {0.f, 0.f, 0.f, 0.f};
    {
        const float* src = &g_x.ypart[L][c][0][t * 4];
        uint4 v[3];
        uint32_t n = 0;
        #pragma unroll 1
        do {
            v[0] = ld_x128(src); v[1] = ld_x128(src + 384);
            v[2] = make_uint4(0u, 0u, 0u, 0u);
            xw = 0u; busy = 0u;
            if (warp == 0) {
                v[2] = ld_x128(src + 768); xw = ld_x32(xsrc);
                asm volatile("ld.relaxed.gpu.global.u8 %0, [%1];" : "=r"(busy) : "l"(fsrc) : "memory");
            }
            poll_tick(n);
        } while (warp_any(any_empty(v[0]) || any_empty(v[1]) || any_empty(v[2]) || xw == EMPTY || busy != 0));
        TL(288, L * 32 + 30); TL(352, L * 32 + 31);
        #pragma unroll
        for (int i = 0; i < 3; i++) { a[0] += __uint_as_float(v[i].x); a[1] += __uint_as_float(v[i].y); a[2] += __uint_as_float(v[i].z); a[3] += __uint_as_float(v[i].w); }
    }
    halve<2>(a, lane, 2); halve<1>(a, lane, 4);
    a[0] += __shfl_xor_sync(0xffffffffu, a[0], 8); a[0] += __shfl_xor_sync(0xffffffffu, a[0], 16);
    if (lane < 8) stsf(M_SR + warp * 32 + ((lane & 1) * 4 + (lane & 2) + (lane >> 2)) * 4, a[0]);
    const uint32_t xn = ln2(xw, kx);
    named_sync(NB_SIDE, 96);
    if (t < 4) {
        const float2 y0 = lds64f(M_SR + t * 8), y1 = lds64f(M_SR + 32 + t * 8), y2 = lds64f(M_SR + 64 + t * 8);
        const uint32_t y = pack_bf16(y0.x + y1.x + y2.x, y0.y + y1.y + y2.y);
        const uint32_t res = badd2(xw, badd2(xn, bmul2(y, rsel)));
        *dst = res;
        if (L == 0) st_x32(&g_x.x2row[c * 4 + t], res);
    }
}

__device__ __forceinline__ void fix_row(uint32_t lb) {
    const int t = tid_now() - 288, c = cta_now(), lane = t & 31, warp = warp_uniform(t >> 5);
    uint4 v[2];
    {
        uint32_t n = 0;
        #pragma unroll 1
        do {
            v[0] = ld_x128(g_x.x2row + t * 4);
            v[1] = make_uint4(0u, 0u, 0u, 0u);
            if (warp == 0) v[1] = ld_x128(g_x.x2row + (96 + t) * 4);
            poll_tick(n);
        } while (warp_any(any_empty(v[0]) || any_empty(v[1])));
    }
    const uint32_t w[8] = {v[0].x, v[0].y, v[0].z, v[0].w, v[1].x, v[1].y, v[1].z, v[1].w};
    float su = 0.f, sq = 0.f;
    #pragma unroll
    for (int i = 0; i < 8; i++) { const float a = bf_lo(w[i]), b = bf_hi(w[i]); su += a + b; sq = fmaf(a, a, fmaf(b, b, sq)); }
    su = warp_sum(su); sq = warp_sum(sq);
    if (lane == 0) sts64(M_SR + 96 + warp * 8, __float_as_uint(su), __float_as_uint(sq));
    named_sync(NB_SIDE, 96);
    const float2 s0 = lds64f(M_SR + 96), s1 = lds64f(M_SR + 104), s2 = lds64f(M_SR + 112);
    const float mean = (s0.x + s1.x + s2.x) * (1.f / D_);
    const float rstd = rsq(fmaxf((s0.y + s1.y + s2.y) * (1.f / D_) - mean * mean, 0.f) + LN_EPS);
    const Ln2 k = ln2_coef(mean, rstd);
    #pragma unroll
    for (int i = 0; i < 2; i++)
        if (i == 0 || warp == 0) sts128(SD_VEC + (t + 96 * i) * 16, ln2(w[4*i], k), ln2(w[4*i+1], k), ln2(w[4*i+2], k), ln2(w[4*i+3], k));
    named_sync(NB_SIDE, 96);
    TL(288, 32 + 22);
    mbar_nap(lb + B_SW, 0);
    float a[8];
    #pragma unroll
    for (int i = 0; i < 8; i++) a[i] = 0.f;
    const uint32_t xa = base32(SD_VEC + lane * 2), wa = base32(SD_W + lane * 48 + warp * 16);
    #pragma unroll 2
    for (int b = 0; b < 32; b++) {
        const float x = bf_lo(lds16(xa + b * 64));
        const uint4 u = lds128(wa + b * 1536);
        a[0] = fmaf(x, bf_lo(u.x), a[0]); a[1] = fmaf(x, bf_hi(u.x), a[1]); a[2] = fmaf(x, bf_lo(u.y), a[2]); a[3] = fmaf(x, bf_hi(u.y), a[3]);
        a[4] = fmaf(x, bf_lo(u.z), a[4]); a[5] = fmaf(x, bf_hi(u.z), a[5]); a[6] = fmaf(x, bf_lo(u.w), a[6]); a[7] = fmaf(x, bf_hi(u.w), a[7]);
    }
    halve<4>(a, lane, 16); halve<2>(a, lane, 8); halve<1>(a, lane, 4);
    a[0] = quad_sum(a[0]);
    if ((lane & 3) == 0) st_x32(&g_x.fix[c * 24 + warp * 8 + (lane >> 2)], __float_as_uint(a[0]));
    TL(288, 32 + 23);
    if (((int)lds32(M_RT + 12) >> 8) == mt_of(c)) {
        const float* src = &g_x.fix[(t >> 5) * D_ + nt_of(c) * 64 + (t & 31) * 2];
        uint2 f;
        uint32_t n = 0;
        #pragma unroll 1
        do { f = ld_x64(src); poll_tick(n); } while (warp_any(f.x == EMPTY || f.y == EMPTY));
        sts64(Q_FIX + t * 8, f.x, f.y);
    }
}

__device__ __forceinline__ void out_piece(bf16* __restrict__ out, int r, int ch, bool on) {
    const uint4 v = lds128(((ch & 8) ? YT1 : YT0) + r * 128 + (((ch ^ r) & 7) << 4)), kk = lds128(XT0 + r * 16);
    const Ln2 k = {kk.x, kk.y, kk.z, kk.w};
    const int c = blockIdx.x;
    stg128_pred(out + (blk_of(c) * 128 + r) * D_ + cb_of(c) * 128 + ch * 8, make_uint4(add_ln2(v.x, k), add_ln2(v.y, k), add_ln2(v.z, k), add_ln2(v.w, k)), on);
}
__device__ __forceinline__ void publish(uint8_t* f) {
    bulk_commit();
    bulk_wait();
    fence_async_global();
    asm volatile("st.release.gpu.global.u8 [%0], 0;" :: "l"(f) : "memory");
}
__device__ __forceinline__ void side_role(const Maps& mp, const bf16* __restrict__ x0, const bf16* __restrict__ wo, const bf16* __restrict__ w_down, const bf16* __restrict__ w_r, bf16* __restrict__ out) {
    #pragma unroll 1
    for (int L = 0; L < 2; L++) {
        const uint32_t lb = M_BAR + L * BAR_SET;
        if (L == 0) prep_work(x0, w_r, lb);
        else fix_row(lb);
        epi_inputs(L, w_r);
        const int t = tid_now() - 288, c = cta_now(), mt = mt_of(c), nt = nt_of(c), warp = warp_uniform(t >> 5);
        TL(288, L * 32 + 4);
        named_arrive(NB_EPI, 224);
        named_arrive(NB_EPI + 1, 224);
        if (warp == 0) {
            named_sync(NB_ML, 288);
            #pragma unroll
            for (int i = 0; i < 16; i++) sts128(base32(A_RING + 16384 + t * 16) + (i >> 2) * R_SLOT + (i & 3) * 512, 0x2C002C00u, 0x2C002C00u, 0x2C002C00u, 0x2C002C00u);
            fence_async_smem();
            __syncwarp();
            mbar_arrive_elect(lb + B_ONE);
        }
        if (elect_one()) {
            #pragma unroll 1
            for (int n = warp - 1; n >= 0 && n < 3 * warp - 2; n++) {
                char* dst = g_kv + (size_t)(nt * 2 + (n >> 1)) * 16 * KV_TILE;
                if (n < 3) mbar_nap(lb + (n == 0 ? B_K0 : n == 1 ? B_KS : B_AE + 16), 0);
                bulk_store(dst + ((2 * mt - 1 + (n & 1)) & 15) * KV_TILE, n == 0 ? A_KP : n == 1 ? A_RING : A_STB + (n - 2) * 8192, 8192 << (n & 1));
                if (n & 1) bulk_store(dst + 2 * mt * KV_TILE + 24576, n == 1 ? A_RING + R_SLOT + 8192 : A_STB + 24576, 8192);
                publish(&g_x.kv[L][nt * 2 + (n >> 1)][2 * mt + (n & 1)]);
                if (n == 1) TL(352, L * 32 + 6);
                if (n == 0) TL(320, L * 32 + 27);
            }
            if (warp == 2) {
                const bool ffn = c < NFC;
                const uint64_t pol = policy_evict_first();
                mbar_expect_tx(lb + B_GU, ffn ? 131072 : 0);
                mbar_expect_tx(lb + B_WD, ffn ? 65536 : 0);
                l2_prefetch(reinterpret_cast<const char*>(wo) + (size_t)c * 16384, 16384);
                if (ffn) {
                    #pragma unroll 1
                    for (int i = 0; i < 12; i++) {
                        if (i < 8) tma_load_s(F_GU0 + i * 16384, (i & 1) ? &mp.u : &mp.g, c * 32, (i >> 1) * 256, lb + B_GU, pol);
                        else l2_prefetch(reinterpret_cast<const char*>(w_down) + (size_t)c * 65536 + (i - 8) * 16384, 16384);
                        __nanosleep(900);
                    }
                }
                mbar_nap(lb + B_OD, 0);
                __nanosleep(1000);
                l2_prefetch(g_u.fill[c], sizeof(g_u.fill[0]));
                if (L == 0) {
                    mbar_nap(lb + B_XS, 0);
                    tma_store(&mp.x[1], YT0, cb_of(c) * 128, blk_of(c) * 128);
                    tma_store(&mp.x[1], YT1, cb_of(c) * 128 + 64, blk_of(c) * 128);
                    publish(&g_x.x[blk_of(c) >> 1][(blk_of(c) & 1) * 8 + cb_of(c)]);
                    mbar_arrive(lb + B_XD);
                    TL(352, 18);
                }
            } else {
                #pragma unroll 1
                for (int p = 0; p < 2; p++) { mbar_sleep(lb + B_OD + (p * 2 + warp) * 8, 0); ctr_arrive(g_x.o[L][mt * 2 + warp][p]); TL(288, L * 32 + 19); }
            }
        }
        __syncwarp();
        if (L) {
            mbar_sleep(lb + B_XS, 0);
            const int cand = (int)lds32(M_CR) & 127;
            #pragma unroll 2
            for (int r = t >> 4; r < 132; r += 6) out_piece(out, r & 127, t & 15, r < 128 && r != cand);
            TL(288, 32 + 18);
            mbar_sleep(lb + B_RT, 0);
            out_piece(out, cand, t & 15, t < 16 && lds32(M_CR) != lds32(M_RT + 28));
        }
        const uint32_t late = mbar_test(lb + B_FD, 0);
        mbar_sleep(lb + B_FD, 0);
        __nanosleep(late ? 50 : 400);
        if (c == 0 && t == 0 && L == 0) g_pctr = 0;
        ffn_finish(L, out);
        TL(288, L * 32 + 20);
    }
}

struct Cols { float2 c[4]; float hs; };
template <int HH>
__device__ __forceinline__ void load_cols(Cols& k, uint32_t cs) {
    #pragma unroll
    for (int jj = 0; jj < 4; jj++) k.c[jj] = lds64f(cs + (HH * 32 + jj * 8) * 4);
    k.hs = ldsf(M_HS + HH * 4);
}
template <int HH>
__device__ __forceinline__ void qkv_epi_head(const float (&acc0)[96], const float (&acc1)[96], const float (&cf)[4], const float (&nm)[4], const Cols& k, uint32_t (&pk)[4][4]) {
    #pragma unroll
    for (int jj = 0; jj < 4; jj++) {
        #pragma unroll
        for (int i = 0; i < 4; i++) {
            const float* a = (i >> 1) ? acc1 : acc0;
            const float sc = cf[i] * k.hs;
            const float x = fmaf(nm[i], k.c[jj].x, a[4 * (4 * HH + jj) + 2 * (i & 1)]) * sc;
            const float y = fmaf(nm[i], k.c[jj].y, a[4 * (4 * HH + jj) + 2 * (i & 1) + 1]) * sc;
            pk[i][jj] = pack_f16(x, y) & 0xFFF8FFF8u;
        }
    }
}
__device__ __forceinline__ void stage_kv(uint32_t dst, const uint32_t (&pk)[4][4]) {
    #pragma unroll
    for (int i = 0; i < 4; i++) stsm4(dst + (i >> 1) * 1024 + (i & 1) * 128, pk[i][0], pk[i][1], pk[i][2], pk[i][3]);
}
template <int OFF>
__device__ __forceinline__ void patch_row(float (&acc)[96], uint32_t fx) {
    #pragma unroll
    for (int j = 0; j < 24; j++) { const float2 f = lds64f(fx + j * 32); acc[4 * j + OFF] = f.x; acc[4 * j + OFF + 1] = f.y; }
}
template <bool INIT>
__device__ __forceinline__ void qkv_step(float (&acc0)[96], float (&acc1)[96], uint64_t da, uint64_t db) {
    wg_fence();
    #pragma unroll
    for (int kk = 0; kk < 4; kk++) {
        if (INIT && kk == 0) { wg_gemm_n192_init(acc0, da, db); wg_gemm_n192_init(acc1, da + (8192 >> 4), db); }
        else { wg_gemm_n192(acc0, da + kk * 2, db + kk * 128); wg_gemm_n192(acc1, da + (8192 >> 4) + kk * 2, db + kk * 128); }
    }
    wg_commit();
}
__device__ __forceinline__ void qkv_phase(int L, uint32_t lb, int wg, uint32_t (&qa)[8], uint32_t (&qb)[8], uint32_t (&SA)[32], uint32_t (&SB_)[32]) {
    float acc0[96], acc1[96];
    {
        const bool leader = (tid_now() & 127) == 0;
        const uint64_t da0 = opaque(desc_sw128(SB + wg * 16384, 16, 1024)), db0 = opaque(desc_sw128(SB + Q_ABYTES, 8192, 1024));
        mbar_spin(lb + B_QF, 0);
        TL(0, L * 32 + 1); CK(0, L * 32 + 10);
        qkv_step<true>(acc0, acc1, da0, db0);
        uint32_t st = 1, ph = 0;
        #pragma unroll 1
        for (int k = 1; k < 16; k++) {
            mbar_spin(lb + B_QF + 8 * st, ph);
            if (k == 14 && wg) named_sync(NB_CONS, 256);
            qkv_step<false>(acc0, acc1, da0 + st * (Q_STB >> 4), db0 + st * (Q_STB >> 4));
            if (k == 15 && !wg) named_arrive(NB_CONS, 256);
            wg_wait<1>();
            if (leader) mbar_arrive(lb + B_QE + 8 * (st == 0 ? 2 : st - 1));
            if (++st == 3) { st = 0; ph ^= 1; }
        }
    }
    named_sync(NB_EPI + wg, 224);
    const int tid = tid_now(), lane = tid & 31, w = (tid >> 5) & 3, g = lane >> 2, t = lane & 3;
    const int lr0 = wg * 128 + w * 16 + g;
    float cf[4], nm[4];
    #pragma unroll
    for (int i = 0; i < 4; i++) { const float2 r = lds64f(base32(Q_RC + lr0 * 8) + ((i >> 1) * 64 + (i & 1) * 8) * 8); cf[i] = r.x; nm[i] = r.y; }
    const uint32_t cs = base32(Q_CS + t * 8);
    const int d = L ? (int)lds32(M_RT + 12) - (mt_of(cta_now()) * 256 + lr0) : -1;
    const uint32_t ko = base32((lane >> 3) * 2048 + (w * 16 + (lane & 7)) * 16);
    Cols k0, k1;
    load_cols<2>(k0, cs);
    wg_wait<0>();
    pin(acc0); pin(acc1);
    TL(128, L * 32 + 2); CK(128, L * 32 + 11);
    named_arrive(NB_ML, 288);
    if ((tid & 127) == 0) mbar_arrive(lb + B_QE);
    if (__builtin_expect((d & ~72) == 0, 0)) {
        if (d == 0) { patch_row<0>(acc0, cs + (Q_FIX - Q_CS)); cf[0] = 1.f; nm[0] = 0.f; }
        else if (d == 8) { patch_row<2>(acc0, cs + (Q_FIX - Q_CS)); cf[1] = 1.f; nm[1] = 0.f; }
        else if (d == 64) { patch_row<0>(acc1, cs + (Q_FIX - Q_CS)); cf[2] = 1.f; nm[2] = 0.f; }
        else { patch_row<2>(acc1, cs + (Q_FIX - Q_CS)); cf[3] = 1.f; nm[3] = 0.f; }
    }
    __syncwarp();
    uint32_t pk[4][4];
    qkv_epi_head<2>(acc0, acc1, cf, nm, k0, pk);
    load_cols<4>(k1, cs);
    mbar_spin(lb + B_QE + 8 - 8 * wg, wg);
    stage_kv((wg ? A_RING : A_KP) + ko, pk);
    if (!wg) {
        fence_async_smem();
        __syncwarp();
        mbar_arrive_elect(lb + B_K0);
    }
    qkv_epi_head<4>(acc0, acc1, cf, nm, k1, pk);
    load_cols<3>(k0, cs);
    stage_kv(A_RING + wg * R_SLOT + 8192 + ko, pk);
    fence_async_smem();
    __syncwarp();
    mbar_arrive_elect(lb + B_KS);
    qkv_epi_head<3>(acc0, acc1, cf, nm, k0, pk);
    load_cols<0>(k1, cs);
    load_cols<5>(k0, cs);
    stage_kv(A_STB + wg * 8192 + ko, pk);
    qkv_epi_head<0>(acc0, acc1, cf, nm, k1, pk);
    #pragma unroll
    for (int s = 0; s < 2; s++) {
        qa[4*s] = pk[0][2*s]; qa[4*s+1] = pk[1][2*s]; qa[4*s+2] = pk[0][2*s+1]; qa[4*s+3] = pk[1][2*s+1];
        qb[4*s] = pk[2][2*s]; qb[4*s+1] = pk[3][2*s]; qb[4*s+2] = pk[2][2*s+1]; qb[4*s+3] = pk[3][2*s+1];
    }
    mbar_spin(lb + B_K0, 0);
    {
        constexpr uint64_t dk = desc_plain(A_KP, 2048, 128);
        wg_fence();
        wg_qk_init(SA, qa[0], qa[1], qa[2], qa[3], dk);
        wg_qk_acc(SA, qa[4], qa[5], qa[6], qa[7], dk + 256);
        wg_qk_init(SB_, qb[0], qb[1], qb[2], qb[3], dk);
        wg_qk_acc(SB_, qb[4], qb[5], qb[6], qb[7], dk + 256);
        wg_commit();
    }
    qkv_epi_head<5>(acc0, acc1, cf, nm, k0, pk);
    load_cols<1>(k1, cs);
    stage_kv(A_STB + 16384 + wg * 8192 + ko, pk);
    qkv_epi_head<1>(acc0, acc1, cf, nm, k1, pk);
    #pragma unroll
    for (int u = 0; u < 2; u++)
        #pragma unroll
        for (int s = 0; s < 2; s++) sts128(A_QX + (u * 2 + s) * 4096 + tid * 16, pk[2*u][2*s], pk[2*u+1][2*s], pk[2*u][2*s+1], pk[2*u+1][2*s+1]);
    fence_async_smem();
    wg_wait<0>();
    pin(SA); pin(SB_);
    TL(128, L * 32 + 5); CK(128, L * 32 + 12);
}

#define PMASK 0x00005555u
#define IMASK 0x20202020u
__host__ __device__ constexpr bool is_poly(int j) { return !((PMASK >> j) & 1); }
#define TBIAS 0x5DEB5DEBu
struct Shift { uint32_t f0, f1, n0, n1, bad; };

__device__ __forceinline__ uint32_t exp2_mufu(uint32_t s, uint32_t nm) {
    uint32_t r;
    asm("ex2.approx.f16x2 %0, %1;" : "=r"(r) : "r"(hadd2(s, nm)));
    return r;
}
__device__ __forceinline__ uint32_t exp2_fix(uint32_t s, uint32_t fm, uint32_t ca, uint32_t& U, bool mul, uint32_t sixteen) {
    uint32_t G, D;
    asm("fma.rn.relu.f16x2 %0, %1, %2, %3;" : "=r"(U) : "r"(s), "r"(0x00400040u), "r"(fm));
    asm("fma.rn.f16x2 %0, %1, %2, %3;" : "=r"(G) : "r"(U & 0x003F003Fu), "r"(ca), "r"(0x98B898B8u));
    asm("{.reg .b32 n; neg.f16x2 n, %1; fma.rn.relu.f16x2 %0, %1, n, %2;}" : "=r"(D) : "r"(G), "r"(0x00570057u));
    if (mul) return U * sixteen - D;
    return (U << 4) - D;
}
__device__ __forceinline__ uint32_t or3(uint32_t a, uint32_t b, uint32_t c) { uint32_t r; asm("lop3.b32 %0, %1, %2, %3, 0xFE;" : "=r"(r) : "r"(a), "r"(b), "r"(c)); return r; }
__device__ __forceinline__ void exp_tile(const uint32_t (&S)[32], uint32_t (&P)[32], Shift& h, uint32_t ca, uint32_t sixteen) {
    uint32_t U[33];
    int n = 0;
    #pragma unroll
    for (int i = 0; i < 32; i++) {
        if (is_poly(i)) P[i] = exp2_fix(S[i], (i & 1) ? h.f1 : h.f0, ca, U[n++], (IMASK >> i) & 1, sixteen);
        else P[i] = exp2_mufu(S[i], (i & 1) ? h.n1 : h.n0);
    }
    U[n] = 0u;
    #pragma unroll
    for (int i = 0; i < 32; i += 6) {
        if (i + 5 <= n) h.bad = or3(h.bad, or3(U[i], U[i + 1], U[i + 2]), or3(U[i + 3], U[i + 4], U[i + 5]));
        else {
            #pragma unroll
            for (int j = i; j < i + 6; j += 2) if (j < n) h.bad = or3(h.bad, U[j], U[j + 1]);
        }
    }
    pin(P);
}
__device__ __forceinline__ uint32_t hfma2(uint32_t a, uint32_t b, uint32_t c) { uint32_t r; asm("fma.rn.f16x2 %0, %1, %2, %3;" : "=r"(r) : "r"(a), "r"(b), "r"(c)); return r; }
__device__ __forceinline__ void unit_start(const uint32_t (&S)[32], Shift& h, uint32_t (&o2)[10]) {
    uint32_t m[4] = {S[0], S[1], S[2], S[3]};
    #pragma unroll
    for (int i = 1; i < 8; i++)
        #pragma unroll
        for (int e = 0; e < 4; e++) m[e] = hmax2(m[e], S[4 * i + e]);
    const uint32_t a = hadd2(m[0], m[2]), c = hadd2(m[1], m[3]);
    uint32_t x = hadd2(__byte_perm(a, c, 0x5410), __byte_perm(a, c, 0x7632));
    x = hadd2(x, __shfl_xor_sync(0xffffffffu, x, 1));
    x = hadd2(x, __shfl_xor_sync(0xffffffffu, x, 2));
    const uint32_t T = hfma2(x, 0xAC00AC00u, TBIAS);
    const uint32_t n = hadd2(T, 0xDE00DE00u), f = hfma2(n, 0x00400040u, 0x03C003C0u);
    h.n0 = __byte_perm(n, 0, 0x1010); h.n1 = __byte_perm(n, 0, 0x3232);
    h.f0 = __byte_perm(f, 0, 0x1010); h.f1 = __byte_perm(f, 0, 0x3232);
    h.bad = T ^ 0x58005800u;
    #pragma unroll
    for (int i = 0; i < 10; i++) o2[i] = 0u;
}
__device__ __forceinline__ uint32_t o_offset() {
    const int c = cta_now(), tid = tid_now();
    return (mt_of(c) * 256 + (tid & 128) + ((tid >> 1) & 48) + ((tid >> 2) & 7)) * (D_ * 2) + nt_of(c) * 64 + (tid & 3) * 16;
}
template <int PASS, int UNIT>
__device__ __forceinline__ void unit_end(const uint32_t (&o)[10], uint32_t bad, uint32_t lb, uint32_t oo, uint32_t& fail, float iv) {
    float v[20];
    #pragma unroll
    for (int i = 0; i < 10; i++) h2_unpack(o[i], v[2 * i], v[2 * i + 1]);
    const float i0 = rcp(v[16]) * iv, i1 = rcp(v[18]) * iv;
    uint32_t r[8], z = 0;
    #pragma unroll
    for (int j = 0; j < 4; j++) {
        r[j] = pack_bf16(v[4*j] * i0, v[4*j+1] * i0); r[4 + j] = pack_bf16(v[4*j+2] * i1, v[4*j+3] * i1);
        z = bfma2(r[j], r[4 + j], z);
    }
    const bool good = o[8] - 0x34003400u < 0x48000000u && o[9] - 0x34003400u < 0x48000000u &&
                      ((bad & 0xF800F800u) | (bmul2(z, 0u) & 0x7FFF7FFFu) | (fail & (1u << (2 * PASS + UNIT)))) == 0;
    const bool all = __all_sync(0xffffffffu, good);
    char* dst = reinterpret_cast<char*>(g_o) + oo + (UNIT * 64 * D_ + PASS * 512) * 2;
    stg128_pred(dst, make_uint4(r[0], r[1], r[2], r[3]), all);
    stg128_pred(dst + 16 * D_, make_uint4(r[4], r[5], r[6], r[7]), all);
    if (__builtin_expect(!all, 0)) {
        fail |= 1u << (2 * PASS + UNIT);
        if (PASS == 0) {
            #pragma unroll
            for (int s = 0; s < 2; s++) g_qsave[cta_now()][UNIT * 2 + s][tid_now()] = lds128(A_KP + (UNIT * 2 + s) * 4096 + tid_now() * 16);
        }
    }
    __syncwarp();
    mbar_arrive_elect_p(lb + PASS * 16, all);
}
__device__ __forceinline__ void swap_q(uint32_t (&q)[8], uint32_t a) {
    asm volatile("{\n.reg .pred p;\nsetp.ne.u32 p, %8, 0;\n"
                 "@p st.shared.v4.b32 [%8 + -8192], {%0, %1, %2, %3};\n@p st.shared.v4.b32 [%8 + -4096], {%4, %5, %6, %7};\n"
                 "@p ld.shared.v4.b32 {%0, %1, %2, %3}, [%8];\n@p ld.shared.v4.b32 {%4, %5, %6, %7}, [%8 + 4096];\n}"
                 : "+r"(q[0]), "+r"(q[1]), "+r"(q[2]), "+r"(q[3]), "+r"(q[4]), "+r"(q[5]), "+r"(q[6]), "+r"(q[7]) : "r"(a) : "memory");
}
static_assert(A_QX == A_KP + 8192, "parking places");
template <bool INIT>
__device__ __forceinline__ void issue_pv(uint32_t (&o)[10], const uint32_t (&P)[32], uint64_t dv) {
    if (INIT) wg_pv_init(o, P[0], P[1], P[2], P[3], dv); else wg_pv_acc(o, P[0], P[1], P[2], P[3], dv);
    #pragma unroll
    for (int k = 1; k < 8; k++) wg_pv_acc(o, P[4*k], P[4*k+1], P[4*k+2], P[4*k+3], dv + k * 16);
}

__device__ __forceinline__ uint4 quad_transpose(uint32_t x0, uint32_t x1, uint32_t x2, uint32_t x3, int t) {
    const bool b0 = t & 1, b1 = t & 2;
    uint32_t s0 = b0 ? x0 : x1, s1 = b0 ? x2 : x3;
    s0 = __shfl_xor_sync(0xffffffffu, s0, 1); s1 = __shfl_xor_sync(0xffffffffu, s1, 1);
    const uint32_t y0 = b0 ? s0 : x0, y1 = b0 ? x1 : s0, y2 = b0 ? s1 : x2, y3 = b0 ? x3 : s1;
    uint32_t u0 = b1 ? y0 : y2, u1 = b1 ? y1 : y3;
    u0 = __shfl_xor_sync(0xffffffffu, u0, 2); u1 = __shfl_xor_sync(0xffffffffu, u1, 2);
    return b1 ? make_uint4(u0, u1, y2, y3) : make_uint4(y0, y1, u0, u1);
}
__device__ __forceinline__ uint32_t movm(uint32_t v) { uint32_t r; asm volatile("movmatrix.sync.aligned.m8n8.trans.b16 %0, %1;" : "=r"(r) : "r"(v)); return r; }
__device__ __forceinline__ void attn_repair(uint32_t lb, int wg, int ow, int pass, int unit) {
    const int tid = tid_now(), w = (tid >> 5) & 3, g = (tid & 31) >> 2, t = tid & 3;
    uint4* const sc = &g_qsave[cta_now()][0][tid & ~96];
    const uint4 qx = __ldcg(sc + (pass * 2 + unit) * 512 + ow * 32), qy = __ldcg(sc + (pass * 2 + unit) * 512 + 256 + ow * 32);
    float ss = ldsf(M_SS + pass * 4);
    if (ss == 0.f) ss = 1.f;
    const uint4 q0 = quad_transpose(qx.x, qx.z, qy.x, qy.z, t), q1 = quad_transpose(qx.y, qx.w, qy.y, qy.w, t);
    const char* kv = g_kv + (size_t)(nt_of(cta_now()) * 2 + pass) * 16 * KV_TILE + t * 2048 + g * 16;
    float o[4][4], m0 = -INFINITY, m1 = -INFINITY, l0 = 0.f, l1 = 0.f;
    #pragma unroll
    for (int j = 0; j < 4; j++) { o[j][0] = 0.f; o[j][1] = 0.f; o[j][2] = 0.f; o[j][3] = 0.f; }
    uint4 kf[8];
    #pragma unroll
    for (int i = 0; i < 8; i++) kf[i] = __ldcg(reinterpret_cast<const uint4*>(kv + ((4 * w - 1) & 15) * KV_TILE + i * 128));
    #pragma unroll 1
    for (int b = 8 * w; b < 8 * w + 8; b++) {
        uint4 vf[8];
        #pragma unroll
        for (int i = 0; i < 8; i++) vf[i] = __ldcg(reinterpret_cast<const uint4*>(kv + (b >> 1) * KV_TILE + (b & 1) * 1024 + 8192 + i * 128));
        float s[8][4];
        #pragma unroll
        for (int i = 0; i < 8; i++) {
            s[i][0] = 0.f; s[i][1] = 0.f; s[i][2] = 0.f; s[i][3] = 0.f;
            mma_f16(s[i], q0.x, q1.x, q0.y, q1.y, kf[i].x, kf[i].y); mma_f16(s[i], q0.z, q1.z, q0.w, q1.w, kf[i].z, kf[i].w);
        }
        #pragma unroll
        for (int i = 0; i < 8; i++) kf[i] = __ldcg(reinterpret_cast<const uint4*>(kv + (((b - 1) >> 1) & 15) * KV_TILE + (~b & 1) * 1024 + i * 128));
        float t0 = m0, t1 = m1;
        #pragma unroll
        for (int i = 0; i < 8; i++) { t0 = fmaxf(t0, fmaxf(s[i][0], s[i][1])); t1 = fmaxf(t1, fmaxf(s[i][2], s[i][3])); }
        t0 = quad_max(t0); t1 = quad_max(t1);
        const float a0 = ex2((m0 - t0) * ss), a1 = ex2((m1 - t1) * ss);
        m0 = t0; m1 = t1;
        l0 *= a0; l1 *= a1;
        #pragma unroll
        for (int j = 0; j < 4; j++) { o[j][0] *= a0; o[j][1] *= a0; o[j][2] *= a1; o[j][3] *= a1; }
        #pragma unroll
        for (int k = 0; k < 4; k++) {
            uint32_t pf[4];
            #pragma unroll
            for (int e = 0; e < 2; e++) {
                const float p0 = ex2((s[2*k+e][0] - m0) * ss), p1 = ex2((s[2*k+e][1] - m0) * ss), p2 = ex2((s[2*k+e][2] - m1) * ss), p3 = ex2((s[2*k+e][3] - m1) * ss);
                l0 += p0 + p1; l1 += p2 + p3;
                pf[2*e] = pack_f16(p0, p1); pf[2*e+1] = pack_f16(p2, p3);
            }
            mma_f16(o[0], pf[0], pf[1], pf[2], pf[3], movm(vf[2*k].x), movm(vf[2*k+1].x));
            mma_f16(o[1], pf[0], pf[1], pf[2], pf[3], movm(vf[2*k].y), movm(vf[2*k+1].y));
            mma_f16(o[2], pf[0], pf[1], pf[2], pf[3], movm(vf[2*k].z), movm(vf[2*k+1].z));
            mma_f16(o[3], pf[0], pf[1], pf[2], pf[3], movm(vf[2*k].w), movm(vf[2*k+1].w));
        }
    }
    sc[24 * 256 + w * 32] = make_uint4(__float_as_uint(m0), __float_as_uint(m1), __float_as_uint(quad_sum(l0)), __float_as_uint(quad_sum(l1)));
    #pragma unroll
    for (int j = 0; j < 4; j++) sc[(25 + j) * 256 + w * 32] = make_uint4(__float_as_uint(o[j][0]), __float_as_uint(o[j][1]), __float_as_uint(o[j][2]), __float_as_uint(o[j][3]));
    named_sync(NB_WG + wg, 128);
    uint4 h[4];
    #pragma unroll
    for (int i = 0; i < 4; i++) { h[i] = __ldcg(sc + 24 * 256 + i * 32); m0 = fmaxf(m0, __uint_as_float(h[i].x)); m1 = fmaxf(m1, __uint_as_float(h[i].y)); }
    float r[4] = {0.f, 0.f, 0.f, 0.f};
    l0 = 0.f; l1 = 0.f;
    #pragma unroll
    for (int i = 0; i < 4; i++) {
        const uint4 v = __ldcg(sc + (25 + w) * 256 + i * 32);
        const float a0 = ex2((__uint_as_float(h[i].x) - m0) * ss), a1 = ex2((__uint_as_float(h[i].y) - m1) * ss);
        l0 = fmaf(a0, __uint_as_float(h[i].z), l0); l1 = fmaf(a1, __uint_as_float(h[i].w), l1);
        r[0] = fmaf(a0, __uint_as_float(v.x), r[0]); r[1] = fmaf(a0, __uint_as_float(v.y), r[1]);
        r[2] = fmaf(a1, __uint_as_float(v.z), r[2]); r[3] = fmaf(a1, __uint_as_float(v.w), r[3]);
    }
    const float iv = 16.f * ldsf(M_IV + pass * 4), i0 = iv * rcp(l0), i1 = iv * rcp(l1);
    uint32_t* dst = reinterpret_cast<uint32_t*>(reinterpret_cast<char*>(g_o) + (o_offset() & ~48u) + ((unit * 64 + (ow - w) * 16) * D_ + pass * 512) * 2) + w * 4 + t;
    dst[0] = pack_bf16(r[0] * i0, r[1] * i0);
    dst[4 * D_] = pack_bf16(r[2] * i1, r[3] * i1);
    named_sync(NB_WG + wg, 128);
    if ((tid & 127) == 0) mbar_arrive(lb + B_OD + (pass * 2 + wg) * 8);
    __syncwarp();
}
__device__ __forceinline__ bool wg_any(bool p, int id) {
    uint32_t r;
    asm volatile("{\n.reg .pred a, b;\nsetp.ne.u32 a, %1, 0;\nbarrier.cta.red.or.aligned.pred b, %2, 128, a;\nselp.u32 %0, 1, 0, b;\n}" : "=r"(r) : "r"((uint32_t)p), "r"(id) : "memory");
    return r != 0;
}

__device__ __forceinline__ void load_gu(uint32_t (&f)[64], uint32_t src, int warp, int lane) {
    const uint32_t row = (warp & 3) * 64 + (lane >> 4) * 8 + (lane & 7), ch = (lane >> 3) & 1, sw = (lane >> 1) & 3;
    const uint32_t a0 = base32(src + (warp >> 2) * 32768 + row * 64 + ((ch ^ sw) << 4)), a1 = base32(a0 ^ 32);
    #pragma unroll
    for (int i = 0; i < 16; i++) ldsm4t(f[4*i], f[4*i+1], f[4*i+2], f[4*i+3], ((i & 1) ? a1 : a0) + ((i >> 1) & 1) * 16384 + (i >> 2) * 1024);
}

__device__ __forceinline__ void arrive_loaded(uint32_t bar, const uint32_t (&f)[64], uint32_t zero) {
    uint32_t x = 0;
    #pragma unroll
    for (int i = 0; i < 16; i++) x |= f[4 * i];
    mbar_arrive_elect(bar + (x & zero));
}
__device__ __forceinline__ void flush(uint32_t (&o2)[10], const uint32_t (&o)[10]) {
    #pragma unroll
    for (int i = 0; i < 10; i++) o2[i] = hadd2(o2[i], o[i]);
}
__device__ __forceinline__ void attention_phase(int L, uint32_t lb, int wg, uint32_t (&qa)[8], uint32_t (&qb)[8], uint32_t (&SA)[32], uint32_t (&SB_)[32], uint64_t dk0, uint64_t dv0, uint32_t ca, uint32_t (&wa)[64], uint32_t zero, uint32_t sixteen) {
    uint32_t PA[32], PB[32], oa[10], ob[10], oa2[10], ob2[10];
    Shift ha, hb;
    uint32_t fail = (lds32(M_SS) ? 3u : 0u) | (lds32(M_SS + 4) ? 12u : 0u);
    ca += base32(fail) >> 4;
    const uint32_t oo = o_offset(), odb = lb + B_OD + wg * 8;
    constexpr uint64_t SL = R_SLOT >> 4, KH = 4096 >> 4;
    unit_start(SA, ha, oa2);
    exp_tile(SA, PA, ha, ca, sixteen);
    #pragma unroll
    for (int i = 0; i < 10; i++) { ob[i] = 0u; ob2[i] = 0u; }
    hb = ha;
    mbar_spin(lb + B_KS, 0);
    mbar_spin(lb + B_ONE, 0);
    #pragma unroll 1
    for (int it = 0; ; it++) {
        const uint32_t ph = it & 1;
        uint32_t qsw = 0;
        #pragma unroll
        for (int u = 0; u < 4; u++) {
            const uint64_t dk = opaque(dk0) + u * SL, dv = opaque(dv0) + u * SL;
            wg_fence();
            if (u == 0) issue_pv<true>(oa, PA, dv); else issue_pv<false>(oa, PA, dv);
            wg_qk_init(SA, qa[0], qa[1], qa[2], qa[3], dk);
            wg_qk_acc(SA, qa[4], qa[5], qa[6], qa[7], dk + KH);
            wg_commit();
            if (u > 0) wg_wait<1>();
            pin(SB_); pin(ob);
            if (u == 0) {
                flush(ob2, ob);
                if (__builtin_expect((it & 3) == 0, 0)) {
                    if (it) unit_end<0, 1>(ob2, hb.bad, odb, oo, fail, ldsf(M_IV));
                    unit_start(SB_, hb, ob2);
                }
            } else mbar_arrive_elect(lb + B_AE + 8 * (u - 1));
            if (u == 3) swap_q(qb, qsw ? qsw + 8192 : 0u);
            exp_tile(SB_, PB, hb, ca, sixteen);
            wg_fence();
            if (u == 0) issue_pv<true>(ob, PB, dv); else issue_pv<false>(ob, PB, dv);
            wg_qk_init(SB_, qb[0], qb[1], qb[2], qb[3], dk);
            wg_qk_acc(SB_, qb[4], qb[5], qb[6], qb[7], dk + KH);
            wg_commit();
            wg_wait<1>();
            pin(SA); pin(oa);
            if (u == 2) { qsw = it == 3 ? A_QX + tid_now() * 16 : 0u; swap_q(qa, qsw); }
            if (u == 3) {
                flush(oa2, oa);
                if (__builtin_expect((it & 3) == 3, 0)) {
                    TL(0, L * 32 + 7 + (it >> 2)); CK(0, L * 32 + 1 + (it >> 2));
                    if (it == 7) goto done;
                    unit_end<0, 0>(oa2, ha.bad, odb, oo, fail, ldsf(M_IV));
                    unit_start(SA, ha, oa2);
                }
            }
            exp_tile(SA, PA, ha, ca, sixteen);
            mbar_spin(lb + B_AF + 8 * ((u + 1) & 3), u < 3 ? ph : ph ^ 1);
        }
        wg_wait<0>();
        mbar_arrive_elect(lb + B_AE + 24);
    }
done:
    const float iv = ldsf(M_IV + 4);
    mbar_spin(lb + B_GU, 0);
    load_gu(wa, F_GU0, tid_now() >> 5, tid_now() & 31);
    unit_end<1, 0>(oa2, ha.bad, odb, oo, fail, iv);
    wg_wait<0>();
    pin(ob);
    mbar_arrive_elect(lb + B_AE + 24);
    flush(ob2, ob);
    unit_end<1, 1>(ob2, hb.bad, odb, oo, fail, iv);
    arrive_loaded(lb + B_FG, wa, zero);
    if (__builtin_expect(wg_any(fail != 0, NB_WG + wg), 0)) {
        uint4* const qs = &g_qsave[cta_now()][0][tid_now()];
        qs[4 * 256] = make_uint4(qa[0], qa[1], qa[2], qa[3]); qs[5 * 256] = make_uint4(qa[4], qa[5], qa[6], qa[7]);
        qs[6 * 256] = make_uint4(qb[0], qb[1], qb[2], qb[3]); qs[7 * 256] = make_uint4(qb[4], qb[5], qb[6], qb[7]);
        #pragma unroll
        for (int i = 0; i < 16; i++) qs[(8 + i) * 256] = make_uint4(wa[4*i], wa[4*i+1], wa[4*i+2], wa[4*i+3]);
        sts32(M_SR + (tid_now() >> 5) * 4, fail);
        named_sync(NB_WG + wg, 128);
        #pragma unroll 1
        for (int r = 0; r < 16; r++)
            if ((warp_uniform(lds32(M_SR + wg * 16 + (r & 3) * 4)) >> (r >> 2)) & 1) attn_repair(lb, wg, r & 3, r >> 3, (r >> 2) & 1);
        #pragma unroll
        for (int i = 0; i < 16; i++) { const uint4 v = __ldcg(qs + (8 + i) * 256); wa[4*i] = v.x; wa[4*i+1] = v.y; wa[4*i+2] = v.z; wa[4*i+3] = v.w; }
    }
    TL(0, L * 32 + 9); CK(0, L * 32 + 8);
}

__device__ __forceinline__ void oproj_steps(float (&acc)[64], uint32_t lb, int wg, int k0, int k1) {
    const bool leader = (tid_now() & 127) == 0;
    #pragma unroll 1
    for (int k = k0; k < k1; k++) {
        const uint32_t st = k & 3;
        mbar_spin(lb + B_OF + 8 * st, (k >> 2) & 1);
        const uint64_t da = desc_sw128(o_a(st) + wg * 8192, 16, 1024);
        const uint64_t db = desc_sw128(o_b(st), 8192, 1024);
        wg_fence();
        #pragma unroll
        for (int kk = 0; kk < 4; kk++) wg_gemm_n128(acc, da + kk * 2, db + kk * 128);
        wg_commit();
        wg_wait<1>();
        if (leader && k > 0) mbar_arrive(lb + B_OE + 8 * ((k - 1) & 3));
    }
}

__device__ __forceinline__ uint32_t lane_key(uint32_t key, int lane) { return (key | 31u) ^ lane; }
__device__ __forceinline__ uint4 best_of(const uint4& e, int lane) {
    const uint32_t m = redux_max(lane_key(e.x, lane)), src = ~m & 31u;
    return make_uint4(m, __shfl_sync(0xffffffffu, e.y, src), __shfl_sync(0xffffffffu, e.z, src), __shfl_sync(0xffffffffu, e.w, src));
}
template <typename T> __device__ __forceinline__ T* early(T* p) { asm volatile("" : "+l"(p)); return p; }
__device__ __forceinline__ void load_wd(uint32_t (&wd)[64], uint32_t lb, int warp, int lane) {
    mbar_spin(lb + B_WD, 0);
    const uint32_t a0 = F_WD + warp * 8192 + ((lane >> 4) * 8 + (lane & 7)) * 128, ch = ((lane >> 3) & 1) ^ (lane & 7);
    #pragma unroll
    for (int i = 0; i < 16; i++) ldsm4t(wd[4*i], wd[4*i+1], wd[4*i+2], wd[4*i+3], base32(a0 + ((ch ^ (i & 6)) << 4)) + (i >> 3) * 4096 + (i & 1) * 2048);
}
__device__ __forceinline__ void stage_tile(const uint32_t (&xa)[4], const uint32_t (&xv)[32]) {
    #pragma unroll
    for (int m = 0; m < 8; m++) stsm4(xa[m & 3] + (m < 4 ? YT0 - XT0 : YT1 - XT0), xv[4*m], xv[4*m+1], xv[4*m+2], xv[4*m+3]);
    fence_async_smem();
    __syncwarp();
}

__device__ __forceinline__ void tail_phase(int L, uint32_t lb, int wg, const uint32_t (&wa)[64]) {
    const int c = cta_now(), blk = blk_of(c), cb = cb_of(c), tid = tid_now();
    const int lane = tid & 31, w = (tid >> 5) & 3, g = lane >> 2, t = lane & 3;
    const int lr0 = wg * 64 + w * 16 + g;
    uint32_t xa[4];
    #pragma unroll
    for (int m = 0; m < 4; m++) xa[m] = base32(XT0 + (wg * 64 + w * 16 + (lane & 15)) * 128 + (((lane >> 4) ^ (lane & 7) ^ (2 * m)) << 4));
    uint32_t xv[32];
    const bool ffn = c < NFC;
    uint32_t wb[64], wd[64];
    float own[6];
    {
        float acc[64];
        #pragma unroll
        for (int i = 0; i < 64; i++) acc[i] = 0.f;
        pin(acc);
        float2 rs0 = make_float2(0.f, 0.f), rs1 = rs0;
        if (L) { rs0 = __ldcg(&g_x.rs1[blk * 128 + lr0]); rs1 = __ldcg(&g_x.rs1[blk * 128 + lr0 + 8]); }
        oproj_steps(acc, lb, wg, 0, 8);
        mbar_spin(lb + B_RES, 0);
        #pragma unroll
        for (int m = 0; m < 8; m++) ldsm4(xv[4*m], xv[4*m+1], xv[4*m+2], xv[4*m+3], xa[m & 3] + (m < 4 ? 0 : XT1 - XT0));
        if (L) {
            const int d = (int)lds32(M_RT + 12) - (blk * 128 + lr0);
            const Ln2 k0 = ln2_coef(rs0.y, d == 0 ? 0.f : rsq(rs0.x + LN_EPS)), k1 = ln2_coef(rs1.y, d == 8 ? 0.f : rsq(rs1.x + LN_EPS));
            #pragma unroll
            for (int j = 0; j < 16; j++) { xv[2*j] = add_ln2(xv[2*j], k0); xv[2*j+1] = add_ln2(xv[2*j+1], k1); }
        }
        pin(xv);
        oproj_steps(acc, lb, wg, 8, 16);
        uint32_t wv[16];
        #pragma unroll
        for (int i = 0; i < 4; i++) ldsm4(wv[4*i], wv[4*i+1], wv[4*i+2], wv[4*i+3], (lane & 1) ? M_RED + (lane >> 3) * 16 + i * 64 : M_RED + 256);
        uint4* const pdst = early(&g_x.part[L][blk][cb][lr0]);
        wg_wait<0>();
        pin(acc);
        if ((tid & 127) == 0) mbar_arrive(lb + B_OE + 24);
        TL(0, L * 32 + 11); CK(0, L * 32 + 13);
        float sa[4] = {0.f, 0.f, 0.f, 0.f}, sb[4] = {0.f, 0.f, 0.f, 0.f}, sc[4] = {0.f, 0.f, 0.f, 0.f};
        float sd[4] = {0.f, 0.f, 0.f, 0.f}, se[4] = {0.f, 0.f, 0.f, 0.f};
        #pragma unroll
        for (int m = 0; m < 8; m++) {
            #pragma unroll
            for (int i = 0; i < 4; i++) xv[4*m+i] = badd2(xv[4*m+i], pack_bf16(acc[8*m + 2*i], acc[8*m + 2*i + 1]));
            mma_bf16(sa, xv[4*m], xv[4*m+1], xv[4*m+2], xv[4*m+3], wv[2*m], wv[2*m+1]);
            mma_bf16_k8(sb, xv[4*m], xv[4*m+1], xv[4*m]); mma_bf16_k8(sc, xv[4*m], xv[4*m+1], xv[4*m+1]);
            mma_bf16_k8(sd, xv[4*m+2], xv[4*m+3], xv[4*m+2]); mma_bf16_k8(se, xv[4*m+2], xv[4*m+3], xv[4*m+3]);
        }
        const float q0 = (g & 1) ? sb[1] + sd[1] : sb[0] + sd[0], q1 = (g & 1) ? sc[3] + se[3] : sc[2] + se[2];
        if (t == (g >> 1)) {
            st_x128(pdst, __float_as_uint(sa[0]), __float_as_uint(q0), __float_as_uint(sa[1]), 0u);
            st_x128(pdst + 8, __float_as_uint(sa[2]), __float_as_uint(q1), __float_as_uint(sa[3]), 0u);
        }
        __syncwarp();
        own[0] = sa[0]; own[1] = __shfl_sync(0xffffffffu, q0, (lane & 28) + (g >> 1)); own[2] = sa[1];
        own[3] = sa[2]; own[4] = __shfl_sync(0xffffffffu, q1, (lane & 28) + (g >> 1)); own[5] = sa[3];
    }
    TL(0, L * 32 + 12);
    load_gu(wb, F_GU1, tid >> 5, lane);
    stage_tile(xa, xv);
    uint4* const hdst = early(&g_x.hdr[L][(tid & 15) * 8 + cb][blk]);
    uint32_t* const cdst = early(&g_x.cand[L][blk][cb * 64 + t * 4]);
    const float ws = ldsf(M_WS);
    float mean, var, rstd;
    uint4 f;
    {
        const bool o0 = cb == 2 * t, o1 = cb == 2 * t + 1;
        const uint32_t m0 = o0 ? 0u : EMPTY, m1 = o1 ? 0u : EMPTY;
        const uint4* const psrc = &g_x.part[L][blk][2 * t][lr0];
        uint4 p[4];
        uint32_t n = 0;
        #pragma unroll 1
        do {
            p[0] = ld_x128(psrc); p[1] = ld_x128(psrc + 128); p[2] = ld_x128(psrc + 8); p[3] = ld_x128(psrc + 136);
            poll_tick(n);
        } while (warp_any((((p[0].w | p[2].w) & m0) | ((p[1].w | p[3].w) & m1)) != 0));
        mbar_arrive_elect_p(lb + B_XS, L == 0);
        float v[8];
        #pragma unroll
        for (int h = 0; h < 2; h++) {
            v[3*h] = (o0 ? own[3*h] : __uint_as_float(p[2*h].x)) + (o1 ? own[3*h] : __uint_as_float(p[2*h+1].x));
            v[3*h+1] = (o0 ? own[3*h+1] : __uint_as_float(p[2*h].y)) + (o1 ? own[3*h+1] : __uint_as_float(p[2*h+1].y));
            v[3*h+2] = (o0 ? own[3*h+2] : __uint_as_float(p[2*h].z)) + (o1 ? own[3*h+2] : __uint_as_float(p[2*h+1].z));
        }
        halve<3>(v, lane, 1);
        #pragma unroll
        for (int i = 0; i < 3; i++) v[i] += __shfl_xor_sync(0xffffffffu, v[i], 2);
        mean = v[0] * (1.f / D_);
        var = fmaxf(v[1] * (1.f / D_) - mean * mean, 0.f);
        rstd = rsq(var + LN_EPS);
        TL(0, L * 32 + 13);
        const uint32_t key = lane_key(order_bits(rstd * (v[2] - mean * ws)), lane);
        if (redux_max(key) == key) sts128(M_SR + (tid >> 5) * 16, key, __float_as_uint(mean), __float_as_uint(rstd), blk * 128 + lr0 + 8 * (t & 1));
        named_sync(NB_CONS, 256);
        f = best_of(lds128(M_SR + (lane & 7) * 16), lane);
        st_x128_if(tid < 16, hdst, f.x, f.y, f.z, f.w);
        const int d = (int)f.w - (blk * 128 + lr0);
        if ((d & ~8) == 0) {
            #pragma unroll
            for (int b = 0; b < 4; b++)
                st_x128(cdst + b * 16, d ? xv[8*b+1] : xv[8*b], d ? xv[8*b+3] : xv[8*b+2], d ? xv[8*b+5] : xv[8*b+4], d ? xv[8*b+7] : xv[8*b+6]);
        }
        __syncwarp();
    }
    if (t < 2) {
        if (L) { const Ln2 k = ln2_coef(mean, rstd); sts128(XT0 + (lr0 + 8 * t) * 16, k.nm, k.rh, k.rl, k.c); }
        else if (cb == 0) st_x64(&g_x.rs1[blk * 128 + lr0 + 8 * t], __float_as_uint(var), __float_as_uint(mean));
    }
    TL(0, L * 32 + 28);
    if (tid == 0) sts32(M_CR, f.w);
    __syncwarp();
    mbar_arrive_elect_p(lb + B_XS, L);
    load_wd(wd, lb, tid >> 5, lane);
    TL(0, L * 32 + 25);
    const uint32_t* const xsrc = early(&g_x.cand[L][0][(tid >> 5) * 32 + t * 4]);
    float* const ydst = early(&g_x.ypart[L][(tid >> 5) * 16 + t * 4][c][g]);
    uint4 e;
    {
        uint32_t n = 0;
        #pragma unroll 1
        do { e = ld_x128(&g_x.hdr[L][blk * 8 + cb][lane & 15]); poll_tick(n); } while (warp_any(e.w == EMPTY && (lane & 15) != blk));
        if ((lane & 15) == blk) e = f;
        e = best_of(e, lane);
    }
    TL(0, L * 32 + 14);
    if (tid == 0) sts128(M_RT + 16 * L, (e.x & 0x80000000u) ? e.x ^ 0x80000000u : ~e.x, e.y, e.z, e.w);
    if (tid == 0) mbar_arrive(lb + B_RT);
    if (ffn) {
        const uint32_t* src = xsrc + (~e.x & 15u) * (D_ / 2);
        const Ln2 kx = ln2_coef(__uint_as_float(e.y), __uint_as_float(e.z));
        uint4 x[4];
        uint32_t n = 0;
        #pragma unroll 1
        do {
            x[0] = ld_x128(src); x[1] = ld_x128(src + 16); x[2] = ld_x128(src + 256); x[3] = ld_x128(src + 272);
            poll_tick(n);
        } while (warp_any(max(max(x[0].x, x[1].x), max(x[2].x, x[3].x)) == EMPTY));
        TL(0, L * 32 + 15);
        float d[4][4];
        #pragma unroll
        for (int i = 0; i < 4; i++) { d[i][0] = 0.f; d[i][1] = 0.f; d[i][2] = 0.f; d[i][3] = 0.f; }
        #pragma unroll
        for (int k = 0; k < 8; k++) {
            const uint32_t b0 = ln2((k & 1) ? x[k >> 1].z : x[k >> 1].x, kx), b1 = ln2((k & 1) ? x[k >> 1].w : x[k >> 1].y, kx);
            const uint32_t* f = (k < 4 ? wa : wb) + (k & 3) * 16;
            #pragma unroll
            for (int i = 0; i < 4; i++) mma_bf16(d[i], f[4*i], f[4*i+1], f[4*i+2], f[4*i+3], b0, b1);
        }
        #pragma unroll
        for (int h = 0; h < 2; h++) {
            const float a = (t & 1) ? d[1][2*h] : d[0][2*h], b = (t & 1) ? d[3][2*h] : d[2][2*h];
            stsf(M_RED + ((tid >> 5) * 64 + t * 16 + h * 8 + g) * 4, (t & 2) ? b : a);
        }
        named_sync(NB_CONS, 256);
        TL(0, L * 32 + 16);
        float2 v[8];
        #pragma unroll
        for (int i = 0; i < 8; i++) v[i] = lds64f(base32(M_RED + lane * 8) + i * 256);
        const float s0 = ((v[0].x + v[1].x) + (v[2].x + v[3].x)) + ((v[4].x + v[5].x) + (v[6].x + v[7].x));
        const float s1 = ((v[0].y + v[1].y) + (v[2].y + v[3].y)) + ((v[4].y + v[5].y) + (v[6].y + v[7].y));
        const uint32_t mine = pack_bf16(s0, s1), other = __shfl_xor_sync(0xffffffffu, mine, 16);
        const uint32_t gv = lane < 16 ? mine : other, uv = lane < 16 ? other : mine;
        const float g0 = bf_lo(gv), g1 = bf_hi(gv);
        const uint32_t hv = bmul2(pack_bf16(g0 * sigmoid(g0), g1 * sigmoid(g1)), uv);
        uint32_t hb[4];
        #pragma unroll
        for (int i = 0; i < 4; i++) hb[i] = __shfl_sync(0xffffffffu, hv, 4 * i + t);
        float y[8][4];
        #pragma unroll
        for (int i = 0; i < 8; i++) {
            y[i][0] = 0.f; y[i][1] = 0.f; y[i][2] = 0.f; y[i][3] = 0.f;
            mma_bf16(y[i], wd[8*i], wd[8*i+1], wd[8*i+2], wd[8*i+3], hb[0], hb[1]);
            mma_bf16(y[i], wd[8*i+4], wd[8*i+5], wd[8*i+6], wd[8*i+7], hb[2], hb[3]);
        }
        #pragma unroll
        for (int i = 0; i < 2; i++)
            #pragma unroll
            for (int h = 0; h < 2; h++) {
                const float a = (t & 1) ? y[2 + i][2*h] : y[i][2*h], b = (t & 1) ? y[6 + i][2*h] : y[4 + i][2*h];
                st_x32(ydst + (i * 2 + h) * (NFC * 8), __float_as_uint((t & 2) ? b : a));
            }
    }
    __syncwarp();
    mbar_arrive_elect(lb + B_FD);
    TL(0, L * 32 + 17);
}

__device__ __forceinline__ void qkv_load_w(const Maps& mp, uint32_t dst, int k, uint32_t fb) { tma_load3(dst, &mp.wqkv, nt_of(blockIdx.x) * 64, k * 64, 0, fb); }
__device__ __forceinline__ void qkv_load_x(const CUtensorMap* tx, uint32_t sa, int k, uint32_t fb) {
    #pragma unroll
    for (int a = 0; a < 2; a++) tma_load(sa + a * 16384, tx, k * 64, mt_of(blockIdx.x) * 256 + a * 128, fb);
}
__device__ __forceinline__ void producer_role(const Maps& mp) {
    const int c = blockIdx.x, mt = mt_of(c), nt = nt_of(c), blk = blk_of(c), cb = cb_of(c);
    const uint64_t pol = policy_evict_first();
    #pragma unroll 1
    for (int L = 0; L < 2; L++) {
        const uint32_t lb = M_BAR + L * BAR_SET;
        const CUtensorMap* tx = &mp.x[L];
        mbar_expect_tx(lb + B_SW, 49152);
        if (L == 0) {
            mbar_nap(lb + B_QF, 0);
            qkv_load_w(mp, SD_W, mt * 2, lb + B_SW);
            qkv_load_w(mp, SD_W + 24576, mt * 2 + 1, lb + B_SW);
        }
        {
            uint32_t st = 0, ph = L;
            #pragma unroll 1
            for (int k = L ? 0 : 3; k < 16; k++) {
                mbar_sleep(k < 2 ? M_BAR + (k ? B_FD : B_XS) : lb + B_QE + 8 * st, k < 2 ? 0 : ph);
                const uint32_t fb = lb + B_QF + 8 * st, sa = SB + st * Q_STB;
                mbar_expect_tx(fb, Q_STB);
                qkv_load_w(mp, sa + Q_ABYTES, k, fb);
                if (k == 0) {
                    mbar_nap(M_BAR + B_XD, 0);
                    flags16_wait(g_x.x[mt]);
                    fence_async_global();
                    mbar_nap(M_BAR + B_RT, 0);
                    TL(256, 32);
                }
                qkv_load_x(tx, sa, k, fb);
                if (L && k >= 3 && k < 7) tma_load(SD_W + (k - 3) * 12288, &mp.r, c * 24, (k - 3) * 256, lb + B_SW);
                if (++st == 3) { st = 0; ph ^= 1; }
            }
        }
        mbar_sleep(lb + B_QE, 1);
        TL(256, L * 32 + 26);
        mbar_arrive(lb + B_AF);
        {
            const char* kv = g_kv + (size_t)nt * 32 * KV_TILE;
            const uint8_t* fl = g_x.kv[L][nt * 2];
            __nanosleep(200);
            #pragma unroll 1
            for (int j = 1; j < 4; j++) {
                flag_wait(fl + ((2 * mt + j + 1) & 15));
                fence_async_global();
                const uint32_t bytes = j == 1 ? 8192 : 16384;
                mbar_expect_tx(lb + B_AF + 8 * j, bytes);
                bulk_load(A_RING + j * R_SLOT, kv + ((2 * mt + j) & 15) * KV_TILE, bytes, lb + B_AF + 8 * j);
                if (j == 1) TL(256, L * 32 + 21);
            }
            flags16_wait(fl);
            fence_async_global();
            int t0 = 2 * mt;
            #pragma unroll 1
            for (int it = 1; it < 8; it++) {
                #pragma unroll
                for (int u = 0; u < 4; u++) {
                    const char* src = kv + ((t0 + 4 * it + u) & 15) * KV_TILE;
                    const uint32_t fb = lb + B_AF + 8 * u, dst = A_RING + u * R_SLOT;
                    mbar_nap(lb + B_AE + 8 * u, (it - 1) & 1);
                    mbar_expect_tx(fb, 16384);
                    if (u < 3) bulk_load(dst, src, 16384, fb);
                    else {
                        bulk_load(dst + 8192, src + 8192, 8192, fb);
                        if (it == 3) {
                            flags16_wait(fl + 128);
                            fence_async_global();
                            kv += 16 * KV_TILE; src = kv + 15 * KV_TILE; t0 = 0;
                        }
                        bulk_load(dst, src, 8192, fb);
                    }
                }
            }
        }
        #pragma unroll 1
        for (int it = 0; it < 4; it++) {
            #pragma unroll
            for (int s = 0; s < 4; s++) {
                mbar_spin(lb + (it ? B_OE + 8 * s : s < 2 ? B_AE + 8 + 8 * s : B_FG), it ? (it - 1) & 1 : s < 2);
                const uint32_t fb = lb + B_OF + 8 * s;
                mbar_expect_tx(fb, 32768);
                #pragma unroll
                for (int b = 0; b < 2; b++)
                    tma_load5(o_b(s) + b * 8192, &mp.wo[it >> 1], cb * 128 + b * 64, (it & 1) * 8 + s * 2, fb);
                if (s == 0 && !(it & 1)) {
                    ctr_wait(g_x.o[L][blk][it >> 1], 15);
                    fence_async_global();
                    TL(256, L * 32 + 10);
                }
                tma_load(o_a(s), &mp.o, it * 256 + s * 64, blk * 128, fb);
            }
            if (it == 0) {
                mbar_spin(lb + B_AE + 24, 1);
                mbar_expect_tx(lb + B_RES, 32768);
                tma_load_s(XT0, tx, cb * 128, blk * 128, lb + B_RES, pol);
                tma_load_s(XT1, tx, cb * 128 + 64, blk * 128, lb + B_RES, pol);
            }
        }
        if (c < NFC) {
            #pragma unroll 1
            for (int i = 0; i < 4; i++) {
                mbar_spin(lb + B_OE + 16 + 8 * (i >> 1), 1);
                tma_load3_s(F_WD + i * 16384, &mp.d, 0, c * 32, i * 4, lb + B_WD, pol);
            }
        }
    }
}

__global__ void __launch_bounds__(384, 1) k_all(const __grid_constant__ Maps mp, const bf16* __restrict__ x0, const bf16* __restrict__ wo, const bf16* __restrict__ w_down,
                                                const bf16* __restrict__ w_r, bf16* __restrict__ out, const uint64_t dk0, const uint64_t dv0, const uint32_t ca, const uint32_t zero, const uint32_t sixteen) {
    extern __shared__ __align__(1024) char smem[];
    if (smem_u32(smem) != SB) __trap();
    const int warp = warp_uniform(threadIdx.x >> 5), wg = warp >> 2;
    TL(0, 0);
    if (warp == 8) {
      if (elect_one()) {
        tm_prefetch(&mp.x[0]); tm_prefetch(&mp.wqkv);
        #pragma unroll
        for (int s = 0; s < 3; s++) { mbar_init(M_BAR + B_QF + 8 * s, 1); mbar_init(M_BAR + BAR_SET + B_QF + 8 * s, 1); }
        fence_mbar_init();
        #pragma unroll 1
        for (int s = 0; s < 3; s++) {
            const uint32_t sa = SB + s * Q_STB, fb = M_BAR + B_QF + 8 * s;
            mbar_expect_tx(fb, Q_STB);
            qkv_load_x(&mp.x[0], sa, s, fb);
            qkv_load_w(mp, sa + Q_ABYTES, s, fb);
        }
      }
      __syncwarp();
    } else if (warp > 8) {
        if (elect_one()) {
            const uint32_t o0 = warp == 9 ? B_AF : warp == 10 ? B_QE : B_AE, o1 = warp == 9 ? B_QE : warp == 10 ? B_AE : B_END, cnt = warp == 9 ? 1 : warp == 10 ? 2 : 8;
            #pragma unroll 1
            for (uint32_t o = o0; o < o1; o += 8) { const uint32_t n = o == B_K0 ? 4 : cnt; mbar_init(M_BAR + o, n); mbar_init(M_BAR + BAR_SET + o, n); }
            fence_mbar_init();
        }
        __syncwarp();
    }
    __syncthreads();
    if (wg == 2) {
        reg_dec<40>();
        if (warp > 8) side_role(mp, x0, wo, w_down, w_r, out);
        else if (elect_one()) producer_role(mp);
    } else {
        reg_inc<232>();
        #pragma unroll 1
        for (int L = 0; L < 2; L++) {
            const uint32_t lb = M_BAR + L * BAR_SET;
            uint32_t qa[8], qb[8], sa[32], sb[32], wa[64];
            qkv_phase(L, lb, wg, qa, qb, sa, sb);
            attention_phase(L, lb, wg, qa, qb, sa, sb, dk0, dv0, ca, wa, zero, sixteen);
            tail_phase(L, lb, wg, wa);
        }
    }
}

typedef CUresult (*EncodeFn)(CUtensorMap*, CUtensorMapDataType, cuuint32_t, void*, const cuuint64_t*, const cuuint64_t*, const cuuint32_t*,
                             const cuuint32_t*, CUtensorMapInterleave, CUtensorMapSwizzle, CUtensorMapL2promotion, CUtensorMapFloatOOBfill);

void make_map(EncodeFn enc, CUtensorMap* tm, const void* ptr, int rank, const cuuint64_t* dims, const cuuint64_t* strides, const cuuint32_t* box, CUtensorMapSwizzle sw) {
    const cuuint32_t es[5] = {1, 1, 1, 1, 1};
    enc(tm, CU_TENSOR_MAP_DATA_TYPE_BFLOAT16, rank, const_cast<void*>(ptr), dims, strides, box, es, CU_TENSOR_MAP_INTERLEAVE_NONE, sw,
        box[0] == 64 ? CU_TENSOR_MAP_L2_PROMOTION_L2_128B : CU_TENSOR_MAP_L2_PROMOTION_NONE, CU_TENSOR_MAP_FLOAT_OOB_FILL_NONE);
}
void make_map2(EncodeFn enc, CUtensorMap* tm, const void* ptr, uint64_t cols, uint64_t rows, uint32_t bc, uint32_t br, CUtensorMapSwizzle sw) {
    const cuuint64_t dims[2] = {cols, rows}, strides[1] = {cols * 2};
    const cuuint32_t box[2] = {bc, br};
    make_map(enc, tm, ptr, 2, dims, strides, box, sw);
}

}

extern "C" void kernel_launch(void* const* d_in, const int* in_sizes, int n_in, void* d_out, int out_size) {
    const bf16* x0 = (const bf16*)d_in[0];
    const bf16* wqkv = (const bf16*)d_in[1];
    const bf16* wo = (const bf16*)d_in[2];
    const bf16* w_r = (const bf16*)d_in[4];
    const bf16* w_gate = (const bf16*)d_in[5];
    const bf16* w_up = (const bf16*)d_in[6];
    const bf16* w_down = (const bf16*)d_in[7];

    EncodeFn enc = nullptr;
    cudaDriverEntryPointQueryResult qr;
    cudaGetDriverEntryPoint("cuTensorMapEncodeTiled", (void**)&enc, cudaEnableDefault, &qr);
    void *p_o, *p_x1;
    cudaGetSymbolAddress(&p_o, g_o); cudaGetSymbolAddress(&p_x1, g_x1);
    const CUtensorMapSwizzle S128 = CU_TENSOR_MAP_SWIZZLE_128B, S64 = CU_TENSOR_MAP_SWIZZLE_64B, S0 = CU_TENSOR_MAP_SWIZZLE_NONE;
    Maps mp;
    make_map2(enc, &mp.x[0], x0, D_, S_, 64, 128, S128); make_map2(enc, &mp.x[1], p_x1, D_, S_, 64, 128, S128);
    make_map2(enc, &mp.o, p_o, D_, S_, 64, 128, S128);
    {
        const cuuint64_t dims[3] = {D_, D_, 3}, strides[2] = {3 * D_ * 2, D_ * 2};
        const cuuint32_t box[3] = {64, 64, 3};
        make_map(enc, &mp.wqkv, wqkv, 3, dims, strides, box, S128);
    }
    make_map2(enc, &mp.r, wqkv, 3 * D_, D_, 24, 256, S0);
    make_map2(enc, &mp.g, w_gate, FF, D_, 32, 256, S64); make_map2(enc, &mp.u, w_up, FF, D_, 32, 256, S64);
    for (int p = 0; p < 2; p++) {
        const cuuint64_t dims[5] = {D_, 2, 4, 4, 16}, strides[4] = {D_ * 2, 8 * D_ * 2, 2 * D_ * 2, 64 * D_ * 2};
        const cuuint32_t box[5] = {64, 2, 4, 4, 2};
        make_map(enc, &mp.wo[p], wo + (size_t)p * 32 * D_, 5, dims, strides, box, S128);
    }
    {
        const cuuint64_t dims[3] = {64, FF, 16}, strides[2] = {D_ * 2, 128};
        const cuuint32_t box[3] = {64, 32, 4};
        make_map(enc, &mp.d, w_down, 3, dims, strides, box, S128);
    }
    cudaFuncSetAttribute(k_all, cudaFuncAttributeMaxDynamicSharedMemorySize, K_SMEM);
    k_all<<<128, 384, K_SMEM, cudaStreamPerThread>>>(mp, x0, wo, w_down, w_r, (bf16*)d_out, desc_plain(A_RING, 2048, 128), desc_plain(A_RING + 8192, 128, 2048), 0x64A264A2u, 0u, 16u);
}
```

```cpp
#include <cuda_runtime.h>
#include <cuda_bf16.h>
#include <cuda_fp16.h>
#include <cuda.h>
#include <cudaTypedefs.h>
#include <stdint.h>

namespace {

typedef __nv_bfloat16 bf16;

constexpr int S_ = 2048, D_ = 1024, NH = 32, FF = 3584, NFC = FF / 32;
constexpr float LN_EPS = 1e-5f;
constexpr float QSCALE = 0.17677669529663687f * 1.4426950408889634f;
constexpr uint32_t EMPTY = 0xFFFFFFFFu;

constexpr int KV_TILE = 16384;
__device__ __align__(1024) char g_kv[NH * 16 * KV_TILE];
__device__ __align__(1024) bf16 g_o[S_ * D_];
__device__ __align__(1024) bf16 g_x1[S_ * D_];
__device__ __align__(16) float2 g_cs[8][3 * D_];
__device__ __align__(16) float2 g_rs0[S_];
__device__ uint4 g_qsave[128][29][256];
struct Xchg {
    uint4 part[2][16][8][128];
    float ypart[2][128][NFC][8];
    uint32_t cand[2][16][D_ / 2];
    uint4 hdr[2][128][16];
    float2 rs1[S_];
    float fix[3 * D_];
    uint32_t x2row[D_ / 2];
    uint8_t kv[2][NH][128];
    int o[2][16][2][32];
    uint8_t x[8][128];
};
constexpr int FILL = (sizeof(Xchg) / 128 + 127) / 128 * 8;
union XchgFill { Xchg x; uint4 fill[128][FILL]; };
static_assert(FILL > 768 && FILL <= 1024, "exchange area");
__device__ __align__(128) XchgFill g_u;
#define g_x g_u.x
__device__ int g_pctr;

constexpr uint32_t SMEM_BASE = 1024;

__device__ __forceinline__ int tid_now() { int v; asm volatile("mov.u32 %0, %%tid.x;" : "=r"(v)); return v; }
__device__ __forceinline__ int cta_now() { int v; asm volatile("mov.u32 %0, %%ctaid.x;" : "=r"(v)); return v; }
__device__ __forceinline__ uint64_t opaque(uint64_t v) { uint64_t r; asm volatile("mov.b64 %0, %1;" : "=l"(r) : "l"(v)); return r; }
__device__ __forceinline__ uint32_t base32(uint32_t v) { uint32_t r; asm("mov.b32 %0, %1;" : "=r"(r) : "r"(v)); return r; }
__device__ __forceinline__ uint32_t smem_u32(const void* p) { return (uint32_t)__cvta_generic_to_shared(p); }
__device__ __forceinline__ void mbar_init(uint32_t bar, int cnt) { asm volatile("mbarrier.init.shared::cta.b64 [%0], %1;" :: "r"(bar), "r"(cnt) : "memory"); }
__device__ __forceinline__ void mbar_expect_tx(uint32_t bar, uint32_t bytes) { asm volatile("mbarrier.arrive.expect_tx.shared::cta.b64 _, [%0], %1;" :: "r"(bar), "r"(bytes) : "memory"); }
__device__ __forceinline__ void mbar_arrive(uint32_t bar) { asm volatile("mbarrier.arrive.shared::cta.b64 _, [%0];" :: "r"(bar) : "memory"); }
__device__ __forceinline__ void mbar_sleep(uint32_t bar, uint32_t parity) {
    asm volatile("{\n.reg .pred p;\n.reg .u32 n;\nmov.u32 n, 0;\n"
                 "LAB_WAIT:\nmbarrier.try_wait.parity.shared::cta.b64 p, [%0], %1, 0x10000;\n@p bra LAB_DONE;\n"
                 "add.u32 n, n, 1;\nsetp.lt.u32 p, n, 0x10000;\n@p bra LAB_WAIT;\ntrap;\nLAB_DONE:\n}" :: "r"(bar), "r"(parity) : "memory");
}
__device__ __forceinline__ void mbar_nap(uint32_t bar, uint32_t parity) {
    asm volatile("{\n.reg .pred p;\nLAB_WAIT:\nmbarrier.try_wait.parity.shared::cta.b64 p, [%0], %1, 0x10000;\n@!p bra LAB_WAIT;\n}" :: "r"(bar), "r"(parity) : "memory");
}
__device__ __forceinline__ void mbar_spin(uint32_t bar, uint32_t parity) {
    asm volatile("{\n.reg .pred p;\nLAB_WAIT:\nmbarrier.try_wait.parity.shared::cta.b64 p, [%0], %1;\n@!p bra LAB_WAIT;\n}" :: "r"(bar), "r"(parity) : "memory");
}
__device__ __forceinline__ uint32_t mbar_test(uint32_t bar, uint32_t parity) {
    uint32_t ok;
    asm volatile("{\n.reg .pred p;\nmbarrier.test_wait.parity.shared::cta.b64 p, [%1], %2;\nselp.u32 %0, 1, 0, p;\n}" : "=r"(ok) : "r"(bar), "r"(parity) : "memory");
    return ok;
}
__device__ __forceinline__ bool elect_one() {
    uint32_t r;
    asm volatile("{\n.reg .pred p;\nelect.sync _|p, 0xffffffff;\nselp.u32 %0, 1, 0, p;\n}" : "=r"(r));
    return r != 0;
}
__device__ __forceinline__ void mbar_arrive_elect(uint32_t bar) {
    asm volatile("{\n.reg .pred p;\nelect.sync _|p, 0xffffffff;\n@p mbarrier.arrive.shared::cta.b64 _, [%0];\n}" :: "r"(bar) : "memory");
}
__device__ __forceinline__ void mbar_arrive_elect_p(uint32_t bar, uint32_t on) {
    asm volatile("{\n.reg .pred p, q;\nelect.sync _|p, 0xffffffff;\nsetp.ne.and.u32 q, %1, 0, p;\n@q mbarrier.arrive.shared::cta.b64 _, [%0];\n}" :: "r"(bar), "r"(on) : "memory");
}
__device__ __forceinline__ int warp_uniform(int v) { return __shfl_sync(0xffffffffu, v, 0); }
__device__ __forceinline__ void fence_mbar_init() { asm volatile("fence.mbarrier_init.release.cluster;" ::: "memory"); }
__device__ __forceinline__ void fence_async_smem() { asm volatile("fence.proxy.async.shared::cta;" ::: "memory"); }
__device__ __forceinline__ void fence_async_global() { asm volatile("fence.proxy.async.global;" ::: "memory"); }
__device__ __forceinline__ void named_sync(int id, int n) { asm volatile("bar.sync %0, %1;" :: "r"(id), "r"(n) : "memory"); }
__device__ __forceinline__ void named_arrive(int id, int n) { asm volatile("bar.arrive %0, %1;" :: "r"(id), "r"(n) : "memory"); }
__device__ __forceinline__ void bulk_load(uint32_t dst, const void* src, uint32_t bytes, uint32_t bar) {
    asm volatile("cp.async.bulk.shared::cluster.global.mbarrier::complete_tx::bytes [%0], [%1], %2, [%3];" :: "r"(dst), "l"(src), "r"(bytes), "r"(bar) : "memory");
}
__device__ __forceinline__ void bulk_store(void* dst, uint32_t src, uint32_t bytes) {
    asm volatile("cp.async.bulk.global.shared::cta.bulk_group [%0], [%1], %2;" :: "l"(dst), "r"(src), "r"(bytes) : "memory");
}
__device__ __forceinline__ void bulk_commit() { asm volatile("cp.async.bulk.commit_group;" ::: "memory"); }
__device__ __forceinline__ void bulk_wait() { asm volatile("cp.async.bulk.wait_group 0;" ::: "memory"); }
__device__ __forceinline__ void l2_prefetch(const void* src, uint32_t bytes) {
    asm volatile("cp.async.bulk.prefetch.L2.global [%0], %1;" :: "l"(src), "r"(bytes) : "memory");
}
__device__ __forceinline__ void tma_load(uint32_t dst, const CUtensorMap* tm, int c0, int c1, uint32_t bar) {
    asm volatile("cp.async.bulk.tensor.2d.shared::cluster.global.mbarrier::complete_tx::bytes [%0], [%1, {%3, %4}], [%2];"
                 :: "r"(dst), "l"(tm), "r"(bar), "r"(c0), "r"(c1) : "memory");
}
__device__ __forceinline__ void tma_load3(uint32_t dst, const CUtensorMap* tm, int c0, int c1, int c2, uint32_t bar) {
    asm volatile("cp.async.bulk.tensor.3d.shared::cluster.global.mbarrier::complete_tx::bytes [%0], [%1, {%3, %4, %5}], [%2];"
                 :: "r"(dst), "l"(tm), "r"(bar), "r"(c0), "r"(c1), "r"(c2) : "memory");
}
__device__ __forceinline__ void tma_load5(uint32_t dst, const CUtensorMap* tm, int c0, int c4, uint32_t bar) {
    asm volatile("cp.async.bulk.tensor.5d.shared::cluster.global.mbarrier::complete_tx::bytes [%0], [%1, {%3, %5, %5, %5, %4}], [%2];"
                 :: "r"(dst), "l"(tm), "r"(bar), "r"(c0), "r"(c4), "r"(0) : "memory");
}
__device__ __forceinline__ uint64_t policy_evict_first() { uint64_t p; asm volatile("createpolicy.fractional.L2::evict_first.b64 %0, 1.0;" : "=l"(p)); return p; }
__device__ __forceinline__ void tma_load_s(uint32_t dst, const CUtensorMap* tm, int c0, int c1, uint32_t bar, uint64_t pol) {
    asm volatile("cp.async.bulk.tensor.2d.shared::cluster.global.mbarrier::complete_tx::bytes.L2::cache_hint [%0], [%1, {%3, %4}], [%2], %5;"
                 :: "r"(dst), "l"(tm), "r"(bar), "r"(c0), "r"(c1), "l"(pol) : "memory");
}
__device__ __forceinline__ void tma_load3_s(uint32_t dst, const CUtensorMap* tm, int c0, int c1, int c2, uint32_t bar, uint64_t pol) {
    asm volatile("cp.async.bulk.tensor.3d.shared::cluster.global.mbarrier::complete_tx::bytes.L2::cache_hint [%0], [%1, {%3, %4, %5}], [%2], %6;"
                 :: "r"(dst), "l"(tm), "r"(bar), "r"(c0), "r"(c1), "r"(c2), "l"(pol) : "memory");
}
__device__ __forceinline__ void tma_store(const CUtensorMap* tm, uint32_t src, int c0, int c1) {
    asm volatile("cp.async.bulk.tensor.2d.global.shared::cta.bulk_group [%0, {%2, %3}], [%1];" :: "l"(tm), "r"(src), "r"(c0), "r"(c1) : "memory");
}
__device__ __forceinline__ void tm_prefetch(const CUtensorMap* tm) { asm volatile("prefetch.tensormap [%0];" :: "l"(tm) : "memory"); }
__device__ __forceinline__ void wg_fence() { asm volatile("wgmma.fence.sync.aligned;" ::: "memory"); }
__device__ __forceinline__ void wg_commit() { asm volatile("wgmma.commit_group.sync.aligned;" ::: "memory"); }
template <int N> __device__ __forceinline__ void wg_wait() { asm volatile("wgmma.wait_group.sync.aligned %0;" :: "n"(N) : "memory"); }
template <int N> __device__ __forceinline__ void pin(uint32_t (&r)[N]) {
    #pragma unroll
    for (int i = 0; i < N; i++) asm volatile("" : "+r"(r[i]) :: "memory");
}
template <int N> __device__ __forceinline__ void pin(float (&r)[N]) {
    #pragma unroll
    for (int i = 0; i < N; i++) asm volatile("" : "+f"(r[i]) :: "memory");
}
template <int N> __device__ __forceinline__ void reg_inc() { asm volatile("setmaxnreg.inc.sync.aligned.u32 %0;" :: "n"(N)); }
template <int N> __device__ __forceinline__ void reg_dec() { asm volatile("setmaxnreg.dec.sync.aligned.u32 %0;" :: "n"(N)); }
__host__ __device__ constexpr uint64_t desc_plain(uint32_t addr, uint32_t lbo, uint32_t sbo) {
    return (uint64_t)((addr & 0x3FFFF) >> 4) | ((uint64_t)(lbo >> 4) << 16) | ((uint64_t)(sbo >> 4) << 32);
}
__host__ __device__ constexpr uint64_t desc_sw128(uint32_t addr, uint32_t lbo, uint32_t sbo) { return desc_plain(addr, lbo, sbo) | (1ull << 62); }

__device__ __forceinline__ uint32_t lds32(uint32_t a) { uint32_t v; asm volatile("ld.shared.b32 %0, [%1];" : "=r"(v) : "r"(a) : "memory"); return v; }
__device__ __forceinline__ uint32_t lds16(uint32_t a) { uint32_t v; asm volatile("ld.shared.u16 %0, [%1];" : "=r"(v) : "r"(a) : "memory"); return v; }
__device__ __forceinline__ float ldsf(uint32_t a) { return __uint_as_float(lds32(a)); }
__device__ __forceinline__ float2 lds64f(uint32_t a) { float2 v; asm volatile("ld.shared.v2.f32 {%0, %1}, [%2];" : "=f"(v.x), "=f"(v.y) : "r"(a) : "memory"); return v; }
__device__ __forceinline__ uint4 lds128(uint32_t a) { uint4 v; asm volatile("ld.shared.v4.b32 {%0, %1, %2, %3}, [%4];" : "=r"(v.x), "=r"(v.y), "=r"(v.z), "=r"(v.w) : "r"(a) : "memory"); return v; }
__device__ __forceinline__ void sts32(uint32_t a, uint32_t v) { asm volatile("st.shared.b32 [%0], %1;" :: "r"(a), "r"(v) : "memory"); }
__device__ __forceinline__ void stsf(uint32_t a, float v) { sts32(a, __float_as_uint(v)); }
__device__ __forceinline__ void sts64(uint32_t a, uint32_t x, uint32_t y) { asm volatile("st.shared.v2.b32 [%0], {%1, %2};" :: "r"(a), "r"(x), "r"(y) : "memory"); }
__device__ __forceinline__ void sts128(uint32_t a, uint32_t x, uint32_t y, uint32_t z, uint32_t w) { asm volatile("st.shared.v4.b32 [%0], {%1, %2, %3, %4};" :: "r"(a), "r"(x), "r"(y), "r"(z), "r"(w) : "memory"); }
__device__ __forceinline__ void stsm4(uint32_t a, uint32_t x, uint32_t y, uint32_t z, uint32_t w) {
    asm volatile("stmatrix.sync.aligned.m8n8.x4.shared.b16 [%0], {%1, %2, %3, %4};" :: "r"(a), "r"(x), "r"(y), "r"(z), "r"(w) : "memory");
}
__device__ __forceinline__ void ldsm4(uint32_t& a0, uint32_t& a1, uint32_t& a2, uint32_t& a3, uint32_t addr) {
    asm volatile("ldmatrix.sync.aligned.m8n8.x4.shared.b16 {%0,%1,%2,%3}, [%4];" : "=r"(a0), "=r"(a1), "=r"(a2), "=r"(a3) : "r"(addr) : "memory");
}
__device__ __forceinline__ void ldsm4t(uint32_t& a0, uint32_t& a1, uint32_t& a2, uint32_t& a3, uint32_t addr) {
    asm volatile("ldmatrix.sync.aligned.m8n8.x4.trans.shared.b16 {%0,%1,%2,%3}, [%4];" : "=r"(a0), "=r"(a1), "=r"(a2), "=r"(a3) : "r"(addr) : "memory");
}
__device__ __forceinline__ void mma_bf16(float (&d)[4], uint32_t a0, uint32_t a1, uint32_t a2, uint32_t a3, uint32_t b0, uint32_t b1) {
    asm("mma.sync.aligned.m16n8k16.row.col.f32.bf16.bf16.f32 {%0,%1,%2,%3}, {%4,%5,%6,%7}, {%8,%9}, {%0,%1,%2,%3};"
        : "+f"(d[0]), "+f"(d[1]), "+f"(d[2]), "+f"(d[3]) : "r"(a0), "r"(a1), "r"(a2), "r"(a3), "r"(b0), "r"(b1));
}
__device__ __forceinline__ void mma_bf16_k8(float (&d)[4], uint32_t a0, uint32_t a1, uint32_t b0) {
    asm("mma.sync.aligned.m16n8k8.row.col.f32.bf16.bf16.f32 {%0,%1,%2,%3}, {%4,%5}, {%6}, {%0,%1,%2,%3};"
        : "+f"(d[0]), "+f"(d[1]), "+f"(d[2]), "+f"(d[3]) : "r"(a0), "r"(a1), "r"(b0));
}
__device__ __forceinline__ void mma_f16(float (&d)[4], uint32_t a0, uint32_t a1, uint32_t a2, uint32_t a3, uint32_t b0, uint32_t b1) {
    asm("mma.sync.aligned.m16n8k16.row.col.f32.f16.f16.f32 {%0,%1,%2,%3}, {%4,%5,%6,%7}, {%8,%9}, {%0,%1,%2,%3};"
        : "+f"(d[0]), "+f"(d[1]), "+f"(d[2]), "+f"(d[3]) : "r"(a0), "r"(a1), "r"(a2), "r"(a3), "r"(b0), "r"(b1));
}
__device__ __forceinline__ void stg128_pred(void* p, const uint4& v, bool on) {
    asm volatile("{\n.reg .pred q;\nsetp.ne.u32 q, %5, 0;\n@q st.global.v4.b32 [%0], {%1, %2, %3, %4};\n}"
                 :: "l"(p), "r"(v.x), "r"(v.y), "r"(v.z), "r"(v.w), "r"((uint32_t)on) : "memory");
}
__device__ __forceinline__ void st_x32(void* p, uint32_t v) { asm volatile("st.relaxed.gpu.global.u32 [%0], %1;" :: "l"(p), "r"(v) : "memory"); }
__device__ __forceinline__ void st_x64(void* p, uint32_t x, uint32_t y) {
    asm volatile("{\n.reg .b64 v;\nmov.b64 v, {%1, %2};\nst.relaxed.gpu.global.b64 [%0], v;\n}" :: "l"(p), "r"(x), "r"(y) : "memory");
}
__device__ __forceinline__ void st_x128(void* p, uint32_t x, uint32_t y, uint32_t z, uint32_t w) {
    asm volatile("{\n.reg .b64 a, b;\n.reg .b128 v;\nmov.b64 a, {%1, %2};\nmov.b64 b, {%3, %4};\nmov.b128 v, {a, b};\nst.relaxed.gpu.global.b128 [%0], v;\n}"
                 :: "l"(p), "r"(x), "r"(y), "r"(z), "r"(w) : "memory");
}
__device__ __forceinline__ void st_x128_if(bool on, void* p, uint32_t x, uint32_t y, uint32_t z, uint32_t w) {
    asm volatile("{\n.reg .pred q;\n.reg .b64 a, b;\n.reg .b128 v;\nsetp.ne.u32 q, %5, 0;\nmov.b64 a, {%1, %2};\nmov.b64 b, {%3, %4};\nmov.b128 v, {a, b};\n"
                 "@q st.relaxed.gpu.global.b128 [%0], v;\n}" :: "l"(p), "r"(x), "r"(y), "r"(z), "r"(w), "r"((uint32_t)on) : "memory");
}
__device__ __forceinline__ uint32_t ld_x32(const void* p) { uint32_t v; asm volatile("ld.relaxed.gpu.global.u32 %0, [%1];" : "=r"(v) : "l"(p) : "memory"); return v; }
__device__ __forceinline__ uint2 ld_x64(const void* p) {
    uint2 v; asm volatile("{\n.reg .b64 a;\nld.relaxed.gpu.global.b64 a, [%2];\nmov.b64 {%0, %1}, a;\n}" : "=r"(v.x), "=r"(v.y) : "l"(p) : "memory"); return v;
}
__device__ __forceinline__ uint4 ld_x128(const void* p) {
    uint4 v;
    asm volatile("{\n.reg .b64 a, b;\n.reg .b128 v;\nld.relaxed.gpu.global.b128 v, [%4];\nmov.b128 {a, b}, v;\nmov.b64 {%0, %1}, a;\nmov.b64 {%2, %3}, b;\n}"
                 : "=r"(v.x), "=r"(v.y), "=r"(v.z), "=r"(v.w) : "l"(p) : "memory");
    return v;
}
__device__ __forceinline__ void poll_tick(uint32_t& n) { asm volatile("{\n.reg .pred p;\nadd.u32 %0, %0, 1;\nsetp.ge.u32 p, %0, 0x800000;\n@p st.global.u32 [%1], %0;\n}" : "+r"(n) : "l"(0ull)); }
__device__ __forceinline__ void ctr_arrive(int* c) { asm volatile("red.release.gpu.global.add.s32 [%0], 1;" :: "l"(c) : "memory"); }
__device__ __forceinline__ void ctr_wait(const int* c, int target) {
    int v;
    uint32_t n = 0;
    #pragma unroll 1
    do {
        asm volatile("ld.acquire.gpu.global.s32 %0, [%1];" : "=r"(v) : "l"(c) : "memory");
        poll_tick(n);
    } while (v < target);
}
__device__ __forceinline__ void flag_wait(const uint8_t* f) {
    uint32_t n = 0, v;
    #pragma unroll 1
    do { asm volatile("ld.acquire.gpu.global.u8 %0, [%1];" : "=r"(v) : "l"(f) : "memory"); poll_tick(n); } while (v);
}
__device__ __forceinline__ void flags16_wait(const uint8_t* f) {
    uint32_t n = 0;
    uint64_t v;
    #pragma unroll 1
    do {
        asm volatile("{\n.reg .b64 a, b;\n.reg .b128 v;\nld.acquire.gpu.global.b128 v, [%1];\nmov.b128 {a, b}, v;\nor.b64 %0, a, b;\n}" : "=l"(v) : "l"(f) : "memory");
        poll_tick(n);
    } while (v != 0);
}
__device__ __forceinline__ bool any_empty(const uint4& v) { return v.x == EMPTY || v.y == EMPTY || v.z == EMPTY || v.w == EMPTY; }
__device__ __forceinline__ bool warp_any(bool p) { return __any_sync(0xffffffffu, p); }

__device__ __forceinline__ float ex2(float x) { float y; asm("ex2.approx.ftz.f32 %0, %1;" : "=f"(y) : "f"(x)); return y; }
__device__ __forceinline__ float rsq(float x) { float y; asm("rsqrt.approx.ftz.f32 %0, %1;" : "=f"(y) : "f"(x)); return y; }
__device__ __forceinline__ float rcp(float x) { float y; asm("rcp.approx.ftz.f32 %0, %1;" : "=f"(y) : "f"(x)); return y; }
__device__ __forceinline__ float sigmoid(float x) { return rcp(1.f + ex2(x * -1.4426950408889634f)); }
__device__ __forceinline__ uint32_t pack_bf16(float lo, float hi) { uint32_t r; asm("cvt.rn.bf16x2.f32 %0, %1, %2;" : "=r"(r) : "f"(hi), "f"(lo)); return r; }
__device__ __forceinline__ uint32_t pack_f16(float lo, float hi) { uint32_t r; asm("cvt.rn.f16x2.f32 %0, %1, %2;" : "=r"(r) : "f"(hi), "f"(lo)); return r; }
__device__ __forceinline__ float bf_lo(uint32_t v) { return __uint_as_float(v << 16); }
__device__ __forceinline__ float bf_hi(uint32_t v) { return __uint_as_float(v & 0xFFFF0000u); }
__device__ __forceinline__ float bf_round(float x) { return __uint_as_float(pack_bf16(0.f, x)); }
__device__ __forceinline__ void h2_unpack(uint32_t v, float& lo, float& hi) {
    asm("{.reg .f16 l, h; mov.b32 {l, h}, %2; cvt.f32.f16 %0, l; cvt.f32.f16 %1, h;}" : "=f"(lo), "=f"(hi) : "r"(v));
}
__device__ __forceinline__ uint32_t hadd2(uint32_t a, uint32_t b) { uint32_t r; asm("add.rn.f16x2 %0, %1, %2;" : "=r"(r) : "r"(a), "r"(b)); return r; }
__device__ __forceinline__ uint32_t hmax2(uint32_t a, uint32_t b) { uint32_t r; asm("max.f16x2 %0, %1, %2;" : "=r"(r) : "r"(a), "r"(b)); return r; }
__device__ __forceinline__ uint32_t badd2(uint32_t a, uint32_t b) { uint32_t r; asm("add.rn.bf16x2 %0, %1, %2;" : "=r"(r) : "r"(a), "r"(b)); return r; }
__device__ __forceinline__ uint32_t bmul2(uint32_t a, uint32_t b) { uint32_t r; asm("mul.rn.bf16x2 %0, %1, %2;" : "=r"(r) : "r"(a), "r"(b)); return r; }
__device__ __forceinline__ float warp_sum(float v) {
    #pragma unroll
    for (int o = 16; o > 0; o >>= 1) v += __shfl_xor_sync(0xffffffffu, v, o);
    return v;
}
__device__ __forceinline__ float quad_sum(float v) { v += __shfl_xor_sync(0xffffffffu, v, 1); return v + __shfl_xor_sync(0xffffffffu, v, 2); }
__device__ __forceinline__ float quad_max(float v) { v = fmaxf(v, __shfl_xor_sync(0xffffffffu, v, 1)); return fmaxf(v, __shfl_xor_sync(0xffffffffu, v, 2)); }
__device__ __forceinline__ uint32_t redux_max(uint32_t v) { uint32_t r; asm volatile("redux.sync.max.u32 %0, %1, 0xffffffff;" : "=r"(r) : "r"(v)); return r; }
__device__ __forceinline__ uint32_t redux_min(uint32_t v) { uint32_t r; asm volatile("redux.sync.min.u32 %0, %1, 0xffffffff;" : "=r"(r) : "r"(v)); return r; }
__device__ __forceinline__ uint32_t order_bits(float r) { const uint32_t u = __float_as_uint(r); return (u & 0x80000000u) ? ~u : (u | 0x80000000u); }
struct Ln2 { uint32_t nm, rh, rl, c; };
__device__ __forceinline__ Ln2 ln2_coef(float mean, float rstd) {
    const uint32_t a = pack_bf16(-mean, rstd), b = pack_bf16((-mean - bf_lo(a)) * rstd, rstd - bf_hi(a));
    return {__byte_perm(a, 0, 0x1010), __byte_perm(a, 0, 0x3232), __byte_perm(b, 0, 0x3232), __byte_perm(b, 0, 0x1010)};
}
__device__ __forceinline__ uint32_t bfma2(uint32_t a, uint32_t b, uint32_t c) { uint32_t r; asm("fma.rn.bf16x2 %0, %1, %2, %3;" : "=r"(r) : "r"(a), "r"(b), "r"(c)); return r; }
__device__ __forceinline__ uint32_t ln2(uint32_t v, const Ln2& k) { const uint32_t d = badd2(v, k.nm); return bfma2(d, k.rh, bfma2(d, k.rl, k.c)); }
__device__ __forceinline__ uint32_t add_ln2(uint32_t v, const Ln2& k) { return badd2(v, ln2(v, k)); }

#define TL(TID, i)
#define CK(TID, i)

__device__ __forceinline__ void wg_gemm_n128(float (&d)[64], uint64_t desca, uint64_t desc) {
    asm volatile("{\n.reg .pred p;\nsetp.ne.b32 p, 1, 0;\n"
        "wgmma.mma_async.sync.aligned.m64n128k16.f32.bf16.bf16 "
        "{%0,%1,%2,%3,%4,%5,%6,%7,%8,%9,%10,%11,%12,%13,%14,%15,%16,%17,%18,%19,%20,%21,%22,%23,%24,%25,%26,%27,%28,%29,%30,%31,%32,%33,%34,%35,%36,%37,%38,%39,%40,%41,%42,%43,%44,%45,%46,%47,%48,%49,%50,%51,%52,%53,%54,%55,%56,%57,%58,%59,%60,%61,%62,%63}, "
        "%64, %65, p, 1, 1, 0, 1;\n}\n"
        : "+f"(d[0]), "+f"(d[1]), "+f"(d[2]), "+f"(d[3]), "+f"(d[4]), "+f"(d[5]), "+f"(d[6]), "+f"(d[7]), "+f"(d[8]), "+f"(d[9]), "+f"(d[10]), "+f"(d[11]),
          "+f"(d[12]), "+f"(d[13]), "+f"(d[14]), "+f"(d[15]), "+f"(d[16]), "+f"(d[17]), "+f"(d[18]), "+f"(d[19]), "+f"(d[20]), "+f"(d[21]), "+f"(d[22]), "+f"(d[23]),
          "+f"(d[24]), "+f"(d[25]), "+f"(d[26]), "+f"(d[27]), "+f"(d[28]), "+f"(d[29]), "+f"(d[30]), "+f"(d[31]), "+f"(d[32]), "+f"(d[33]), "+f"(d[34]), "+f"(d[35]),
          "+f"(d[36]), "+f"(d[37]), "+f"(d[38]), "+f"(d[39]), "+f"(d[40]), "+f"(d[41]), "+f"(d[42]), "+f"(d[43]), "+f"(d[44]), "+f"(d[45]), "+f"(d[46]), "+f"(d[47]),
          "+f"(d[48]), "+f"(d[49]), "+f"(d[50]), "+f"(d[51]), "+f"(d[52]), "+f"(d[53]), "+f"(d[54]), "+f"(d[55]), "+f"(d[56]), "+f"(d[57]), "+f"(d[58]), "+f"(d[59]),
          "+f"(d[60]), "+f"(d[61]), "+f"(d[62]), "+f"(d[63])
        : "l"(desca), "l"(desc));
}
__device__ __forceinline__ void wg_gemm_n192(float (&d)[96], uint64_t desca, uint64_t desc) {
    asm volatile("{\n.reg .pred p;\nsetp.ne.b32 p, 1, 0;\n"
        "wgmma.mma_async.sync.aligned.m64n192k16.f32.bf16.bf16 "
        "{%0,%1,%2,%3,%4,%5,%6,%7,%8,%9,%10,%11,%12,%13,%14,%15,%16,%17,%18,%19,%20,%21,%22,%23,%24,%25,%26,%27,%28,%29,%30,%31,%32,%33,%34,%35,%36,%37,%38,%39,%40,%41,%42,%43,%44,%45,%46,%47,%48,%49,%50,%51,%52,%53,%54,%55,%56,%57,%58,%59,%60,%61,%62,%63,%64,%65,%66,%67,%68,%69,%70,%71,%72,%73,%74,%75,%76,%77,%78,%79,%80,%81,%82,%83,%84,%85,%86,%87,%88,%89,%90,%91,%92,%93,%94,%95}, "
        "%96, %97, p, 1, 1, 0, 1;\n}\n"
        : "+f"(d[0]), "+f"(d[1]), "+f"(d[2]), "+f"(d[3]), "+f"(d[4]), "+f"(d[5]), "+f"(d[6]), "+f"(d[7]), "+f"(d[8]), "+f"(d[9]), "+f"(d[10]), "+f"(d[11]),
          "+f"(d[12]), "+f"(d[13]), "+f"(d[14]), "+f"(d[15]), "+f"(d[16]), "+f"(d[17]), "+f"(d[18]), "+f"(d[19]), "+f"(d[20]), "+f"(d[21]), "+f"(d[22]), "+f"(d[23]),
          "+f"(d[24]), "+f"(d[25]), "+f"(d[26]), "+f"(d[27]), "+f"(d[28]), "+f"(d[29]), "+f"(d[30]), "+f"(d[31]), "+f"(d[32]), "+f"(d[33]), "+f"(d[34]), "+f"(d[35]),
          "+f"(d[36]), "+f"(d[37]), "+f"(d[38]), "+f"(d[39]), "+f"(d[40]), "+f"(d[41]), "+f"(d[42]), "+f"(d[43]), "+f"(d[44]), "+f"(d[45]), "+f"(d[46]), "+f"(d[47]),
          "+f"(d[48]), "+f"(d[49]), "+f"(d[50]), "+f"(d[51]), "+f"(d[52]), "+f"(d[53]), "+f"(d[54]), "+f"(d[55]), "+f"(d[56]), "+f"(d[57]), "+f"(d[58]), "+f"(d[59]),
          "+f"(d[60]), "+f"(d[61]), "+f"(d[62]), "+f"(d[63]), "+f"(d[64]), "+f"(d[65]), "+f"(d[66]), "+f"(d[67]), "+f"(d[68]), "+f"(d[69]), "+f"(d[70]), "+f"(d[71]),
          "+f"(d[72]), "+f"(d[73]), "+f"(d[74]), "+f"(d[75]), "+f"(d[76]), "+f"(d[77]), "+f"(d[78]), "+f"(d[79]), "+f"(d[80]), "+f"(d[81]), "+f"(d[82]), "+f"(d[83]),
          "+f"(d[84]), "+f"(d[85]), "+f"(d[86]), "+f"(d[87]), "+f"(d[88]), "+f"(d[89]), "+f"(d[90]), "+f"(d[91]), "+f"(d[92]), "+f"(d[93]), "+f"(d[94]), "+f"(d[95])
        : "l"(desca), "l"(desc));
}
__device__ __forceinline__ void wg_gemm_n192_init(float (&d)[96], uint64_t desca, uint64_t desc) {
    asm volatile("{\n.reg .pred p;\nsetp.ne.b32 p, 0, 0;\n"
        "wgmma.mma_async.sync.aligned.m64n192k16.f32.bf16.bf16 "
        "{%0,%1,%2,%3,%4,%5,%6,%7,%8,%9,%10,%11,%12,%13,%14,%15,%16,%17,%18,%19,%20,%21,%22,%23,%24,%25,%26,%27,%28,%29,%30,%31,%32,%33,%34,%35,%36,%37,%38,%39,%40,%41,%42,%43,%44,%45,%46,%47,%48,%49,%50,%51,%52,%53,%54,%55,%56,%57,%58,%59,%60,%61,%62,%63,%64,%65,%66,%67,%68,%69,%70,%71,%72,%73,%74,%75,%76,%77,%78,%79,%80,%81,%82,%83,%84,%85,%86,%87,%88,%89,%90,%91,%92,%93,%94,%95}, "
        "%96, %97, p, 1, 1, 0, 1;\n}\n"
        : "=f"(d[0]), "=f"(d[1]), "=f"(d[2]), "=f"(d[3]), "=f"(d[4]), "=f"(d[5]), "=f"(d[6]), "=f"(d[7]), "=f"(d[8]), "=f"(d[9]), "=f"(d[10]), "=f"(d[11]),
          "=f"(d[12]), "=f"(d[13]), "=f"(d[14]), "=f"(d[15]), "=f"(d[16]), "=f"(d[17]), "=f"(d[18]), "=f"(d[19]), "=f"(d[20]), "=f"(d[21]), "=f"(d[22]), "=f"(d[23]),
          "=f"(d[24]), "=f"(d[25]), "=f"(d[26]), "=f"(d[27]), "=f"(d[28]), "=f"(d[29]), "=f"(d[30]), "=f"(d[31]), "=f"(d[32]), "=f"(d[33]), "=f"(d[34]), "=f"(d[35]),
          "=f"(d[36]), "=f"(d[37]), "=f"(d[38]), "=f"(d[39]), "=f"(d[40]), "=f"(d[41]), "=f"(d[42]), "=f"(d[43]), "=f"(d[44]), "=f"(d[45]), "=f"(d[46]), "=f"(d[47]),
          "=f"(d[48]), "=f"(d[49]), "=f"(d[50]), "=f"(d[51]), "=f"(d[52]), "=f"(d[53]), "=f"(d[54]), "=f"(d[55]), "=f"(d[56]), "=f"(d[57]), "=f"(d[58]), "=f"(d[59]),
          "=f"(d[60]), "=f"(d[61]), "=f"(d[62]), "=f"(d[63]), "=f"(d[64]), "=f"(d[65]), "=f"(d[66]), "=f"(d[67]), "=f"(d[68]), "=f"(d[69]), "=f"(d[70]), "=f"(d[71]),
          "=f"(d[72]), "=f"(d[73]), "=f"(d[74]), "=f"(d[75]), "=f"(d[76]), "=f"(d[77]), "=f"(d[78]), "=f"(d[79]), "=f"(d[80]), "=f"(d[81]), "=f"(d[82]), "=f"(d[83]),
          "=f"(d[84]), "=f"(d[85]), "=f"(d[86]), "=f"(d[87]), "=f"(d[88]), "=f"(d[89]), "=f"(d[90]), "=f"(d[91]), "=f"(d[92]), "=f"(d[93]), "=f"(d[94]), "=f"(d[95])
        : "l"(desca), "l"(desc));
}
__device__ __forceinline__ void wg_qk_init(uint32_t (&d)[32], uint32_t a0, uint32_t a1, uint32_t a2, uint32_t a3, uint64_t desc) {
    asm volatile("{\n.reg .pred p;\nsetp.ne.b32 p, 0, 0;\n"
        "wgmma.mma_async.sync.aligned.m64n128k16.f16.f16.f16 "
        "{%0,%1,%2,%3,%4,%5,%6,%7,%8,%9,%10,%11,%12,%13,%14,%15,%16,%17,%18,%19,%20,%21,%22,%23,%24,%25,%26,%27,%28,%29,%30,%31}, "
        "{%32,%33,%34,%35}, %36, p, 1, 1, 0;\n}\n"
        : "=r"(d[0]), "=r"(d[1]), "=r"(d[2]), "=r"(d[3]), "=r"(d[4]), "=r"(d[5]), "=r"(d[6]), "=r"(d[7]), "=r"(d[8]), "=r"(d[9]), "=r"(d[10]), "=r"(d[11]),
          "=r"(d[12]), "=r"(d[13]), "=r"(d[14]), "=r"(d[15]), "=r"(d[16]), "=r"(d[17]), "=r"(d[18]), "=r"(d[19]), "=r"(d[20]), "=r"(d[21]), "=r"(d[22]), "=r"(d[23]),
          "=r"(d[24]), "=r"(d[25]), "=r"(d[26]), "=r"(d[27]), "=r"(d[28]), "=r"(d[29]), "=r"(d[30]), "=r"(d[31])
        : "r"(a0), "r"(a1), "r"(a2), "r"(a3), "l"(desc));
}
__device__ __forceinline__ void wg_qk_acc(uint32_t (&d)[32], uint32_t a0, uint32_t a1, uint32_t a2, uint32_t a3, uint64_t desc) {
    asm volatile("{\n.reg .pred p;\nsetp.ne.b32 p, 1, 0;\n"
        "wgmma.mma_async.sync.aligned.m64n128k16.f16.f16.f16 "
        "{%0,%1,%2,%3,%4,%5,%6,%7,%8,%9,%10,%11,%12,%13,%14,%15,%16,%17,%18,%19,%20,%21,%22,%23,%24,%25,%26,%27,%28,%29,%30,%31}, "
        "{%32,%33,%34,%35}, %36, p, 1, 1, 0;\n}\n"
        : "+r"(d[0]), "+r"(d[1]), "+r"(d[2]), "+r"(d[3]), "+r"(d[4]), "+r"(d[5]), "+r"(d[6]), "+r"(d[7]), "+r"(d[8]), "+r"(d[9]), "+r"(d[10]), "+r"(d[11]),
          "+r"(d[12]), "+r"(d[13]), "+r"(d[14]), "+r"(d[15]), "+r"(d[16]), "+r"(d[17]), "+r"(d[18]), "+r"(d[19]), "+r"(d[20]), "+r"(d[21]), "+r"(d[22]), "+r"(d[23]),
          "+r"(d[24]), "+r"(d[25]), "+r"(d[26]), "+r"(d[27]), "+r"(d[28]), "+r"(d[29]), "+r"(d[30]), "+r"(d[31])
        : "r"(a0), "r"(a1), "r"(a2), "r"(a3), "l"(desc));
}
__device__ __forceinline__ void wg_pv_init(uint32_t (&d)[10], uint32_t a0, uint32_t a1, uint32_t a2, uint32_t a3, uint64_t desc) {
    asm volatile("{\n.reg .pred p;\nsetp.ne.b32 p, 0, 0;\n"
        "wgmma.mma_async.sync.aligned.m64n40k16.f16.f16.f16 "
        "{%0,%1,%2,%3,%4,%5,%6,%7,%8,%9}, "
        "{%10,%11,%12,%13}, %14, p, 1, 1, 1;\n}\n"
        : "=r"(d[0]), "=r"(d[1]), "=r"(d[2]), "=r"(d[3]), "=r"(d[4]), "=r"(d[5]), "=r"(d[6]), "=r"(d[7]), "=r"(d[8]), "=r"(d[9])
        : "r"(a0), "r"(a1), "r"(a2), "r"(a3), "l"(desc));
}
__device__ __forceinline__ void wg_pv_acc(uint32_t (&d)[10], uint32_t a0, uint32_t a1, uint32_t a2, uint32_t a3, uint64_t desc) {
    asm volatile("{\n.reg .pred p;\nsetp.ne.b32 p, 1, 0;\n"
        "wgmma.mma_async.sync.aligned.m64n40k16.f16.f16.f16 "
        "{%0,%1,%2,%3,%4,%5,%6,%7,%8,%9}, "
        "{%10,%11,%12,%13}, %14, p, 1, 1, 1;\n}\n"
        : "+r"(d[0]), "+r"(d[1]), "+r"(d[2]), "+r"(d[3]), "+r"(d[4]), "+r"(d[5]), "+r"(d[6]), "+r"(d[7]), "+r"(d[8]), "+r"(d[9])
        : "r"(a0), "r"(a1), "r"(a2), "r"(a3), "l"(desc));
}

constexpr uint32_t SB = SMEM_BASE;
constexpr uint32_t R_SLOT = 18432, A_RING = SB, A_KP = SB + 73728, A_QX = SB + 81920, A_STB = SB + 98304;
constexpr uint32_t F_GU0 = SB + 98304, F_GU1 = SB + 163840, F_WD = F_GU0;
__host__ __device__ constexpr uint32_t o_a(uint32_t s) { return s == 0 ? SB : s == 1 ? A_QX : F_GU0 + (s - 2) * 32768; }
__host__ __device__ constexpr uint32_t o_b(uint32_t s) { return s < 2 ? SB + 16384 + s * 16384 : F_GU0 + 16384 + (s - 2) * 32768; }
constexpr uint32_t XT0 = SB + 49152, XT1 = XT0 + 16384, YT0 = o_a(0), YT1 = o_a(1);
constexpr uint32_t Q_ABYTES = 256 * 64 * 2, Q_STB = Q_ABYTES + 192 * 64 * 2;
constexpr uint32_t Q_CS = SB + 3 * Q_STB, Q_RC = Q_CS + 768, Q_FIX = Q_RC + 2048;
constexpr uint32_t SD_VEC = SB + 176128, SD_W = SB + 180224;
static_assert(Q_FIX + 768 <= SD_VEC, "smem");
constexpr uint32_t M_RED = SB + 229376, M_BAR = M_RED + 2048, BAR_SET = 336, M_HS = M_BAR + 2 * BAR_SET, M_SM = M_HS + 128;
constexpr uint32_t M_IV = M_SM;
constexpr uint32_t M_WS = M_SM + 16;
constexpr uint32_t M_CR = M_SM + 20;
constexpr uint32_t M_SS = M_SM + 24;
constexpr uint32_t M_RT = M_SM + 32;
constexpr uint32_t M_SR = M_SM + 96;
constexpr int K_SMEM = M_SR + 128 - SB;
static_assert(K_SMEM == 232448, "smem");
constexpr uint32_t B_QF = 0, B_AF = 24, B_OF = 56, B_RES = 88, B_GU = 96, B_WD = 104, B_RT = 112, B_SW = 120, B_ONE = 128, B_XD = 136, B_QE = 144, B_OE = 168,
                   B_PX = 200, B_AE = 224, B_OD = 256, B_FG = 288, B_FD = 296, B_XS = 304, B_KS = 312, B_K0 = 320, B_END = 328;
constexpr int NB_ML = 1, NB_CONS = 2, NB_SIDE = 3, NB_EPI = 4, NB_WG = 6;

__device__ __forceinline__ int mt_of(int c) { return (c >> 2) & 7; }
__device__ __forceinline__ int nt_of(int c) { return (c >> 5) * 4 + (c & 3); }
__device__ __forceinline__ int blk_of(int c) { return c >> 3; }
__device__ __forceinline__ int cb_of(int c) { return c & 7; }

struct Maps { CUtensorMap x[2], wqkv, o, wo[2], r, g, u, d; };

template <int N>
__device__ __forceinline__ void halve(float (&v)[8], int lane, int bit) {
    const bool up = lane & bit;
    #pragma unroll
    for (int i = 0; i < N; i++) v[i] = (up ? v[N + i] : v[i]) + __shfl_xor_sync(0xffffffffu, up ? v[i] : v[N + i], bit);
}

__device__ __forceinline__ void reset_exchange(int c, int t) {
    #pragma unroll 1
    for (int i = t; i < FILL; i += 96) g_u.fill[c][i] = make_uint4(EMPTY, EMPTY, EMPTY, EMPTY);
}
__device__ __forceinline__ void prep_work(const bf16* __restrict__ x0, const bf16* __restrict__ w_r, uint32_t lb) {
    const int t = tid_now() - 288, c = cta_now(), lane = t & 31, warp = warp_uniform(t >> 5);
    const uint32_t wb = SD_W + warp * 8192;
    mbar_nap(lb + B_SW, 0);
    {
        float cs[8], cq[8];
        #pragma unroll
        for (int i = 0; i < 8; i++) { cs[i] = 0.f; cq[i] = 0.f; }
        #pragma unroll 1
        for (int h = 0; h < 2; h++) {
            #pragma unroll 2
            for (int r = 0; r < 16; r++) {
                const uint4 u = lds128(wb + h * 24576 + (lane >> 3) * 128 + r * 512 + (((lane & 7) ^ ((r * 4 + (lane >> 3)) & 7)) << 4));
                const uint32_t w[4] = {u.x, u.y, u.z, u.w};
                #pragma unroll
                for (int e = 0; e < 4; e++) {
                    const float a = bf_lo(w[e]), b = bf_hi(w[e]);
                    cs[2*e] += a; cs[2*e+1] += b; cq[2*e] = fmaf(a, a, cq[2*e]); cq[2*e+1] = fmaf(b, b, cq[2*e+1]);
                }
            }
            fence_async_smem();
            __syncwarp();
            if (elect_one()) {
                const uint32_t bytes = h == 0 ? 8192 : warp < 2 ? 4096 : 2048;
                mbar_expect_tx(lb + B_PX + warp * 8, bytes);
                bulk_load(wb + h * 24576, h && warp == 2 ? w_r : x0 + (size_t)(c * 16 + (h ? 12 + warp * 2 : warp * 4)) * D_, bytes, lb + B_PX + warp * 8);
            }
            __syncwarp();
        }
        halve<4>(cs, lane, 16); halve<2>(cs, lane, 8);
        halve<4>(cq, lane, 16); halve<2>(cq, lane, 8);
        *reinterpret_cast<float4*>(&g_cs[mt_of(c)][warp * D_ + nt_of(c) * 64 + (lane & 7) * 8 + (lane >> 3) * 2]) = make_float4(cs[0], cq[0], cs[1], cq[1]);
    }
    TL(288, 22);
    reset_exchange(c, t);
    mbar_nap(lb + B_PX + warp * 8, 0);
    #pragma unroll 1
    for (int i = 0; i < (warp < 2 ? 6 : 5); i++) {
        const int r = i < 4 ? warp * 4 + i : 8 + warp * 2 + i;
        float s0 = 0.f, s1 = 0.f, q0 = 0.f, q1 = 0.f;
        #pragma unroll 2
        for (int j = 0; j < 4; j++) {
            const uint4 u = lds128(wb + (i >> 2) * 16384 + i * 2048 + j * 512 + lane * 16);
            const uint32_t w[4] = {u.x, u.y, u.z, u.w};
            #pragma unroll
            for (int e = 0; e < 4; e++) { const float a = bf_lo(w[e]), b = bf_hi(w[e]); s0 += a; s1 += b; q0 = fmaf(a, a, q0); q1 = fmaf(b, b, q1); }
        }
        s0 += s1; q0 += q1;
        float v = (lane & 16 ? q0 : s0) + __shfl_xor_sync(0xffffffffu, lane & 16 ? s0 : q0, 16);
        #pragma unroll
        for (int o = 8; o > 0; o >>= 1) v += __shfl_xor_sync(0xffffffffu, v, o);
        const float mean = v * (1.f / D_), sq = __shfl_xor_sync(0xffffffffu, mean, 16);
        if (lane == 0) {
            if (r < 16) g_rs0[c * 16 + r] = make_float2(fmaxf(sq - mean * mean, 0.f), mean);
            else stsf(M_WS, v);
        }
    }
    named_sync(NB_SIDE, 96);
    if (t == 0) { TL(288, 23); ctr_arrive(&g_pctr); ctr_wait(&g_pctr, 128); TL(288, 24); }
    named_sync(NB_SIDE, 96);
}

constexpr float TCOMP = 1.00245f;
__device__ __forceinline__ int half_exp(uint32_t bits, int off) { return min(max((((int)(bits >> 23) - 125) >> 1) + off, -55), 55); }
__device__ __forceinline__ float pow2(int e) { return __uint_as_float((uint32_t)(127 + e) << 23); }
__device__ __forceinline__ void head_scales(int h) {
    const float fq = ldsf(M_SR + h * 4), fk = ldsf(M_SR + 8 + h * 4);
    const uint32_t vmax = lds32(M_SR + 16 + h * 4), vmin = lds32(M_SR + 24 + h * 4);
    const bool ok = fq <= 1024.f && fk <= 1024.f && fq * fk <= 50000.f && vmax <= vmin + (12u << 23);
    const int a = ok ? 0 : half_exp(__float_as_uint(fq), -8), b = ok ? 0 : half_exp(__float_as_uint(fk), -8), v = half_exp(vmax, ok ? 3 : -10);
    stsf(M_HS + h * 4, TCOMP * QSCALE * pow2(-a)); stsf(M_HS + 8 + h * 4, TCOMP * pow2(-b)); stsf(M_HS + 16 + h * 4, TCOMP * pow2(-v));
    stsf(M_SS + h * 4, ok ? 0.f : pow2(a + b));
    stsf(M_IV + h * 4, pow2(v - 4));
}

__device__ __forceinline__ void epi_inputs(int L, const bf16* __restrict__ w_r) {
    const int t = tid_now() - 288, c = cta_now(), mt = mt_of(c), nt = nt_of(c), lane = t & 31;
    const uint32_t wr = t < 64 ? __ldg(reinterpret_cast<const uint32_t*>(w_r) + cb_of(c) * 64 + t) : 0x3F803F80u;
    #pragma unroll 1
    for (int k = 0; k < 3; k++) {
        const int i = t + 96 * k, col = (i >> 6) * D_ + nt * 64 + (i & 63);
        const float2* rsp = (L ? g_x.rs1 : g_rs0) + mt * 256 + (i & 255);
        uint2 sv = ld_x64(rsp);
        if (k < 2) {
            float2 p[8];
            #pragma unroll
            for (int j = 0; j < 8; j++) p[j] = __ldcg(&g_cs[j][col]);
            stsf(Q_CS + i * 4, ((p[0].x + p[1].x) + (p[2].x + p[3].x)) + ((p[4].x + p[5].x) + (p[6].x + p[7].x)));
            const float zz = ((p[0].y + p[1].y) + (p[2].y + p[3].y)) + ((p[4].y + p[5].y) + (p[6].y + p[7].y));
            const float zs = warp_sum(zz);
            const uint32_t zb = __float_as_uint(zz), zmax = redux_max(zb), zmin = redux_min(zb ? zb : 0x7F800000u);
            if (lane == 0) {
                sts32(M_SR + (i >> 5) * 4, i < 128 ? __float_as_uint(zs) : zmax);
                if (i >= 128) sts32(M_SR + 8 + (i >> 5) * 4, zmin);
            }
        } else {
            named_sync(NB_SIDE, 96);
            if (t < 2) head_scales(t);
            __syncwarp();
        }
        uint32_t n = 0;
        #pragma unroll 1
        while (warp_any(sv.x == EMPTY)) { sv = ld_x64(rsp); poll_tick(n); }
        const float var = __uint_as_float(sv.x), a = L ? 1.f + rsq(var + LN_EPS) : 1.f;
        sts64(Q_RC + (i & 255) * 8, __float_as_uint(a * rsq(a * a * var + LN_EPS)), sv.y ^ 0x80000000u);
    }
    if (t < 68) sts32(M_RED + t * 4, wr);
}

__device__ __forceinline__ void ffn_finish(int L, bf16* __restrict__ out) {
    const int t = tid_now() - 288, c = cta_now(), lane = t & 31, warp = warp_uniform(t >> 5);
    TL(288, L * 32 + 29);
    const uint4 rv = lds128(M_RT + 16 * L);
    const int idx = (int)rv.w;
    const uint32_t* xsrc = &g_x.cand[L][idx >> 7][(c >> 2) * 16 + (t & 3) * 4 + (c & 3)];
    const uint8_t* fsrc = &g_x.x[idx >> 8][((idx >> 7) & 1) * 8 + (c >> 4)];
    uint32_t xw, busy;
    const float sg = sigmoid(bf_round(__uint_as_float(rv.x)));
    uint32_t rsel = pack_bf16(sg, sg);
    Ln2 kx = ln2_coef(__uint_as_float(rv.y), __uint_as_float(rv.z));
    uint32_t* dst = reinterpret_cast<uint32_t*>(L ? out : g_x1) + idx * (D_ / 2) + c * 4 + t;
    asm volatile("" : "+r"(rsel), "+r"(kx.nm), "+r"(kx.rh), "+r"(kx.rl), "+r"(kx.c), "+l"(dst));
    float a[8] = {0.f, 0.f, 0.f, 0.f};
    {
        const float* src = &g_x.ypart[L][c][0][t * 4];
        uint4 v[3];
        uint32_t n = 0;
        #pragma unroll 1
        do {
            v[0] = ld_x128(src); v[1] = ld_x128(src + 384);
            v[2] = make_uint4(0u, 0u, 0u, 0u);
            xw = 0u; busy = 0u;
            if (warp == 0) {
                v[2] = ld_x128(src + 768); xw = ld_x32(xsrc);
                asm volatile("ld.relaxed.gpu.global.u8 %0, [%1];" : "=r"(busy) : "l"(fsrc) : "memory");
            }
            poll_tick(n);
        } while (warp_any(any_empty(v[0]) || any_empty(v[1]) || any_empty(v[2]) || xw == EMPTY || busy != 0));
        TL(288, L * 32 + 30); TL(352, L * 32 + 31);
        #pragma unroll
        for (int i = 0; i < 3; i++) { a[0] += __uint_as_float(v[i].x); a[1] += __uint_as_float(v[i].y); a[2] += __uint_as_float(v[i].z); a[3] += __uint_as_float(v[i].w); }
    }
    halve<2>(a, lane, 2); halve<1>(a, lane, 4);
    a[0] += __shfl_xor_sync(0xffffffffu, a[0], 8); a[0] += __shfl_xor_sync(0xffffffffu, a[0], 16);
    if (lane < 8) stsf(M_SR + warp * 32 + ((lane & 1) * 4 + (lane & 2) + (lane >> 2)) * 4, a[0]);
    const uint32_t xn = ln2(xw, kx);
    named_sync(NB_SIDE, 96);
    if (t < 4) {
        const float2 y0 = lds64f(M_SR + t * 8), y1 = lds64f(M_SR + 32 + t * 8), y2 = lds64f(M_SR + 64 + t * 8);
        const uint32_t y = pack_bf16(y0.x + y1.x + y2.x, y0.y + y1.y + y2.y);
        const uint32_t res = badd2(xw, badd2(xn, bmul2(y, rsel)));
        *dst = res;
        if (L == 0) st_x32(&g_x.x2row[c * 4 + t], res);
    }
}

__device__ __forceinline__ void fix_row(uint32_t lb) {
    const int t = tid_now() - 288, c = cta_now(), lane = t & 31, warp = warp_uniform(t >> 5);
    uint4 v[2];
    {
        uint32_t n = 0;
        #pragma unroll 1
        do {
            v[0] = ld_x128(g_x.x2row + t * 4);
            v[1] = make_uint4(0u, 0u, 0u, 0u);
            if (warp == 0) v[1] = ld_x128(g_x.x2row + (96 + t) * 4);
            poll_tick(n);
        } while (warp_any(any_empty(v[0]) || any_empty(v[1])));
    }
    const uint32_t w[8] = {v[0].x, v[0].y, v[0].z, v[0].w, v[1].x, v[1].y, v[1].z, v[1].w};
    float su = 0.f, sq = 0.f;
    #pragma unroll
    for (int i = 0; i < 8; i++) { const float a = bf_lo(w[i]), b = bf_hi(w[i]); su += a + b; sq = fmaf(a, a, fmaf(b, b, sq)); }
    su = warp_sum(su); sq = warp_sum(sq);
    if (lane == 0) sts64(M_SR + 96 + warp * 8, __float_as_uint(su), __float_as_uint(sq));
    named_sync(NB_SIDE, 96);
    const float2 s0 = lds64f(M_SR + 96), s1 = lds64f(M_SR + 104), s2 = lds64f(M_SR + 112);
    const float mean = (s0.x + s1.x + s2.x) * (1.f / D_);
    const float rstd = rsq(fmaxf((s0.y + s1.y + s2.y) * (1.f / D_) - mean * mean, 0.f) + LN_EPS);
    const Ln2 k = ln2_coef(mean, rstd);
    #pragma unroll
    for (int i = 0; i < 2; i++)
        if (i == 0 || warp == 0) sts128(SD_VEC + (t + 96 * i) * 16, ln2(w[4*i], k), ln2(w[4*i+1], k), ln2(w[4*i+2], k), ln2(w[4*i+3], k));
    named_sync(NB_SIDE, 96);
    TL(288, 32 + 22);
    mbar_nap(lb + B_SW, 0);
    float a[8];
    #pragma unroll
    for (int i = 0; i < 8; i++) a[i] = 0.f;
    const uint32_t xa = base32(SD_VEC + lane * 2), wa = base32(SD_W + lane * 48 + warp * 16);
    #pragma unroll 2
    for (int b = 0; b < 32; b++) {
        const float x = bf_lo(lds16(xa + b * 64));
        const uint4 u = lds128(wa + b * 1536);
        a[0] = fmaf(x, bf_lo(u.x), a[0]); a[1] = fmaf(x, bf_hi(u.x), a[1]); a[2] = fmaf(x, bf_lo(u.y), a[2]); a[3] = fmaf(x, bf_hi(u.y), a[3]);
        a[4] = fmaf(x, bf_lo(u.z), a[4]); a[5] = fmaf(x, bf_hi(u.z), a[5]); a[6] = fmaf(x, bf_lo(u.w), a[6]); a[7] = fmaf(x, bf_hi(u.w), a[7]);
    }
    halve<4>(a, lane, 16); halve<2>(a, lane, 8); halve<1>(a, lane, 4);
    a[0] = quad_sum(a[0]);
    if ((lane & 3) == 0) st_x32(&g_x.fix[c * 24 + warp * 8 + (lane >> 2)], __float_as_uint(a[0]));
    TL(288, 32 + 23);
    if (((int)lds32(M_RT + 12) >> 8) == mt_of(c)) {
        const float* src = &g_x.fix[(t >> 5) * D_ + nt_of(c) * 64 + (t & 31) * 2];
        uint2 f;
        uint32_t n = 0;
        #pragma unroll 1
        do { f = ld_x64(src); poll_tick(n); } while (warp_any(f.x == EMPTY || f.y == EMPTY));
        sts64(Q_FIX + t * 8, f.x, f.y);
    }
}

__device__ __forceinline__ void out_piece(bf16* __restrict__ out, int r, int ch, bool on) {
    const uint4 v = lds128(((ch & 8) ? YT1 : YT0) + r * 128 + (((ch ^ r) & 7) << 4)), kk = lds128(XT0 + r * 16);
    const Ln2 k = {kk.x, kk.y, kk.z, kk.w};
    const int c = blockIdx.x;
    stg128_pred(out + (blk_of(c) * 128 + r) * D_ + cb_of(c) * 128 + ch * 8, make_uint4(add_ln2(v.x, k), add_ln2(v.y, k), add_ln2(v.z, k), add_ln2(v.w, k)), on);
}
__device__ __forceinline__ void publish(uint8_t* f) {
    bulk_commit();
    bulk_wait();
    fence_async_global();
    asm volatile("st.release.gpu.global.u8 [%0], 0;" :: "l"(f) : "memory");
}
__device__ __forceinline__ void side_role(const Maps& mp, const bf16* __restrict__ x0, const bf16* __restrict__ wo, const bf16* __restrict__ w_down, const bf16* __restrict__ w_r, bf16* __restrict__ out) {
    #pragma unroll 1
    for (int L = 0; L < 2; L++) {
        const uint32_t lb = M_BAR + L * BAR_SET;
        if (L == 0) prep_work(x0, w_r, lb);
        else fix_row(lb);
        epi_inputs(L, w_r);
        const int t = tid_now() - 288, c = cta_now(), mt = mt_of(c), nt = nt_of(c), warp = warp_uniform(t >> 5);
        TL(288, L * 32 + 4);
        named_arrive(NB_EPI, 224);
        named_arrive(NB_EPI + 1, 224);
        if (warp == 0) {
            named_sync(NB_ML, 288);
            #pragma unroll
            for (int i = 0; i < 16; i++) sts128(base32(A_RING + 16384 + t * 16) + (i >> 2) * R_SLOT + (i & 3) * 512, 0x2C002C00u, 0x2C002C00u, 0x2C002C00u, 0x2C002C00u);
            fence_async_smem();
            __syncwarp();
            mbar_arrive_elect(lb + B_ONE);
        }
        if (elect_one()) {
            #pragma unroll 1
            for (int n = warp - 1; n >= 0 && n < 3 * warp - 2; n++) {
                char* dst = g_kv + (size_t)(nt * 2 + (n >> 1)) * 16 * KV_TILE;
                if (n < 3) mbar_nap(lb + (n == 0 ? B_K0 : n == 1 ? B_KS : B_AE + 16), 0);
                bulk_store(dst + ((2 * mt - 1 + (n & 1)) & 15) * KV_TILE, n == 0 ? A_KP : n == 1 ? A_RING : A_STB + (n - 2) * 8192, 8192 << (n & 1));
                if (n & 1) bulk_store(dst + 2 * mt * KV_TILE + 24576, n == 1 ? A_RING + R_SLOT + 8192 : A_STB + 24576, 8192);
                publish(&g_x.kv[L][nt * 2 + (n >> 1)][2 * mt + (n & 1)]);
                if (n == 1) TL(352, L * 32 + 6);
                if (n == 0) TL(320, L * 32 + 27);
            }
            if (warp == 2) {
                const bool ffn = c < NFC;
                const uint64_t pol = policy_evict_first();
                mbar_expect_tx(lb + B_GU, ffn ? 131072 : 0);
                mbar_expect_tx(lb + B_WD, ffn ? 65536 : 0);
                l2_prefetch(reinterpret_cast<const char*>(wo) + (size_t)c * 16384, 16384);
                if (ffn) {
                    #pragma unroll 1
                    for (int i = 0; i < 12; i++) {
                        if (i < 8) tma_load_s(F_GU0 + i * 16384, (i & 1) ? &mp.u : &mp.g, c * 32, (i >> 1) * 256, lb + B_GU, pol);
                        else l2_prefetch(reinterpret_cast<const char*>(w_down) + (size_t)c * 65536 + (i - 8) * 16384, 16384);
                        __nanosleep(900);
                    }
                }
                mbar_nap(lb + B_OD, 0);
                __nanosleep(1000);
                l2_prefetch(g_u.fill[c], sizeof(g_u.fill[0]));
                if (L == 0) {
                    mbar_nap(lb + B_XS, 0);
                    tma_store(&mp.x[1], YT0, cb_of(c) * 128, blk_of(c) * 128);
                    tma_store(&mp.x[1], YT1, cb_of(c) * 128 + 64, blk_of(c) * 128);
                    publish(&g_x.x[blk_of(c) >> 1][(blk_of(c) & 1) * 8 + cb_of(c)]);
                    mbar_arrive(lb + B_XD);
                    TL(352, 18);
                }
            } else {
                #pragma unroll 1
                for (int p = 0; p < 2; p++) { mbar_sleep(lb + B_OD + (p * 2 + warp) * 8, 0); ctr_arrive(g_x.o[L][mt * 2 + warp][p]); TL(288, L * 32 + 19); }
            }
        }
        __syncwarp();
        if (L) {
            mbar_sleep(lb + B_XS, 0);
            const int cand = (int)lds32(M_CR) & 127;
            #pragma unroll 2
            for (int r = t >> 4; r < 132; r += 6) out_piece(out, r & 127, t & 15, r < 128 && r != cand);
            TL(288, 32 + 18);
            mbar_sleep(lb + B_RT, 0);
            out_piece(out, cand, t & 15, t < 16 && lds32(M_CR) != lds32(M_RT + 28));
        }
        const uint32_t late = mbar_test(lb + B_FD, 0);
        mbar_sleep(lb + B_FD, 0);
        __nanosleep(late ? 50 : 400);
        if (c == 0 && t == 0 && L == 0) g_pctr = 0;
        ffn_finish(L, out);
        TL(288, L * 32 + 20);
    }
}

struct Cols { float2 c[4]; float hs; };
template <int HH>
__device__ __forceinline__ void load_cols(Cols& k, uint32_t cs) {
    #pragma unroll
    for (int jj = 0; jj < 4; jj++) k.c[jj] = lds64f(cs + (HH * 32 + jj * 8) * 4);
    k.hs = ldsf(M_HS + HH * 4);
}
template <int HH>
__device__ __forceinline__ void qkv_epi_head(const float (&acc0)[96], const float (&acc1)[96], const float (&cf)[4], const float (&nm)[4], const Cols& k, uint32_t (&pk)[4][4]) {
    #pragma unroll
    for (int jj = 0; jj < 4; jj++) {
        #pragma unroll
        for (int i = 0; i < 4; i++) {
            const float* a = (i >> 1) ? acc1 : acc0;
            const float sc = cf[i] * k.hs;
            const float x = fmaf(nm[i], k.c[jj].x, a[4 * (4 * HH + jj) + 2 * (i & 1)]) * sc;
            const float y = fmaf(nm[i], k.c[jj].y, a[4 * (4 * HH + jj) + 2 * (i & 1) + 1]) * sc;
            pk[i][jj] = pack_f16(x, y) & 0xFFF8FFF8u;
        }
    }
}
__device__ __forceinline__ void stage_kv(uint32_t dst, const uint32_t (&pk)[4][4]) {
    #pragma unroll
    for (int i = 0; i < 4; i++) stsm4(dst + (i >> 1) * 1024 + (i & 1) * 128, pk[i][0], pk[i][1], pk[i][2], pk[i][3]);
}
template <int OFF>
__device__ __forceinline__ void patch_row(float (&acc)[96], uint32_t fx) {
    #pragma unroll
    for (int j = 0; j < 24; j++) { const float2 f = lds64f(fx + j * 32); acc[4 * j + OFF] = f.x; acc[4 * j + OFF + 1] = f.y; }
}
template <bool INIT>
__device__ __forceinline__ void qkv_step(float (&acc0)[96], float (&acc1)[96], uint64_t da, uint64_t db) {
    wg_fence();
    #pragma unroll
    for (int kk = 0; kk < 4; kk++) {
        if (INIT && kk == 0) { wg_gemm_n192_init(acc0, da, db); wg_gemm_n192_init(acc1, da + (8192 >> 4), db); }
        else { wg_gemm_n192(acc0, da + kk * 2, db + kk * 128); wg_gemm_n192(acc1, da + (8192 >> 4) + kk * 2, db + kk * 128); }
    }
    wg_commit();
}
__device__ __forceinline__ void qkv_phase(int L, uint32_t lb, int wg, uint32_t (&qa)[8], uint32_t (&qb)[8], uint32_t (&SA)[32], uint32_t (&SB_)[32]) {
    float acc0[96], acc1[96];
    {
        const bool leader = (tid_now() & 127) == 0;
        const uint64_t da0 = opaque(desc_sw128(SB + wg * 16384, 16, 1024)), db0 = opaque(desc_sw128(SB + Q_ABYTES, 8192, 1024));
        mbar_spin(lb + B_QF, 0);
        TL(0, L * 32 + 1); CK(0, L * 32 + 10);
        qkv_step<true>(acc0, acc1, da0, db0);
        uint32_t st = 1, ph = 0;
        #pragma unroll 1
        for (int k = 1; k < 16; k++) {
            mbar_spin(lb + B_QF + 8 * st, ph);
            if (k == 14 && wg) named_sync(NB_CONS, 256);
            qkv_step<false>(acc0, acc1, da0 + st * (Q_STB >> 4), db0 + st * (Q_STB >> 4));
            if (k == 15 && !wg) named_arrive(NB_CONS, 256);
            wg_wait<1>();
            if (leader) mbar_arrive(lb + B_QE + 8 * (st == 0 ? 2 : st - 1));
            if (++st == 3) { st = 0; ph ^= 1; }
        }
    }
    named_sync(NB_EPI + wg, 224);
    const int tid = tid_now(), lane = tid & 31, w = (tid >> 5) & 3, g = lane >> 2, t = lane & 3;
    const int lr0 = wg * 128 + w * 16 + g;
    float cf[4], nm[4];
    #pragma unroll
    for (int i = 0; i < 4; i++) { const float2 r = lds64f(base32(Q_RC + lr0 * 8) + ((i >> 1) * 64 + (i & 1) * 8) * 8); cf[i] = r.x; nm[i] = r.y; }
    const uint32_t cs = base32(Q_CS + t * 8);
    const int d = L ? (int)lds32(M_RT + 12) - (mt_of(cta_now()) * 256 + lr0) : -1;
    const uint32_t ko = base32((lane >> 3) * 2048 + (w * 16 + (lane & 7)) * 16);
    Cols k0, k1;
    load_cols<2>(k0, cs);
    wg_wait<0>();
    pin(acc0); pin(acc1);
    TL(128, L * 32 + 2); CK(128, L * 32 + 11);
    named_arrive(NB_ML, 288);
    if ((tid & 127) == 0) mbar_arrive(lb + B_QE);
    if (__builtin_expect((d & ~72) == 0, 0)) {
        if (d == 0) { patch_row<0>(acc0, cs + (Q_FIX - Q_CS)); cf[0] = 1.f; nm[0] = 0.f; }
        else if (d == 8) { patch_row<2>(acc0, cs + (Q_FIX - Q_CS)); cf[1] = 1.f; nm[1] = 0.f; }
        else if (d == 64) { patch_row<0>(acc1, cs + (Q_FIX - Q_CS)); cf[2] = 1.f; nm[2] = 0.f; }
        else { patch_row<2>(acc1, cs + (Q_FIX - Q_CS)); cf[3] = 1.f; nm[3] = 0.f; }
    }
    __syncwarp();
    uint32_t pk[4][4];
    qkv_epi_head<2>(acc0, acc1, cf, nm, k0, pk);
    load_cols<4>(k1, cs);
    mbar_spin(lb + B_QE + 8 - 8 * wg, wg);
    stage_kv((wg ? A_RING : A_KP) + ko, pk);
    if (!wg) {
        fence_async_smem();
        __syncwarp();
        mbar_arrive_elect(lb + B_K0);
    }
    qkv_epi_head<4>(acc0, acc1, cf, nm, k1, pk);
    load_cols<3>(k0, cs);
    stage_kv(A_RING + wg * R_SLOT + 8192 + ko, pk);
    fence_async_smem();
    __syncwarp();
    mbar_arrive_elect(lb + B_KS);
    qkv_epi_head<3>(acc0, acc1, cf, nm, k0, pk);
    load_cols<0>(k1, cs);
    load_cols<5>(k0, cs);
    stage_kv(A_STB + wg * 8192 + ko, pk);
    qkv_epi_head<0>(acc0, acc1, cf, nm, k1, pk);
    #pragma unroll
    for (int s = 0; s < 2; s++) {
        qa[4*s] = pk[0][2*s]; qa[4*s+1] = pk[1][2*s]; qa[4*s+2] = pk[0][2*s+1]; qa[4*s+3] = pk[1][2*s+1];
        qb[4*s] = pk[2][2*s]; qb[4*s+1] = pk[3][2*s]; qb[4*s+2] = pk[2][2*s+1]; qb[4*s+3] = pk[3][2*s+1];
    }
    mbar_spin(lb + B_K0, 0);
    {
        constexpr uint64_t dk = desc_plain(A_KP, 2048, 128);
        wg_fence();
        wg_qk_init(SA, qa[0], qa[1], qa[2], qa[3], dk);
        wg_qk_acc(SA, qa[4], qa[5], qa[6], qa[7], dk + 256);
        wg_qk_init(SB_, qb[0], qb[1], qb[2], qb[3], dk);
        wg_qk_acc(SB_, qb[4], qb[5], qb[6], qb[7], dk + 256);
        wg_commit();
    }
    qkv_epi_head<5>(acc0, acc1, cf, nm, k0, pk);
    load_cols<1>(k1, cs);
    stage_kv(A_STB + 16384 + wg * 8192 + ko, pk);
    qkv_epi_head<1>(acc0, acc1, cf, nm, k1, pk);
    #pragma unroll
    for (int u = 0; u < 2; u++)
        #pragma unroll
        for (int s = 0; s < 2; s++) sts128(A_QX + (u * 2 + s) * 4096 + tid * 16, pk[2*u][2*s], pk[2*u+1][2*s], pk[2*u][2*s+1], pk[2*u+1][2*s+1]);
    fence_async_smem();
    wg_wait<0>();
    pin(SA); pin(SB_);
    TL(128, L * 32 + 5); CK(128, L * 32 + 12);
}

#define PMASK 0x00005555u
#define IMASK 0x20202020u
__host__ __device__ constexpr bool is_poly(int j) { return !((PMASK >> j) & 1); }
#define TBIAS 0x5DEB5DEBu
struct Shift { uint32_t f0, f1, n0, n1, bad; };

__device__ __forceinline__ uint32_t exp2_mufu(uint32_t s, uint32_t nm) {
    uint32_t r;
    asm("ex2.approx.f16x2 %0, %1;" : "=r"(r) : "r"(hadd2(s, nm)));
    return r;
}
__device__ __forceinline__ uint32_t exp2_fix(uint32_t s, uint32_t fm, uint32_t ca, uint32_t& U, bool mul, uint32_t sixteen) {
    uint32_t G, D;
    asm("fma.rn.relu.f16x2 %0, %1, %2, %3;" : "=r"(U) : "r"(s), "r"(0x00400040u), "r"(fm));
    asm("fma.rn.f16x2 %0, %1, %2, %3;" : "=r"(G) : "r"(U & 0x003F003Fu), "r"(ca), "r"(0x98B898B8u));
    asm("{.reg .b32 n; neg.f16x2 n, %1; fma.rn.relu.f16x2 %0, %1, n, %2;}" : "=r"(D) : "r"(G), "r"(0x00570057u));
    if (mul) return U * sixteen - D;
    return (U << 4) - D;
}
__device__ __forceinline__ uint32_t or3(uint32_t a, uint32_t b, uint32_t c) { uint32_t r; asm("lop3.b32 %0, %1, %2, %3, 0xFE;" : "=r"(r) : "r"(a), "r"(b), "r"(c)); return r; }
__device__ __forceinline__ void exp_tile(const uint32_t (&S)[32], uint32_t (&P)[32], Shift& h, uint32_t ca, uint32_t sixteen) {
    uint32_t U[33];
    int n = 0;
    #pragma unroll
    for (int i = 0; i < 32; i++) {
        if (is_poly(i)) P[i] = exp2_fix(S[i], (i & 1) ? h.f1 : h.f0, ca, U[n++], (IMASK >> i) & 1, sixteen);
        else P[i] = exp2_mufu(S[i], (i & 1) ? h.n1 : h.n0);
    }
    U[n] = 0u;
    #pragma unroll
    for (int i = 0; i < 32; i += 6) {
        if (i + 5 <= n) h.bad = or3(h.bad, or3(U[i], U[i + 1], U[i + 2]), or3(U[i + 3], U[i + 4], U[i + 5]));
        else {
            #pragma unroll
            for (int j = i; j < i + 6; j += 2) if (j < n) h.bad = or3(h.bad, U[j], U[j + 1]);
        }
    }
    pin(P);
}
__device__ __forceinline__ uint32_t hfma2(uint32_t a, uint32_t b, uint32_t c) { uint32_t r; asm("fma.rn.f16x2 %0, %1, %2, %3;" : "=r"(r) : "r"(a), "r"(b), "r"(c)); return r; }
__device__ __forceinline__ void unit_start(const uint32_t (&S)[32], Shift& h, uint32_t (&o2)[10]) {
    uint32_t m[4] = {S[0], S[1], S[2], S[3]};
    #pragma unroll
    for (int i = 1; i < 8; i++)
        #pragma unroll
        for (int e = 0; e < 4; e++) m[e] = hmax2(m[e], S[4 * i + e]);
    const uint32_t a = hadd2(m[0], m[2]), c = hadd2(m[1], m[3]);
    uint32_t x = hadd2(__byte_perm(a, c, 0x5410), __byte_perm(a, c, 0x7632));
    x = hadd2(x, __shfl_xor_sync(0xffffffffu, x, 1));
    x = hadd2(x, __shfl_xor_sync(0xffffffffu, x, 2));
    const uint32_t T = hfma2(x, 0xAC00AC00u, TBIAS);
    const uint32_t n = hadd2(T, 0xDE00DE00u), f = hfma2(n, 0x00400040u, 0x03C003C0u);
    h.n0 = __byte_perm(n, 0, 0x1010); h.n1 = __byte_perm(n, 0, 0x3232);
    h.f0 = __byte_perm(f, 0, 0x1010); h.f1 = __byte_perm(f, 0, 0x3232);
    h.bad = T ^ 0x58005800u;
    #pragma unroll
    for (int i = 0; i < 10; i++) o2[i] = 0u;
}
__device__ __forceinline__ uint32_t o_offset() {
    const int c = cta_now(), tid = tid_now();
    return (mt_of(c) * 256 + (tid & 128) + ((tid >> 1) & 48) + ((tid >> 2) & 7)) * (D_ * 2) + nt_of(c) * 64 + (tid & 3) * 16;
}
template <int PASS, int UNIT>
__device__ __forceinline__ void unit_end(const uint32_t (&o)[10], uint32_t bad, uint32_t lb, uint32_t oo, uint32_t& fail, float iv) {
    float v[20];
    #pragma unroll
    for (int i = 0; i < 10; i++) h2_unpack(o[i], v[2 * i], v[2 * i + 1]);
    const float i0 = rcp(v[16]) * iv, i1 = rcp(v[18]) * iv;
    uint32_t r[8], z = 0;
    #pragma unroll
    for (int j = 0; j < 4; j++) {
        r[j] = pack_bf16(v[4*j] * i0, v[4*j+1] * i0); r[4 + j] = pack_bf16(v[4*j+2] * i1, v[4*j+3] * i1);
        z = bfma2(r[j], r[4 + j], z);
    }
    const bool good = o[8] - 0x34003400u < 0x48000000u && o[9] - 0x34003400u < 0x48000000u &&
                      ((bad & 0xF800F800u) | (bmul2(z, 0u) & 0x7FFF7FFFu) | (fail & (1u << (2 * PASS + UNIT)))) == 0;
    const bool all = __all_sync(0xffffffffu, good);
    char* dst = reinterpret_cast<char*>(g_o) + oo + (UNIT * 64 * D_ + PASS * 512) * 2;
    stg128_pred(dst, make_uint4(r[0], r[1], r[2], r[3]), all);
    stg128_pred(dst + 16 * D_, make_uint4(r[4], r[5], r[6], r[7]), all);
    if (__builtin_expect(!all, 0)) {
        fail |= 1u << (2 * PASS + UNIT);
        if (PASS == 0) {
            #pragma unroll
            for (int s = 0; s < 2; s++) g_qsave[cta_now()][UNIT * 2 + s][tid_now()] = lds128(A_KP + (UNIT * 2 + s) * 4096 + tid_now() * 16);
        }
    }
    __syncwarp();
    mbar_arrive_elect_p(lb + PASS * 16, all);
}
__device__ __forceinline__ void swap_q(uint32_t (&q)[8], uint32_t a) {
    asm volatile("{\n.reg .pred p;\nsetp.ne.u32 p, %8, 0;\n"
                 "@p st.shared.v4.b32 [%8 + -8192], {%0, %1, %2, %3};\n@p st.shared.v4.b32 [%8 + -4096], {%4, %5, %6, %7};\n"
                 "@p ld.shared.v4.b32 {%0, %1, %2, %3}, [%8];\n@p ld.shared.v4.b32 {%4, %5, %6, %7}, [%8 + 4096];\n}"
                 : "+r"(q[0]), "+r"(q[1]), "+r"(q[2]), "+r"(q[3]), "+r"(q[4]), "+r"(q[5]), "+r"(q[6]), "+r"(q[7]) : "r"(a) : "memory");
}
static_assert(A_QX == A_KP + 8192, "parking places");
template <bool INIT>
__device__ __forceinline__ void issue_pv(uint32_t (&o)[10], const uint32_t (&P)[32], uint64_t dv) {
    if (INIT) wg_pv_init(o, P[0], P[1], P[2], P[3], dv); else wg_pv_acc(o, P[0], P[1], P[2], P[3], dv);
    #pragma unroll
    for (int k = 1; k < 8; k++) wg_pv_acc(o, P[4*k], P[4*k+1], P[4*k+2], P[4*k+3], dv + k * 16);
}

__device__ __forceinline__ uint4 quad_transpose(uint32_t x0, uint32_t x1, uint32_t x2, uint32_t x3, int t) {
    const bool b0 = t & 1, b1 = t & 2;
    uint32_t s0 = b0 ? x0 : x1, s1 = b0 ? x2 : x3;
    s0 = __shfl_xor_sync(0xffffffffu, s0, 1); s1 = __shfl_xor_sync(0xffffffffu, s1, 1);
    const uint32_t y0 = b0 ? s0 : x0, y1 = b0 ? x1 : s0, y2 = b0 ? s1 : x2, y3 = b0 ? x3 : s1;
    uint32_t u0 = b1 ? y0 : y2, u1 = b1 ? y1 : y3;
    u0 = __shfl_xor_sync(0xffffffffu, u0, 2); u1 = __shfl_xor_sync(0xffffffffu, u1, 2);
    return b1 ? make_uint4(u0, u1, y2, y3) : make_uint4(y0, y1, u0, u1);
}
__device__ __forceinline__ uint32_t movm(uint32_t v) { uint32_t r; asm volatile("movmatrix.sync.aligned.m8n8.trans.b16 %0, %1;" : "=r"(r) : "r"(v)); return r; }
__device__ __forceinline__ void attn_repair(uint32_t lb, int wg, int ow, int pass, int unit) {
    const int tid = tid_now(), w = (tid >> 5) & 3, g = (tid & 31) >> 2, t = tid & 3;
    uint4* const sc = &g_qsave[cta_now()][0][tid & ~96];
    const uint4 qx = __ldcg(sc + (pass * 2 + unit) * 512 + ow * 32), qy = __ldcg(sc + (pass * 2 + unit) * 512 + 256 + ow * 32);
    float ss = ldsf(M_SS + pass * 4);
    if (ss == 0.f) ss = 1.f;
    const uint4 q0 = quad_transpose(qx.x, qx.z, qy.x, qy.z, t), q1 = quad_transpose(qx.y, qx.w, qy.y, qy.w, t);
    const char* kv = g_kv + (size_t)(nt_of(cta_now()) * 2 + pass) * 16 * KV_TILE + t * 2048 + g * 16;
    float o[4][4], m0 = -INFINITY, m1 = -INFINITY, l0 = 0.f, l1 = 0.f;
    #pragma unroll
    for (int j = 0; j < 4; j++) { o[j][0] = 0.f; o[j][1] = 0.f; o[j][2] = 0.f; o[j][3] = 0.f; }
    uint4 kf[8];
    #pragma unroll
    for (int i = 0; i < 8; i++) kf[i] = __ldcg(reinterpret_cast<const uint4*>(kv + ((4 * w - 1) & 15) * KV_TILE + i * 128));
    #pragma unroll 1
    for (int b = 8 * w; b < 8 * w + 8; b++) {
        uint4 vf[8];
        #pragma unroll
        for (int i = 0; i < 8; i++) vf[i] = __ldcg(reinterpret_cast<const uint4*>(kv + (b >> 1) * KV_TILE + (b & 1) * 1024 + 8192 + i * 128));
        float s[8][4];
        #pragma unroll
        for (int i = 0; i < 8; i++) {
            s[i][0] = 0.f; s[i][1] = 0.f; s[i][2] = 0.f; s[i][3] = 0.f;
            mma_f16(s[i], q0.x, q1.x, q0.y, q1.y, kf[i].x, kf[i].y); mma_f16(s[i], q0.z, q1.z, q0.w, q1.w, kf[i].z, kf[i].w);
        }
        #pragma unroll
        for (int i = 0; i < 8; i++) kf[i] = __ldcg(reinterpret_cast<const uint4*>(kv + (((b - 1) >> 1) & 15) * KV_TILE + (~b & 1) * 1024 + i * 128));
        float t0 = m0, t1 = m1;
        #pragma unroll
        for (int i = 0; i < 8; i++) { t0 = fmaxf(t0, fmaxf(s[i][0], s[i][1])); t1 = fmaxf(t1, fmaxf(s[i][2], s[i][3])); }
        t0 = quad_max(t0); t1 = quad_max(t1);
        const float a0 = ex2((m0 - t0) * ss), a1 = ex2((m1 - t1) * ss);
        m0 = t0; m1 = t1;
        l0 *= a0; l1 *= a1;
        #pragma unroll
        for (int j = 0; j < 4; j++) { o[j][0] *= a0; o[j][1] *= a0; o[j][2] *= a1; o[j][3] *= a1; }
        #pragma unroll
        for (int k = 0; k < 4; k++) {
            uint32_t pf[4];
            #pragma unroll
            for (int e = 0; e < 2; e++) {
                const float p0 = ex2((s[2*k+e][0] - m0) * ss), p1 = ex2((s[2*k+e][1] - m0) * ss), p2 = ex2((s[2*k+e][2] - m1) * ss), p3 = ex2((s[2*k+e][3] - m1) * ss);
                l0 += p0 + p1; l1 += p2 + p3;
                pf[2*e] = pack_f16(p0, p1); pf[2*e+1] = pack_f16(p2, p3);
            }
            mma_f16(o[0], pf[0], pf[1], pf[2], pf[3], movm(vf[2*k].x), movm(vf[2*k+1].x));
            mma_f16(o[1], pf[0], pf[1], pf[2], pf[3], movm(vf[2*k].y), movm(vf[2*k+1].y));
            mma_f16(o[2], pf[0], pf[1], pf[2], pf[3], movm(vf[2*k].z), movm(vf[2*k+1].z));
            mma_f16(o[3], pf[0], pf[1], pf[2], pf[3], movm(vf[2*k].w), movm(vf[2*k+1].w));
        }
    }
    sc[24 * 256 + w * 32] = make_uint4(__float_as_uint(m0), __float_as_uint(m1), __float_as_uint(quad_sum(l0)), __float_as_uint(quad_sum(l1)));
    #pragma unroll
    for (int j = 0; j < 4; j++) sc[(25 + j) * 256 + w * 32] = make_uint4(__float_as_uint(o[j][0]), __float_as_uint(o[j][1]), __float_as_uint(o[j][2]), __float_as_uint(o[j][3]));
    named_sync(NB_WG + wg, 128);
    uint4 h[4];
    #pragma unroll
    for (int i = 0; i < 4; i++) { h[i] = __ldcg(sc + 24 * 256 + i * 32); m0 = fmaxf(m0, __uint_as_float(h[i].x)); m1 = fmaxf(m1, __uint_as_float(h[i].y)); }
    float r[4] = {0.f, 0.f, 0.f, 0.f};
    l0 = 0.f; l1 = 0.f;
    #pragma unroll
    for (int i = 0; i < 4; i++) {
        const uint4 v = __ldcg(sc + (25 + w) * 256 + i * 32);
        const float a0 = ex2((__uint_as_float(h[i].x) - m0) * ss), a1 = ex2((__uint_as_float(h[i].y) - m1) * ss);
        l0 = fmaf(a0, __uint_as_float(h[i].z), l0); l1 = fmaf(a1, __uint_as_float(h[i].w), l1);
        r[0] = fmaf(a0, __uint_as_float(v.x), r[0]); r[1] = fmaf(a0, __uint_as_float(v.y), r[1]);
        r[2] = fmaf(a1, __uint_as_float(v.z), r[2]); r[3] = fmaf(a1, __uint_as_float(v.w), r[3]);
    }
    const float iv = 16.f * ldsf(M_IV + pass * 4), i0 = iv * rcp(l0), i1 = iv * rcp(l1);
    uint32_t* dst = reinterpret_cast<uint32_t*>(reinterpret_cast<char*>(g_o) + (o_offset() & ~48u) + ((unit * 64 + (ow - w) * 16) * D_ + pass * 512) * 2) + w * 4 + t;
    dst[0] = pack_bf16(r[0] * i0, r[1] * i0);
    dst[4 * D_] = pack_bf16(r[2] * i1, r[3] * i1);
    named_sync(NB_WG + wg, 128);
    if ((tid & 127) == 0) mbar_arrive(lb + B_OD + (pass * 2 + wg) * 8);
    __syncwarp();
}
__device__ __forceinline__ bool wg_any(bool p, int id) {
    uint32_t r;
    asm volatile("{\n.reg .pred a, b;\nsetp.ne.u32 a, %1, 0;\nbarrier.cta.red.or.aligned.pred b, %2, 128, a;\nselp.u32 %0, 1, 0, b;\n}" : "=r"(r) : "r"((uint32_t)p), "r"(id) : "memory");
    return r != 0;
}

__device__ __forceinline__ void load_gu(uint32_t (&f)[64], uint32_t src, int warp, int lane) {
    const uint32_t row = (warp & 3) * 64 + (lane >> 4) * 8 + (lane & 7), ch = (lane >> 3) & 1, sw = (lane >> 1) & 3;
    const uint32_t a0 = base32(src + (warp >> 2) * 32768 + row * 64 + ((ch ^ sw) << 4)), a1 = base32(a0 ^ 32);
    #pragma unroll
    for (int i = 0; i < 16; i++) ldsm4t(f[4*i], f[4*i+1], f[4*i+2], f[4*i+3], ((i & 1) ? a1 : a0) + ((i >> 1) & 1) * 16384 + (i >> 2) * 1024);
}

__device__ __forceinline__ void arrive_loaded(uint32_t bar, const uint32_t (&f)[64], uint32_t zero) {
    uint32_t x = 0;
    #pragma unroll
    for (int i = 0; i < 16; i++) x |= f[4 * i];
    mbar_arrive_elect(bar + (x & zero));
}
__device__ __forceinline__ void flush(uint32_t (&o2)[10], const uint32_t (&o)[10]) {
    #pragma unroll
    for (int i = 0; i < 10; i++) o2[i] = hadd2(o2[i], o[i]);
}
__device__ __forceinline__ void attention_phase(int L, uint32_t lb, int wg, uint32_t (&qa)[8], uint32_t (&qb)[8], uint32_t (&SA)[32], uint32_t (&SB_)[32], uint64_t dk0, uint64_t dv0, uint32_t ca, uint32_t (&wa)[64], uint32_t zero, uint32_t sixteen) {
    uint32_t PA[32], PB[32], oa[10], ob[10], oa2[10], ob2[10];
    Shift ha, hb;
    uint32_t fail = (lds32(M_SS) ? 3u : 0u) | (lds32(M_SS + 4) ? 12u : 0u);
    ca += base32(fail) >> 4;
    const uint32_t oo = o_offset(), odb = lb + B_OD + wg * 8;
    constexpr uint64_t SL = R_SLOT >> 4, KH = 4096 >> 4;
    unit_start(SA, ha, oa2);
    exp_tile(SA, PA, ha, ca, sixteen);
    #pragma unroll
    for (int i = 0; i < 10; i++) { ob[i] = 0u; ob2[i] = 0u; }
    hb = ha;
    mbar_spin(lb + B_KS, 0);
    mbar_spin(lb + B_ONE, 0);
    #pragma unroll 1
    for (int it = 0; ; it++) {
        const uint32_t ph = it & 1;
        uint32_t qsw = 0;
        #pragma unroll
        for (int u = 0; u < 4; u++) {
            const uint64_t dk = opaque(dk0) + u * SL, dv = opaque(dv0) + u * SL;
            wg_fence();
            if (u == 0) issue_pv<true>(oa, PA, dv); else issue_pv<false>(oa, PA, dv);
            wg_qk_init(SA, qa[0], qa[1], qa[2], qa[3], dk);
            wg_qk_acc(SA, qa[4], qa[5], qa[6], qa[7], dk + KH);
            wg_commit();
            if (u > 0) wg_wait<1>();
            pin(SB_); pin(ob);
            if (u == 0) {
                flush(ob2, ob);
                if (__builtin_expect((it & 3) == 0, 0)) {
                    if (it) unit_end<0, 1>(ob2, hb.bad, odb, oo, fail, ldsf(M_IV));
                    unit_start(SB_, hb, ob2);
                }
            } else mbar_arrive_elect(lb + B_AE + 8 * (u - 1));
            if (u == 3) swap_q(qb, qsw ? qsw + 8192 : 0u);
            exp_tile(SB_, PB, hb, ca, sixteen);
            wg_fence();
            if (u == 0) issue_pv<true>(ob, PB, dv); else issue_pv<false>(ob, PB, dv);
            wg_qk_init(SB_, qb[0], qb[1], qb[2], qb[3], dk);
            wg_qk_acc(SB_, qb[4], qb[5], qb[6], qb[7], dk + KH);
            wg_commit();
            wg_wait<1>();
            pin(SA); pin(oa);
            if (u == 2) { qsw = it == 3 ? A_QX + tid_now() * 16 : 0u; swap_q(qa, qsw); }
            if (u == 3) {
                flush(oa2, oa);
                if (__builtin_expect((it & 3) == 3, 0)) {
                    TL(0, L * 32 + 7 + (it >> 2)); CK(0, L * 32 + 1 + (it >> 2));
                    if (it == 7) goto done;
                    unit_end<0, 0>(oa2, ha.bad, odb, oo, fail, ldsf(M_IV));
                    unit_start(SA, ha, oa2);
                }
            }
            exp_tile(SA, PA, ha, ca, sixteen);
            mbar_spin(lb + B_AF + 8 * ((u + 1) & 3), u < 3 ? ph : ph ^ 1);
        }
        wg_wait<0>();
        mbar_arrive_elect(lb + B_AE + 24);
    }
done:
    const float iv = ldsf(M_IV + 4);
    mbar_spin(lb + B_GU, 0);
    load_gu(wa, F_GU0, tid_now() >> 5, tid_now() & 31);
    unit_end<1, 0>(oa2, ha.bad, odb, oo, fail, iv);
    wg_wait<0>();
    pin(ob);
    mbar_arrive_elect(lb + B_AE + 24);
    flush(ob2, ob);
    unit_end<1, 1>(ob2, hb.bad, odb, oo, fail, iv);
    arrive_loaded(lb + B_FG, wa, zero);
    if (__builtin_expect(wg_any(fail != 0, NB_WG + wg), 0)) {
        uint4* const qs = &g_qsave[cta_now()][0][tid_now()];
        qs[4 * 256] = make_uint4(qa[0], qa[1], qa[2], qa[3]); qs[5 * 256] = make_uint4(qa[4], qa[5], qa[6], qa[7]);
        qs[6 * 256] = make_uint4(qb[0], qb[1], qb[2], qb[3]); qs[7 * 256] = make_uint4(qb[4], qb[5], qb[6], qb[7]);
        #pragma unroll
        for (int i = 0; i < 16; i++) qs[(8 + i) * 256] = make_uint4(wa[4*i], wa[4*i+1], wa[4*i+2], wa[4*i+3]);
        sts32(M_SR + (tid_now() >> 5) * 4, fail);
        named_sync(NB_WG + wg, 128);
        #pragma unroll 1
        for (int r = 0; r < 16; r++)
            if ((warp_uniform(lds32(M_SR + wg * 16 + (r & 3) * 4)) >> (r >> 2)) & 1) attn_repair(lb, wg, r & 3, r >> 3, (r >> 2) & 1);
        #pragma unroll
        for (int i = 0; i < 16; i++) { const uint4 v = __ldcg(qs + (8 + i) * 256); wa[4*i] = v.x; wa[4*i+1] = v.y; wa[4*i+2] = v.z; wa[4*i+3] = v.w; }
    }
    TL(0, L * 32 + 9); CK(0, L * 32 + 8);
}

__device__ __forceinline__ void oproj_steps(float (&acc)[64], uint32_t lb, int wg, int k0, int k1) {
    const bool leader = (tid_now() & 127) == 0;
    #pragma unroll 1
    for (int k = k0; k < k1; k++) {
        const uint32_t st = k & 3;
        mbar_spin(lb + B_OF + 8 * st, (k >> 2) & 1);
        const uint64_t da = desc_sw128(o_a(st) + wg * 8192, 16, 1024);
        const uint64_t db = desc_sw128(o_b(st), 8192, 1024);
        wg_fence();
        #pragma unroll
        for (int kk = 0; kk < 4; kk++) wg_gemm_n128(acc, da + kk * 2, db + kk * 128);
        wg_commit();
        wg_wait<1>();
        if (leader && k > 0) mbar_arrive(lb + B_OE + 8 * ((k - 1) & 3));
    }
}

__device__ __forceinline__ uint32_t lane_key(uint32_t key, int lane) { return (key | 31u) ^ lane; }
__device__ __forceinline__ uint4 best_of(const uint4& e, int lane) {
    const uint32_t m = redux_max(lane_key(e.x, lane)), src = ~m & 31u;
    return make_uint4(m, __shfl_sync(0xffffffffu, e.y, src), __shfl_sync(0xffffffffu, e.z, src), __shfl_sync(0xffffffffu, e.w, src));
}
template <typename T> __device__ __forceinline__ T* early(T* p) { asm volatile("" : "+l"(p)); return p; }
__device__ __forceinline__ void load_wd(uint32_t (&wd)[64], uint32_t lb, int warp, int lane) {
    mbar_spin(lb + B_WD, 0);
    const uint32_t a0 = F_WD + warp * 8192 + ((lane >> 4) * 8 + (lane & 7)) * 128, ch = ((lane >> 3) & 1) ^ (lane & 7);
    #pragma unroll
    for (int i = 0; i < 16; i++) ldsm4t(wd[4*i], wd[4*i+1], wd[4*i+2], wd[4*i+3], base32(a0 + ((ch ^ (i & 6)) << 4)) + (i >> 3) * 4096 + (i & 1) * 2048);
}
__device__ __forceinline__ void stage_tile(const uint32_t (&xa)[4], const uint32_t (&xv)[32]) {
    #pragma unroll
    for (int m = 0; m < 8; m++) stsm4(xa[m & 3] + (m < 4 ? YT0 - XT0 : YT1 - XT0), xv[4*m], xv[4*m+1], xv[4*m+2], xv[4*m+3]);
    fence_async_smem();
    __syncwarp();
}

__device__ __forceinline__ void tail_phase(int L, uint32_t lb, int wg, const uint32_t (&wa)[64]) {
    const int c = cta_now(), blk = blk_of(c), cb = cb_of(c), tid = tid_now();
    const int lane = tid & 31, w = (tid >> 5) & 3, g = lane >> 2, t = lane & 3;
    const int lr0 = wg * 64 + w * 16 + g;
    uint32_t xa[4];
    #pragma unroll
    for (int m = 0; m < 4; m++) xa[m] = base32(XT0 + (wg * 64 + w * 16 + (lane & 15)) * 128 + (((lane >> 4) ^ (lane & 7) ^ (2 * m)) << 4));
    uint32_t xv[32];
    const bool ffn = c < NFC;
    uint32_t wb[64], wd[64];
    float own[6];
    {
        float acc[64];
        #pragma unroll
        for (int i = 0; i < 64; i++) acc[i] = 0.f;
        pin(acc);
        float2 rs0 = make_float2(0.f, 0.f), rs1 = rs0;
        if (L) { rs0 = __ldcg(&g_x.rs1[blk * 128 + lr0]); rs1 = __ldcg(&g_x.rs1[blk * 128 + lr0 + 8]); }
        oproj_steps(acc, lb, wg, 0, 8);
        mbar_spin(lb + B_RES, 0);
        #pragma unroll
        for (int m = 0; m < 8; m++) ldsm4(xv[4*m], xv[4*m+1], xv[4*m+2], xv[4*m+3], xa[m & 3] + (m < 4 ? 0 : XT1 - XT0));
        if (L) {
            const int d = (int)lds32(M_RT + 12) - (blk * 128 + lr0);
            const Ln2 k0 = ln2_coef(rs0.y, d == 0 ? 0.f : rsq(rs0.x + LN_EPS)), k1 = ln2_coef(rs1.y, d == 8 ? 0.f : rsq(rs1.x + LN_EPS));
            #pragma unroll
            for (int j = 0; j < 16; j++) { xv[2*j] = add_ln2(xv[2*j], k0); xv[2*j+1] = add_ln2(xv[2*j+1], k1); }
        }
        pin(xv);
        oproj_steps(acc, lb, wg, 8, 16);
        uint32_t wv[16];
        #pragma unroll
        for (int i = 0; i < 4; i++) ldsm4(wv[4*i], wv[4*i+1], wv[4*i+2], wv[4*i+3], (lane & 1) ? M_RED + (lane >> 3) * 16 + i * 64 : M_RED + 256);
        uint4* const pdst = early(&g_x.part[L][blk][cb][lr0]);
        wg_wait<0>();
        pin(acc);
        if ((tid & 127) == 0) mbar_arrive(lb + B_OE + 24);
        TL(0, L * 32 + 11); CK(0, L * 32 + 13);
        float sa[4] = {0.f, 0.f, 0.f, 0.f}, sb[4] = {0.f, 0.f, 0.f, 0.f}, sc[4] = {0.f, 0.f, 0.f, 0.f};
        float sd[4] = {0.f, 0.f, 0.f, 0.f}, se[4] = {0.f, 0.f, 0.f, 0.f};
        #pragma unroll
        for (int m = 0; m < 8; m++) {
            #pragma unroll
            for (int i = 0; i < 4; i++) xv[4*m+i] = badd2(xv[4*m+i], pack_bf16(acc[8*m + 2*i], acc[8*m + 2*i + 1]));
            mma_bf16(sa, xv[4*m], xv[4*m+1], xv[4*m+2], xv[4*m+3], wv[2*m], wv[2*m+1]);
            mma_bf16_k8(sb, xv[4*m], xv[4*m+1], xv[4*m]); mma_bf16_k8(sc, xv[4*m], xv[4*m+1], xv[4*m+1]);
            mma_bf16_k8(sd, xv[4*m+2], xv[4*m+3], xv[4*m+2]); mma_bf16_k8(se, xv[4*m+2], xv[4*m+3], xv[4*m+3]);
        }
        const float q0 = (g & 1) ? sb[1] + sd[1] : sb[0] + sd[0], q1 = (g & 1) ? sc[3] + se[3] : sc[2] + se[2];
        if (t == (g >> 1)) {
            st_x128(pdst, __float_as_uint(sa[0]), __float_as_uint(q0), __float_as_uint(sa[1]), 0u);
            st_x128(pdst + 8, __float_as_uint(sa[2]), __float_as_uint(q1), __float_as_uint(sa[3]), 0u);
        }
        __syncwarp();
        own[0] = sa[0]; own[1] = __shfl_sync(0xffffffffu, q0, (lane & 28) + (g >> 1)); own[2] = sa[1];
        own[3] = sa[2]; own[4] = __shfl_sync(0xffffffffu, q1, (lane & 28) + (g >> 1)); own[5] = sa[3];
    }
    TL(0, L * 32 + 12);
    load_gu(wb, F_GU1, tid >> 5, lane);
    stage_tile(xa, xv);
    uint4* const hdst = early(&g_x.hdr[L][(tid & 15) * 8 + cb][blk]);
    uint32_t* const cdst = early(&g_x.cand[L][blk][cb * 64 + t * 4]);
    const float ws = ldsf(M_WS);
    float mean, var, rstd;
    uint4 f;
    {
        const bool o0 = cb == 2 * t, o1 = cb == 2 * t + 1;
        const uint32_t m0 = o0 ? 0u : EMPTY, m1 = o1 ? 0u : EMPTY;
        const uint4* const psrc = &g_x.part[L][blk][2 * t][lr0];
        uint4 p[4];
        uint32_t n = 0;
        #pragma unroll 1
        do {
            p[0] = ld_x128(psrc); p[1] = ld_x128(psrc + 128); p[2] = ld_x128(psrc + 8); p[3] = ld_x128(psrc + 136);
            poll_tick(n);
        } while (warp_any((((p[0].w | p[2].w) & m0) | ((p[1].w | p[3].w) & m1)) != 0));
        mbar_arrive_elect_p(lb + B_XS, L == 0);
        float v[8];
        #pragma unroll
        for (int h = 0; h < 2; h++) {
            v[3*h] = (o0 ? own[3*h] : __uint_as_float(p[2*h].x)) + (o1 ? own[3*h] : __uint_as_float(p[2*h+1].x));
            v[3*h+1] = (o0 ? own[3*h+1] : __uint_as_float(p[2*h].y)) + (o1 ? own[3*h+1] : __uint_as_float(p[2*h+1].y));
            v[3*h+2] = (o0 ? own[3*h+2] : __uint_as_float(p[2*h].z)) + (o1 ? own[3*h+2] : __uint_as_float(p[2*h+1].z));
        }
        halve<3>(v, lane, 1);
        #pragma unroll
        for (int i = 0; i < 3; i++) v[i] += __shfl_xor_sync(0xffffffffu, v[i], 2);
        mean = v[0] * (1.f / D_);
        var = fmaxf(v[1] * (1.f / D_) - mean * mean, 0.f);
        rstd = rsq(var + LN_EPS);
        TL(0, L * 32 + 13);
        const uint32_t key = lane_key(order_bits(rstd * (v[2] - mean * ws)), lane);
        if (redux_max(key) == key) sts128(M_SR + (tid >> 5) * 16, key, __float_as_uint(mean), __float_as_uint(rstd), blk * 128 + lr0 + 8 * (t & 1));
        named_sync(NB_CONS, 256);
        f = best_of(lds128(M_SR + (lane & 7) * 16), lane);
        st_x128_if(tid < 16, hdst, f.x, f.y, f.z, f.w);
        const int d = (int)f.w - (blk * 128 + lr0);
        if ((d & ~8) == 0) {
            #pragma unroll
            for (int b = 0; b < 4; b++)
                st_x128(cdst + b * 16, d ? xv[8*b+1] : xv[8*b], d ? xv[8*b+3] : xv[8*b+2], d ? xv[8*b+5] : xv[8*b+4], d ? xv[8*b+7] : xv[8*b+6]);
        }
        __syncwarp();
    }
    if (t < 2) {
        if (L) { const Ln2 k = ln2_coef(mean, rstd); sts128(XT0 + (lr0 + 8 * t) * 16, k.nm, k.rh, k.rl, k.c); }
        else if (cb == 0) st_x64(&g_x.rs1[blk * 128 + lr0 + 8 * t], __float_as_uint(var), __float_as_uint(mean));
    }
    TL(0, L * 32 + 28);
    if (tid == 0) sts32(M_CR, f.w);
    __syncwarp();
    mbar_arrive_elect_p(lb + B_XS, L);
    load_wd(wd, lb, tid >> 5, lane);
    TL(0, L * 32 + 25);
    const uint32_t* const xsrc = early(&g_x.cand[L][0][(tid >> 5) * 32 + t * 4]);
    float* const ydst = early(&g_x.ypart[L][(tid >> 5) * 16 + t * 4][c][g]);
    uint4 e;
    {
        uint32_t n = 0;
        #pragma unroll 1
        do { e = ld_x128(&g_x.hdr[L][blk * 8 + cb][lane & 15]); poll_tick(n); } while (warp_any(e.w == EMPTY && (lane & 15) != blk));
        if ((lane & 15) == blk) e = f;
        e = best_of(e, lane);
    }
    TL(0, L * 32 + 14);
    if (tid == 0) sts128(M_RT + 16 * L, (e.x & 0x80000000u) ? e.x ^ 0x80000000u : ~e.x, e.y, e.z, e.w);
    if (tid == 0) mbar_arrive(lb + B_RT);
    if (ffn) {
        const uint32_t* src = xsrc + (~e.x & 15u) * (D_ / 2);
        const Ln2 kx = ln2_coef(__uint_as_float(e.y), __uint_as_float(e.z));
        uint4 x[4];
        uint32_t n = 0;
        #pragma unroll 1
        do {
            x[0] = ld_x128(src); x[1] = ld_x128(src + 16); x[2] = ld_x128(src + 256); x[3] = ld_x128(src + 272);
            poll_tick(n);
        } while (warp_any(max(max(x[0].x, x[1].x), max(x[2].x, x[3].x)) == EMPTY));
        TL(0, L * 32 + 15);
        float d[4][4];
        #pragma unroll
        for (int i = 0; i < 4; i++) { d[i][0] = 0.f; d[i][1] = 0.f; d[i][2] = 0.f; d[i][3] = 0.f; }
        #pragma unroll
        for (int k = 0; k < 8; k++) {
            const uint32_t b0 = ln2((k & 1) ? x[k >> 1].z : x[k >> 1].x, kx), b1 = ln2((k & 1) ? x[k >> 1].w : x[k >> 1].y, kx);
            const uint32_t* f = (k < 4 ? wa : wb) + (k & 3) * 16;
            #pragma unroll
            for (int i = 0; i < 4; i++) mma_bf16(d[i], f[4*i], f[4*i+1], f[4*i+2], f[4*i+3], b0, b1);
        }
        #pragma unroll
        for (int h = 0; h < 2; h++) {
            const float a = (t & 1) ? d[1][2*h] : d[0][2*h], b = (t & 1) ? d[3][2*h] : d[2][2*h];
            stsf(M_RED + ((tid >> 5) * 64 + t * 16 + h * 8 + g) * 4, (t & 2) ? b : a);
        }
        named_sync(NB_CONS, 256);
        TL(0, L * 32 + 16);
        float2 v[8];
        #pragma unroll
        for (int i = 0; i < 8; i++) v[i] = lds64f(base32(M_RED + lane * 8) + i * 256);
        const float s0 = ((v[0].x + v[1].x) + (v[2].x + v[3].x)) + ((v[4].x + v[5].x) + (v[6].x + v[7].x));
        const float s1 = ((v[0].y + v[1].y) + (v[2].y + v[3].y)) + ((v[4].y + v[5].y) + (v[6].y + v[7].y));
        const uint32_t mine = pack_bf16(s0, s1), other = __shfl_xor_sync(0xffffffffu, mine, 16);
        const uint32_t gv = lane < 16 ? mine : other, uv = lane < 16 ? other : mine;
        const float g0 = bf_lo(gv), g1 = bf_hi(gv);
        const uint32_t hv = bmul2(pack_bf16(g0 * sigmoid(g0), g1 * sigmoid(g1)), uv);
        uint32_t hb[4];
        #pragma unroll
        for (int i = 0; i < 4; i++) hb[i] = __shfl_sync(0xffffffffu, hv, 4 * i + t);
        float y[8][4];
        #pragma unroll
        for (int i = 0; i < 8; i++) {
            y[i][0] = 0.f; y[i][1] = 0.f; y[i][2] = 0.f; y[i][3] = 0.f;
            mma_bf16(y[i], wd[8*i], wd[8*i+1], wd[8*i+2], wd[8*i+3], hb[0], hb[1]);
            mma_bf16(y[i], wd[8*i+4], wd[8*i+5], wd[8*i+6], wd[8*i+7], hb[2], hb[3]);
        }
        #pragma unroll
        for (int i = 0; i < 2; i++)
            #pragma unroll
            for (int h = 0; h < 2; h++) {
                const float a = (t & 1) ? y[2 + i][2*h] : y[i][2*h], b = (t & 1) ? y[6 + i][2*h] : y[4 + i][2*h];
                st_x32(ydst + (i * 2 + h) * (NFC * 8), __float_as_uint((t & 2) ? b : a));
            }
    }
    __syncwarp();
    mbar_arrive_elect(lb + B_FD);
    TL(0, L * 32 + 17);
}

__device__ __forceinline__ void qkv_load_w(const Maps& mp, uint32_t dst, int k, uint32_t fb) { tma_load3(dst, &mp.wqkv, nt_of(blockIdx.x) * 64, k * 64, 0, fb); }
__device__ __forceinline__ void qkv_load_x(const CUtensorMap* tx, uint32_t sa, int k, uint32_t fb) {
    #pragma unroll
    for (int a = 0; a < 2; a++) tma_load(sa + a * 16384, tx, k * 64, mt_of(blockIdx.x) * 256 + a * 128, fb);
}
__device__ __forceinline__ void producer_role(const Maps& mp) {
    const int c = blockIdx.x, mt = mt_of(c), nt = nt_of(c), blk = blk_of(c), cb = cb_of(c);
    const uint64_t pol = policy_evict_first();
    #pragma unroll 1
    for (int L = 0; L < 2; L++) {
        const uint32_t lb = M_BAR + L * BAR_SET;
        const CUtensorMap* tx = &mp.x[L];
        mbar_expect_tx(lb + B_SW, 49152);
        if (L == 0) {
            mbar_nap(lb + B_QF, 0);
            qkv_load_w(mp, SD_W, mt * 2, lb + B_SW);
            qkv_load_w(mp, SD_W + 24576, mt * 2 + 1, lb + B_SW);
        }
        {
            uint32_t st = 0, ph = L;
            #pragma unroll 1
            for (int k = L ? 0 : 3; k < 16; k++) {
                mbar_sleep(k < 2 ? M_BAR + (k ? B_FD : B_XS) : lb + B_QE + 8 * st, k < 2 ? 0 : ph);
                const uint32_t fb = lb + B_QF + 8 * st, sa = SB + st * Q_STB;
                mbar_expect_tx(fb, Q_STB);
                qkv_load_w(mp, sa + Q_ABYTES, k, fb);
                if (k == 0) {
                    mbar_nap(M_BAR + B_XD, 0);
                    flags16_wait(g_x.x[mt]);
                    fence_async_global();
                    mbar_nap(M_BAR + B_RT, 0);
                    TL(256, 32);
                }
                qkv_load_x(tx, sa, k, fb);
                if (L && k >= 3 && k < 7) tma_load(SD_W + (k - 3) * 12288, &mp.r, c * 24, (k - 3) * 256, lb + B_SW);
                if (++st == 3) { st = 0; ph ^= 1; }
            }
        }
        mbar_sleep(lb + B_QE, 1);
        TL(256, L * 32 + 26);
        mbar_arrive(lb + B_AF);
        {
            const char* kv = g_kv + (size_t)nt * 32 * KV_TILE;
            const uint8_t* fl = g_x.kv[L][nt * 2];
            __nanosleep(200);
            #pragma unroll 1
            for (int j = 1; j < 4; j++) {
                flag_wait(fl + ((2 * mt + j + 1) & 15));
                fence_async_global();
                const uint32_t bytes = j == 1 ? 8192 : 16384;
                mbar_expect_tx(lb + B_AF + 8 * j, bytes);
                bulk_load(A_RING + j * R_SLOT, kv + ((2 * mt + j) & 15) * KV_TILE, bytes, lb + B_AF + 8 * j);
                if (j == 1) TL(256, L * 32 + 21);
            }
            flags16_wait(fl);
            fence_async_global();
            int t0 = 2 * mt;
            #pragma unroll 1
            for (int it = 1; it < 8; it++) {
                #pragma unroll
                for (int u = 0; u < 4; u++) {
                    const char* src = kv + ((t0 + 4 * it + u) & 15) * KV_TILE;
                    const uint32_t fb = lb + B_AF + 8 * u, dst = A_RING + u * R_SLOT;
                    mbar_nap(lb + B_AE + 8 * u, (it - 1) & 1);
                    mbar_expect_tx(fb, 16384);
                    if (u < 3) bulk_load(dst, src, 16384, fb);
                    else {
                        bulk_load(dst + 8192, src + 8192, 8192, fb);
                        if (it == 3) {
                            flags16_wait(fl + 128);
                            fence_async_global();
                            kv += 16 * KV_TILE; src = kv + 15 * KV_TILE; t0 = 0;
                        }
                        bulk_load(dst, src, 8192, fb);
                    }
                }
            }
        }
        #pragma unroll 1
        for (int it = 0; it < 4; it++) {
            #pragma unroll
            for (int s = 0; s < 4; s++) {
                mbar_spin(lb + (it ? B_OE + 8 * s : s < 2 ? B_AE + 8 + 8 * s : B_FG), it ? (it - 1) & 1 : s < 2);
                const uint32_t fb = lb + B_OF + 8 * s;
                mbar_expect_tx(fb, 32768);
                #pragma unroll
                for (int b = 0; b < 2; b++)
                    tma_load5(o_b(s) + b * 8192, &mp.wo[it >> 1], cb * 128 + b * 64, (it & 1) * 8 + s * 2, fb);
                if (s == 0 && !(it & 1)) {
                    ctr_wait(g_x.o[L][blk][it >> 1], 15);
                    fence_async_global();
                    TL(256, L * 32 + 10);
                }
                tma_load(o_a(s), &mp.o, it * 256 + s * 64, blk * 128, fb);
            }
            if (it == 0) {
                mbar_spin(lb + B_AE + 24, 1);
                mbar_expect_tx(lb + B_RES, 32768);
                tma_load_s(XT0, tx, cb * 128, blk * 128, lb + B_RES, pol);
                tma_load_s(XT1, tx, cb * 128 + 64, blk * 128, lb + B_RES, pol);
            }
        }
        if (c < NFC) {
            #pragma unroll 1
            for (int i = 0; i < 4; i++) {
                mbar_spin(lb + B_OE + 16 + 8 * (i >> 1), 1);
                tma_load3_s(F_WD + i * 16384, &mp.d, 0, c * 32, i * 4, lb + B_WD, pol);
            }
        }
    }
}

__global__ void __launch_bounds__(384, 1) k_all(const __grid_constant__ Maps mp, const bf16* __restrict__ x0, const bf16* __restrict__ wo, const bf16* __restrict__ w_down,
                                                const bf16* __restrict__ w_r, bf16* __restrict__ out, const uint64_t dk0, const uint64_t dv0, const uint32_t ca, const uint32_t zero, const uint32_t sixteen) {
    extern __shared__ __align__(1024) char smem[];
    if (smem_u32(smem) != SB) __trap();
    const int warp = warp_uniform(threadIdx.x >> 5), wg = warp >> 2;
    TL(0, 0);
    if (warp == 8) {
      if (elect_one()) {
        tm_prefetch(&mp.x[0]); tm_prefetch(&mp.wqkv);
        #pragma unroll
        for (int s = 0; s < 3; s++) { mbar_init(M_BAR + B_QF + 8 * s, 1); mbar_init(M_BAR + BAR_SET + B_QF + 8 * s, 1); }
        fence_mbar_init();
        #pragma unroll 1
        for (int s = 0; s < 3; s++) {
            const uint32_t sa = SB + s * Q_STB, fb = M_BAR + B_QF + 8 * s;
            mbar_expect_tx(fb, Q_STB);
            qkv_load_x(&mp.x[0], sa, s, fb);
            qkv_load_w(mp, sa + Q_ABYTES, s, fb);
        }
      }
      __syncwarp();
    } else if (warp > 8) {
        if (elect_one()) {
            const uint32_t o0 = warp == 9 ? B_AF : warp == 10 ? B_QE : B_AE, o1 = warp == 9 ? B_QE : warp == 10 ? B_AE : B_END, cnt = warp == 9 ? 1 : warp == 10 ? 2 : 8;
            #pragma unroll 1
            for (uint32_t o = o0; o < o1; o += 8) { const uint32_t n = o == B_K0 ? 4 : cnt; mbar_init(M_BAR + o, n); mbar_init(M_BAR + BAR_SET + o, n); }
            fence_mbar_init();
        }
        __syncwarp();
    }
    __syncthreads();
    if (wg == 2) {
        reg_dec<40>();
        if (warp > 8) side_role(mp, x0, wo, w_down, w_r, out);
        else if (elect_one()) producer_role(mp);
    } else {
        reg_inc<232>();
        #pragma unroll 1
        for (int L = 0; L < 2; L++) {
            const uint32_t lb = M_BAR + L * BAR_SET;
            uint32_t qa[8], qb[8], sa[32], sb[32], wa[64];
            qkv_phase(L, lb, wg, qa, qb, sa, sb);
            attention_phase(L, lb, wg, qa, qb, sa, sb, dk0, dv0, ca, wa, zero, sixteen);
            tail_phase(L, lb, wg, wa);
        }
    }
}

typedef CUresult (*EncodeFn)(CUtensorMap*, CUtensorMapDataType, cuuint32_t, void*, const cuuint64_t*, const cuuint64_t*, const cuuint32_t*,
                             const cuuint32_t*, CUtensorMapInterleave, CUtensorMapSwizzle, CUtensorMapL2promotion, CUtensorMapFloatOOBfill);

void make_map(EncodeFn enc, CUtensorMap* tm, const void* ptr, int rank, const cuuint64_t* dims, const cuuint64_t* strides, const cuuint32_t* box, CUtensorMapSwizzle sw) {
    const cuuint32_t es[5] = {1, 1, 1, 1, 1};
    enc(tm, CU_TENSOR_MAP_DATA_TYPE_BFLOAT16, rank, const_cast<void*>(ptr), dims, strides, box, es, CU_TENSOR_MAP_INTERLEAVE_NONE, sw,
        box[0] == 64 ? CU_TENSOR_MAP_L2_PROMOTION_L2_128B : CU_TENSOR_MAP_L2_PROMOTION_NONE, CU_TENSOR_MAP_FLOAT_OOB_FILL_NONE);
}
void make_map2(EncodeFn enc, CUtensorMap* tm, const void* ptr, uint64_t cols, uint64_t rows, uint32_t bc, uint32_t br, CUtensorMapSwizzle sw) {
    const cuuint64_t dims[2] = {cols, rows}, strides[1] = {cols * 2};
    const cuuint32_t box[2] = {bc, br};
    make_map(enc, tm, ptr, 2, dims, strides, box, sw);
}

}

extern "C" void kernel_launch(void* const* d_in, const int* in_sizes, int n_in, void* d_out, int out_size) {
    const bf16* x0 = (const bf16*)d_in[0];
    const bf16* wqkv = (const bf16*)d_in[1];
    const bf16* wo = (const bf16*)d_in[2];
    const bf16* w_r = (const bf16*)d_in[4];
    const bf16* w_gate = (const bf16*)d_in[5];
    const bf16* w_up = (const bf16*)d_in[6];
    const bf16* w_down = (const bf16*)d_in[7];

    EncodeFn enc = nullptr;
    cudaDriverEntryPointQueryResult qr;
    cudaGetDriverEntryPoint("cuTensorMapEncodeTiled", (void**)&enc, cudaEnableDefault, &qr);
    void *p_o, *p_x1;
    cudaGetSymbolAddress(&p_o, g_o); cudaGetSymbolAddress(&p_x1, g_x1);
    const CUtensorMapSwizzle S128 = CU_TENSOR_MAP_SWIZZLE_128B, S64 = CU_TENSOR_MAP_SWIZZLE_64B, S0 = CU_TENSOR_MAP_SWIZZLE_NONE;
    Maps mp;
    make_map2(enc, &mp.x[0], x0, D_, S_, 64, 128, S128); make_map2(enc, &mp.x[1], p_x1, D_, S_, 64, 128, S128);
    make_map2(enc, &mp.o, p_o, D_, S_, 64, 128, S128);
    {
        const cuuint64_t dims[3] = {D_, D_, 3}, strides[2] = {3 * D_ * 2, D_ * 2};
        const cuuint32_t box[3] = {64, 64, 3};
        make_map(enc, &mp.wqkv, wqkv, 3, dims, strides, box, S128);
    }
    make_map2(enc, &mp.r, wqkv, 3 * D_, D_, 24, 256, S0);
    make_map2(enc, &mp.g, w_gate, FF, D_, 32, 256, S64); make_map2(enc, &mp.u, w_up, FF, D_, 32, 256, S64);
    for (int p = 0; p < 2; p++) {
        const cuuint64_t dims[5] = {D_, 2, 4, 4, 16}, strides[4] = {D_ * 2, 8 * D_ * 2, 2 * D_ * 2, 64 * D_ * 2};
        const cuuint32_t box[5] = {64, 2, 4, 4, 2};
        make_map(enc, &mp.wo[p], wo + (size_t)p * 32 * D_, 5, dims, strides, box, S128);
    }
    {
        const cuuint64_t dims[3] = {64, FF, 16}, strides[2] = {D_ * 2, 128};
        const cuuint32_t box[3] = {64, 32, 4};
        make_map(enc, &mp.d, w_down, 3, dims, strides, box, S128);
    }
    cudaFuncSetAttribute(k_all, cudaFuncAttributeMaxDynamicSharedMemorySize, K_SMEM);
    k_all<<<128, 384, K_SMEM, cudaStreamPerThread>>>(mp, x0, wo, w_down, w_r, (bf16*)d_out, desc_plain(A_RING, 2048, 128), desc_plain(A_RING + 8192, 128, 2048), 0x64A264A2u, 0u, 16u);
}
```
